```python
import torch

def _softmax(x, axis=-1):
    return torch.softmax(x, dim=axis)
def _gelu(x):
    return torch.nn.functional.gelu(x, approximate="tanh")
def _silu(x):
    return torch.nn.functional.silu(x)
def _sigmoid(x):
    return torch.sigmoid(x)
def _layernorm(x, axis=-1, eps=1e-5):
    m = x.mean(dim=axis, keepdim=True)
    v = x.var(dim=axis, keepdim=True, unbiased=False)
    return (x - m) / torch.sqrt(v + eps)
def _scatter_add(tgt, idx, src, axis=0):
    return tgt.clone().index_add_(axis, idx, src)
def _segment_sum(src, seg, n):
    out = torch.zeros((n,) + src.shape[1:], dtype=src.dtype)
    return out.index_add_(0, seg, src)
def _pad(x, pw):
    flat = tuple(v for pair in reversed(pw) for v in pair)
    return torch.nn.functional.pad(x, flat)

kernel_name = 'standalone__seq2seq_rnn_t_joint__speech'

def setup_inputs():

    _w = (lambda a: (lambda t: t.to(torch.bfloat16) if t.is_floating_point() else t)(torch.as_tensor(a)))
    B, T, D, K = 2, 4000, 256, 3
    U = 8
    sc = (1.0 / (K * D)) ** 0.5
    sd = (1.0 / D) ** 0.5
    return {
        "x": _w((lambda *s: torch.randn(*s, dtype=torch.bfloat16) * 0.2)(B, T, D) * 0.5),
        "w1": _w((lambda *s: torch.randn(*s, dtype=torch.bfloat16) * 3.2)(K, D, D) * sc),
        "w2": _w((lambda *s: torch.randn(*s, dtype=torch.bfloat16) * 3.2)(K, D, D) * sc),
        "g": _w((lambda *s: torch.randn(*s, dtype=torch.bfloat16) * 3.2)(B, U, D) * 0.5),
        "w_f": _w((lambda *s: torch.randn(*s, dtype=torch.bfloat16) * 3.2)(D, D) * sd),
        "w_g": _w((lambda *s: torch.randn(*s, dtype=torch.bfloat16) * 3.2)(D, D) * sd),
        "w_o": _w((lambda *s: torch.randn(*s, dtype=torch.bfloat16) * 3.2)(D, D) * sd),
    }

def reference(x, w1, w2, g, w_f, w_g, w_o):
    B, T, D = x.shape
    K = w1.shape[0]
    pad = K // 2
    xp = _pad(x, ((0,0),(pad,pad),(0,0)))
    h = torch.zeros_like(x)
    for i in range(K):
        h = h + torch.einsum("btc,cd->btd", xp[:, i:i+T, :], w1[i])
    h = _gelu(h)[:, ::2, :]
    T1 = h.shape[1]
    hp = _pad(h, ((0,0),(pad,pad),(0,0)))
    f = torch.zeros_like(h)
    for i in range(K):
        f = f + torch.einsum("btc,cd->btd", hp[:, i:i+T1, :], w2[i])
    f = _gelu(f)[:, ::2, :]
    fe = torch.einsum("btd,de->bte", f, w_f)
    ge = torch.einsum("bud,de->bue", g, w_g)
    j = torch.tanh(fe[:, :, None, :] + ge[:, None, :, :])
    return torch.einsum("btud,dv->btuv", j, w_o)
```

```cpp
#include <cuda_runtime.h>
#include <cuda_bf16.h>
#include <cuda.h>
#include <stdint.h>

namespace {

constexpr int kT2 = 1000;
constexpr int kR = 31;
constexpr int kTilesPerBatch = 33;
constexpr int kNumClusters = 66;
constexpr int kThreads = 384;
constexpr int kSlot = 16384;

constexpr int kSlotFE = 9, kSlotF = 10, kSlotH = 11;
constexpr int kOffG = 13 * kSlot;
constexpr int kOffGE = kOffG + 4096;
constexpr int kGEPitch = 1056;
constexpr int kOffBar = kOffGE + 8 * kGEPitch;
constexpr int kBarX = 0;
constexpr int kBarW = 4;
constexpr int kBarE = 44;
constexpr int kBarHX = 72, kBarFX = 73, kBarFE = 74;
constexpr int kNumBars = 75;
constexpr int kSmemBytes = kOffBar + kNumBars * 8 + 1024;

#define TS(slot_, idx_) do {} while (0)

__device__ __forceinline__ uint32_t smem_u32(const void* p) { return (uint32_t)__cvta_generic_to_shared(p); }
__device__ __forceinline__ void mbar_init(uint32_t a, uint32_t c) { asm volatile("mbarrier.init.shared.b64 [%0], %1;" ::"r"(a), "r"(c) : "memory"); }
__device__ __forceinline__ void mbar_expect(uint32_t a, uint32_t b) { asm volatile("mbarrier.arrive.expect_tx.shared.b64 _, [%0], %1;" ::"r"(a), "r"(b) : "memory"); }
__device__ __forceinline__ void mbar_arrive(uint32_t a) { asm volatile("mbarrier.arrive.shared.b64 _, [%0];" ::"r"(a) : "memory"); }
__device__ __forceinline__ bool mbar_try(uint32_t a) {
  uint32_t ok;
  asm volatile("{\n.reg .pred p;\nmbarrier.try_wait.parity.shared.b64 p, [%1], 0;\nselp.u32 %0, 1, 0, p;\n}\n" : "=r"(ok) : "r"(a) : "memory");
  return ok != 0;
}
__device__ __forceinline__ bool mbar_try_cluster(uint32_t a) {
  uint32_t ok;
  asm volatile("{\n.reg .pred p;\nmbarrier.try_wait.parity.acquire.cluster.shared.b64 p, [%1], 0;\nselp.u32 %0, 1, 0, p;\n}\n" : "=r"(ok) : "r"(a) : "memory");
  return ok != 0;
}
__device__ __forceinline__ void mbar_wait(uint32_t a) {
  if (mbar_try(a)) return;
  const long long t0 = clock64();
  while (!mbar_try(a)) { if (clock64() - t0 > 4000000ll) break; }
}
__device__ __forceinline__ void mbar_wait_cluster(uint32_t a) {
  if (mbar_try_cluster(a)) return;
  const long long t0 = clock64();
  while (!mbar_try_cluster(a)) { if (clock64() - t0 > 4000000ll) break; }
}
__device__ __forceinline__ uint32_t mapa(uint32_t a, uint32_t r) { uint32_t d; asm volatile("mapa.shared::cluster.u32 %0, %1, %2;" : "=r"(d) : "r"(a), "r"(r)); return d; }
__device__ __forceinline__ bool elect_one() { uint32_t p; asm volatile("{\n.reg .pred P;\nelect.sync _|P, 0xffffffff;\nselp.u32 %0, 1, 0, P;\n}\n" : "=r"(p)); return p != 0; }
__device__ __forceinline__ void fence_async_smem() { asm volatile("fence.proxy.async.shared::cta;" ::: "memory"); }
__device__ __forceinline__ void bar_consumers() { asm volatile("bar.sync 1, 256;" ::: "memory"); }
__device__ __forceinline__ void wg_fence() { asm volatile("wgmma.fence.sync.aligned;" ::: "memory"); }
__device__ __forceinline__ void wg_commit() { asm volatile("wgmma.commit_group.sync.aligned;" ::: "memory"); }
template <int N> __device__ __forceinline__ void wg_wait() { asm volatile("wgmma.wait_group.sync.aligned %0;" ::"n"(N) : "memory"); }

__device__ __forceinline__ void tma_load_3d(uint32_t dst, const CUtensorMap* tm, uint32_t bar, int c0, int c1, int c2) {
  asm volatile("cp.async.bulk.tensor.3d.shared::cluster.global.mbarrier::complete_tx::bytes [%0], [%1, {%3, %4, %5}], [%2];"
               ::"r"(dst), "l"(tm), "r"(bar), "r"(c0), "r"(c1), "r"(c2) : "memory");
}
__device__ __forceinline__ void tma_load_4d_mc(uint32_t dst, const CUtensorMap* tm, uint32_t bar, int c0, int c1, int c2, int c3, uint16_t mask) {
  asm volatile("cp.async.bulk.tensor.4d.shared::cluster.global.mbarrier::complete_tx::bytes.multicast::cluster [%0], [%1, {%3, %4, %5, %6}], [%2], %7;"
               ::"r"(dst), "l"(tm), "r"(bar), "r"(c0), "r"(c1), "r"(c2), "r"(c3), "h"(mask) : "memory");
}
__device__ __forceinline__ void tma_store_3d(const CUtensorMap* tm, uint32_t src, int c0, int c1, int c2) {
  asm volatile("cp.async.bulk.tensor.3d.global.shared::cta.bulk_group [%0, {%2, %3, %4}], [%1];"
               ::"l"(tm), "r"(src), "r"(c0), "r"(c1), "r"(c2) : "memory");
}
__device__ __forceinline__ void dsmem_copy(uint32_t dst_remote, uint32_t src, uint32_t bytes, uint32_t bar_remote) {
  asm volatile("cp.async.bulk.shared::cluster.shared::cta.mbarrier::complete_tx::bytes [%0], [%1], %2, [%3];"
               ::"r"(dst_remote), "r"(src), "r"(bytes), "r"(bar_remote) : "memory");
}
__device__ __forceinline__ void st_async_v2(uint32_t dst, float a, float b, uint32_t bar) {
  asm volatile("st.async.shared::cluster.mbarrier::complete_tx::bytes.v2.f32 [%0], {%1, %2}, [%3];" ::"r"(dst), "f"(a), "f"(b), "r"(bar) : "memory");
}
__device__ __forceinline__ void st_async_f32(uint32_t dst, float a, uint32_t bar) {
  asm volatile("st.async.shared::cluster.mbarrier::complete_tx::bytes.f32 [%0], %1, [%2];" ::"r"(dst), "f"(a), "r"(bar) : "memory");
}
__device__ __forceinline__ void stsm_x4_trans(uint32_t addr, uint32_t r0, uint32_t r1, uint32_t r2, uint32_t r3) {
  asm volatile("stmatrix.sync.aligned.m8n8.x4.trans.shared.b16 [%0], {%1, %2, %3, %4};" ::"r"(addr), "r"(r0), "r"(r1), "r"(r2), "r"(r3) : "memory");
}
__device__ __forceinline__ void stsm_x4(uint32_t addr, uint32_t r0, uint32_t r1, uint32_t r2, uint32_t r3) {
  asm volatile("stmatrix.sync.aligned.m8n8.x4.shared.b16 [%0], {%1, %2, %3, %4};" ::"r"(addr), "r"(r0), "r"(r1), "r"(r2), "r"(r3) : "memory");
}
__device__ __forceinline__ float2 lds64(uint32_t a) { float2 v; asm volatile("ld.shared.v2.f32 {%0, %1}, [%2];" : "=f"(v.x), "=f"(v.y) : "r"(a) : "memory"); return v; }
__device__ __forceinline__ float tanh_fast(float x) { float y; asm("tanh.approx.f32 %0, %1;" : "=f"(y) : "f"(x)); return y; }
__device__ __forceinline__ uint32_t pack_bf16(float lo, float hi) { uint32_t r; asm("cvt.rn.bf16x2.f32 %0, %1, %2;" : "=r"(r) : "f"(hi), "f"(lo)); return r; }
__device__ __forceinline__ float gelu_tanh(float x) {
  const float k0 = 0.7978845608028654f, k1 = 0.7978845608028654f * 0.044715f;
  float u = x * fmaf(x * x, k1, k0);
  float hx = 0.5f * x;
  return fmaf(hx, tanh_fast(u), hx);
}
__device__ __forceinline__ uint64_t make_desc(uint32_t addr, uint32_t lbo, uint32_t sbo) {
  return (uint64_t)((addr & 0x3FFFF) >> 4) | ((uint64_t)(lbo >> 4) << 16) | ((uint64_t)(sbo >> 4) << 32) | ((uint64_t)1 << 62);
}

__device__ __forceinline__ void wgmma_ss_n64(float (&d)[32], uint64_t da, uint64_t db, int scale_d) {
  asm volatile("{\n.reg .pred p;\nsetp.ne.b32 p, %34, 0;\n"
    "wgmma.mma_async.sync.aligned.m64n64k16.f32.bf16.bf16 {%0, %1, %2, %3, %4, %5, %6, %7, %8, %9, %10, %11, %12, %13, %14, %15, %16, %17, %18, %19, %20, %21, %22, %23, %24, %25, %26, %27, %28, %29, %30, %31}, %32, %33, p, 1, 1, 1, 0;\n}\n"
    : "+f"(d[0]), "+f"(d[1]), "+f"(d[2]), "+f"(d[3]), "+f"(d[4]), "+f"(d[5]), "+f"(d[6]), "+f"(d[7]), "+f"(d[8]), "+f"(d[9]), "+f"(d[10]), "+f"(d[11]), "+f"(d[12]), "+f"(d[13]), "+f"(d[14]), "+f"(d[15]), "+f"(d[16]), "+f"(d[17]), "+f"(d[18]), "+f"(d[19]), "+f"(d[20]), "+f"(d[21]), "+f"(d[22]), "+f"(d[23]), "+f"(d[24]), "+f"(d[25]), "+f"(d[26]), "+f"(d[27]), "+f"(d[28]), "+f"(d[29]), "+f"(d[30]), "+f"(d[31])
    : "l"(da), "l"(db), "r"(scale_d));
}

__device__ __forceinline__ void wgmma_ss_n32(float (&d)[16], uint64_t da, uint64_t db, int scale_d) {
  asm volatile("{\n.reg .pred p;\nsetp.ne.b32 p, %18, 0;\n"
    "wgmma.mma_async.sync.aligned.m64n32k16.f32.bf16.bf16 {%0, %1, %2, %3, %4, %5, %6, %7, %8, %9, %10, %11, %12, %13, %14, %15}, %16, %17, p, 1, 1, 1, 0;\n}\n"
    : "+f"(d[0]), "+f"(d[1]), "+f"(d[2]), "+f"(d[3]), "+f"(d[4]), "+f"(d[5]), "+f"(d[6]), "+f"(d[7]), "+f"(d[8]), "+f"(d[9]), "+f"(d[10]), "+f"(d[11]), "+f"(d[12]), "+f"(d[13]), "+f"(d[14]), "+f"(d[15])
    : "l"(da), "l"(db), "r"(scale_d));
}

__device__ __forceinline__ void wgmma_ss_n8(float (&d)[4], uint64_t da, uint64_t db, int scale_d) {
  asm volatile("{\n.reg .pred p;\nsetp.ne.b32 p, %6, 0;\n"
    "wgmma.mma_async.sync.aligned.m64n8k16.f32.bf16.bf16 {%0, %1, %2, %3}, %4, %5, p, 1, 1, 1, 0;\n}\n"
    : "+f"(d[0]), "+f"(d[1]), "+f"(d[2]), "+f"(d[3])
    : "l"(da), "l"(db), "r"(scale_d));
}

__device__ __forceinline__ void wgmma_rs_n128(float (&d)[64], uint32_t a0, uint32_t a1, uint32_t a2, uint32_t a3, uint64_t db, int scale_d) {
  asm volatile("{\n.reg .pred p;\nsetp.ne.b32 p, %69, 0;\n"
    "wgmma.mma_async.sync.aligned.m64n128k16.f32.bf16.bf16 {%0, %1, %2, %3, %4, %5, %6, %7, %8, %9, %10, %11, %12, %13, %14, %15, %16, %17, %18, %19, %20, %21, %22, %23, %24, %25, %26, %27, %28, %29, %30, %31, %32, %33, %34, %35, %36, %37, %38, %39, %40, %41, %42, %43, %44, %45, %46, %47, %48, %49, %50, %51, %52, %53, %54, %55, %56, %57, %58, %59, %60, %61, %62, %63}, {%64, %65, %66, %67}, %68, p, 1, 1, 1;\n}\n"
    : "+f"(d[0]), "+f"(d[1]), "+f"(d[2]), "+f"(d[3]), "+f"(d[4]), "+f"(d[5]), "+f"(d[6]), "+f"(d[7]), "+f"(d[8]), "+f"(d[9]), "+f"(d[10]), "+f"(d[11]), "+f"(d[12]), "+f"(d[13]), "+f"(d[14]), "+f"(d[15]), "+f"(d[16]), "+f"(d[17]), "+f"(d[18]), "+f"(d[19]), "+f"(d[20]), "+f"(d[21]), "+f"(d[22]), "+f"(d[23]), "+f"(d[24]), "+f"(d[25]), "+f"(d[26]), "+f"(d[27]), "+f"(d[28]), "+f"(d[29]), "+f"(d[30]), "+f"(d[31]), "+f"(d[32]), "+f"(d[33]), "+f"(d[34]), "+f"(d[35]), "+f"(d[36]), "+f"(d[37]), "+f"(d[38]), "+f"(d[39]), "+f"(d[40]), "+f"(d[41]), "+f"(d[42]), "+f"(d[43]), "+f"(d[44]), "+f"(d[45]), "+f"(d[46]), "+f"(d[47]), "+f"(d[48]), "+f"(d[49]), "+f"(d[50]), "+f"(d[51]), "+f"(d[52]), "+f"(d[53]), "+f"(d[54]), "+f"(d[55]), "+f"(d[56]), "+f"(d[57]), "+f"(d[58]), "+f"(d[59]), "+f"(d[60]), "+f"(d[61]), "+f"(d[62]), "+f"(d[63])
    : "r"(a0), "r"(a1), "r"(a2), "r"(a3), "l"(db), "r"(scale_d));
}

__host__ __device__ constexpr int unit_slot(int u) {
  constexpr int t[40] = {4, 5, 6, 7, 8, 4, 5, 6, 0, 7, 8, 4,  1, 5, 6, 0, 2, 7, 8, 4, 3, 1, 5, 6,
                         0, 2, 7, 8,  4, 3, 1, 5,  6, 11, 12, 0, 2, 7, 8, 10};
  return t[u];
}
__host__ __device__ constexpr int unit_wait(int u) {
  constexpr int t[40] = {-1, -1, -1, -1, -1, 0, 1, 2, 2, 3, 4, 5,  5, 6, 7, 8, 8, 9, 10, 11, 11, 12, 13, 14,
                         15, 16, 17, 18,  19, 20, 21, 22,  23, 23, 23, 24, 25, 26, 27, 27};
  return t[u];
}

struct Params {
  CUtensorMap x, w1, w2, wf, wg, wo, g, out;
};

__global__ void __cluster_dims__(2, 1, 1) __launch_bounds__(kThreads, 1)
rnnt_joint_kernel(const __grid_constant__ Params P) {
  extern __shared__ uint8_t smem_raw[];
  const uint32_t sb = (smem_u32(smem_raw) + 1023u) & ~1023u;
  const uint32_t bars = sb + kOffBar;
  const int warp = threadIdx.x >> 5, lane = threadIdx.x & 31;
  uint32_t cta;
  asm volatile("mov.u32 %0, %%cluster_ctarank;" : "=r"(cta));
  const uint32_t peer = cta ^ 1u;
  const int cl = blockIdx.x >> 1;
  const int b = cl / kTilesPerBatch;
  const int r0 = (cl - b * kTilesPerBatch) * kR;
  const int rvalid = min(kR, kT2 - r0);

  if (warp >= 8) {
    asm volatile("setmaxnreg.dec.sync.aligned.u32 40;");
    if (warp > 8) {
      asm volatile("barrier.cluster.arrive.relaxed.aligned;\nbarrier.cluster.wait.aligned;" ::: "memory");
      return;
    }
    TS(2, 0);
    for (int i = lane; i < kNumBars; i += 32) {
      const uint32_t a = bars + i * 8;
      const bool is_e = (i >= kBarE && i < kBarE + 28);
      mbar_init(a, is_e ? 8 : 1);
      if (!is_e) {
        uint32_t bytes = 16384;
        if (i == kBarW + 28) bytes = 16384 + 4096;
        if (i == kBarFX) bytes = 8192;
        if (i == kBarFE) bytes = 24576;
        mbar_expect(a, bytes);
      }
    }
    if (lane < 8) asm volatile("prefetch.tensormap [%0];" ::"l"(reinterpret_cast<const CUtensorMap*>(&P) + lane) : "memory");
    asm volatile("fence.mbarrier_init.release.cluster;" ::: "memory");
    fence_async_smem();
    __syncwarp();
    if (elect_one()) {
#pragma unroll
      for (int u = 0; u < 5; u++)
        tma_load_3d(sb + unit_slot(u) * kSlot, &P.w1, bars + (kBarW + u) * 8, 0, (u % 3) * 256 + (u / 3) * 64, 2 * cta);
    }
    __syncwarp();
    asm volatile("barrier.cluster.arrive.relaxed.aligned;\nbarrier.cluster.wait.aligned;" ::: "memory");
    TS(2, 1);
    if (elect_one()) {
      const int par = cta == 0 ? 1 : 0;
      const int q0 = cta == 0 ? 2 * r0 - 2 : 2 * r0 - 1;
#pragma unroll
      for (int p = 0; p < 4; p++)
        tma_load_4d_mc(sb + p * kSlot + cta * 8192, &P.x, bars + (kBarX + p) * 8, p * 64, par, q0, b, (uint16_t)3);
    }
    __syncwarp();
#pragma unroll
    for (int u = 5; u < 40; u++) {
      if (unit_wait(u) != unit_wait(u - 1)) mbar_wait(bars + (kBarE + unit_wait(u)) * 8);
      if (u == 33) mbar_wait(bars + kBarFX * 8);
      if (u == 39) mbar_wait(bars + kBarFE * 8);
      if (elect_one()) {
        const uint32_t dst = sb + unit_slot(u) * kSlot, bar = bars + (kBarW + u) * 8;
        if (u < 12) tma_load_3d(dst, &P.w1, bar, 0, (u % 3) * 256 + (u / 3) * 64, 2 * cta);
        else if (u < 24) tma_load_3d(dst, &P.w2, bar, 0, ((u - 12) % 3) * 256 + ((2 * cta + (u - 12) / 3) & 3) * 64, 2 * cta);
        else if (u < 28) tma_load_3d(dst, &P.wf, bar, 0, ((2 * cta + (u - 24)) & 3) * 64, 2 * cta);
        else if (u < 32) {
          tma_load_3d(dst, &P.wg, bar, 0, (u - 28) * 64, 2 * cta);
          if (u == 28) tma_load_3d(sb + kOffG, &P.g, bar, 0, b * 8, 0);
        } else tma_load_3d(dst, &P.wo, bar, 0, ((u - 32) & 3) * 64, ((u - 32) >> 2) * 2);
      }
      __syncwarp();
      if (u == 11) TS(2, 2);
      if (u == 23) TS(2, 3);
      if (u == 31) TS(2, 4);
      if (u == 39) TS(2, 5);
    }
  } else {
    asm volatile("setmaxnreg.inc.sync.aligned.u32 232;");
    const int wg = warp >> 2, w = warp & 3;
    const int gq = lane >> 2, q = lane & 3;
    const uint32_t panel = 2 * cta + wg;
    asm volatile("barrier.cluster.arrive.relaxed.aligned;\nbarrier.cluster.wait.aligned;" ::: "memory");
    if (w == 0) TS(wg, 0);

    {
      float acc[32];
#pragma unroll
      for (int u = 0; u < 12; u++) {
        const int p = u / 3, tap = u % 3;
        if (tap == 0) mbar_wait(bars + (kBarX + p) * 8);
        mbar_wait(bars + (kBarW + u) * 8);
        if (u == 0 && w == 0) TS(wg, 1);
        const uint32_t a0 = sb + unit_slot(u) * kSlot + wg * 8192;
        const uint32_t b0 = sb + p * kSlot + (tap == 1 ? 8192 : (tap == 2 ? 128 : 0));
        wg_fence();
#pragma unroll
        for (int s = 0; s < 4; s++)
          wgmma_ss_n64(acc, make_desc(a0 + s * 2048, 8192, 1024), make_desc(b0 + s * 32, 16, 1024), (u | s) != 0);
        wg_commit();
        if (u > 0) {
          wg_wait<1>();
          if (lane == 0) mbar_arrive(bars + (kBarE + u - 1) * 8);
        }
      }
      wg_wait<0>();
      if (lane == 0) mbar_arrive(bars + (kBarE + 11) * 8);
      if (w == 0) TS(wg, 2);
      const uint32_t hp = sb + kSlotH * kSlot + panel * 8192;
      const int mi = lane >> 3, l8 = lane & 7;
#pragma unroll
      for (int jb = 0; jb < 8; jb += 2) {
        uint32_t r[4];
#pragma unroll
        for (int t = 0; t < 2; t++) {
          r[2 * t + 0] = pack_bf16(gelu_tanh(acc[4 * (jb + t) + 0]), gelu_tanh(acc[4 * (jb + t) + 1]));
          r[2 * t + 1] = pack_bf16(gelu_tanh(acc[4 * (jb + t) + 2]), gelu_tanh(acc[4 * (jb + t) + 3]));
        }
        const int n = 8 * (jb + (mi >> 1)) + l8;
        const int row = n >> 1, chunk = 2 * w + (mi & 1);
        stsm_x4_trans(hp + (n & 1) * 4096 + row * 128 + ((chunk ^ (row & 7)) << 4), r[0], r[1], r[2], r[3]);
      }
      fence_async_smem();
      bar_consumers();
      if (warp == 0) {
        if (elect_one()) {
          const uint32_t src = sb + kSlotH * kSlot + cta * 16384;
          dsmem_copy(mapa(src, peer), src, 16384, mapa(bars + kBarHX * 8, peer));
        }
        __syncwarp();
      }
      if (w == 0) TS(wg, 3);
    }
    {
      float acc[16];
#pragma unroll
      for (int v = 0; v < 12; v++) {
        const int i = v / 3, tap = v % 3;
        if (v == 6) { mbar_wait_cluster(bars + kBarHX * 8); if (w == 0) TS(wg, 4); }
        mbar_wait(bars + (kBarW + 12 + v) * 8);
        const uint32_t kp = (2 * cta + i) & 3;
        const uint32_t a0 = sb + unit_slot(12 + v) * kSlot + wg * 8192;
        const uint32_t b0 = sb + kSlotH * kSlot + kp * 8192 + (tap == 1 ? 4096 : (tap == 2 ? 128 : 0));
        wg_fence();
#pragma unroll
        for (int s = 0; s < 4; s++)
          wgmma_ss_n32(acc, make_desc(a0 + s * 2048, 8192, 1024), make_desc(b0 + s * 32, 16, 1024), (v | s) != 0);
        wg_commit();
        if (v > 0) {
          wg_wait<1>();
          if (lane == 0) mbar_arrive(bars + (kBarE + 12 + v - 1) * 8);
        }
      }
      wg_wait<0>();
      if (lane == 0) mbar_arrive(bars + (kBarE + 23) * 8);
      if (w == 0) TS(wg, 5);
      const uint32_t fp = sb + kSlotF * kSlot + panel * 4096;
      const int mi = lane >> 3, l8 = lane & 7;
#pragma unroll
      for (int jb = 0; jb < 4; jb += 2) {
        uint32_t r[4];
#pragma unroll
        for (int t = 0; t < 2; t++) {
          r[2 * t + 0] = pack_bf16(gelu_tanh(acc[4 * (jb + t) + 0]), gelu_tanh(acc[4 * (jb + t) + 1]));
          r[2 * t + 1] = pack_bf16(gelu_tanh(acc[4 * (jb + t) + 2]), gelu_tanh(acc[4 * (jb + t) + 3]));
        }
        const int n = 8 * (jb + (mi >> 1)) + l8;
        const int chunk = 2 * w + (mi & 1);
        stsm_x4_trans(fp + n * 128 + ((chunk ^ (n & 7)) << 4), r[0], r[1], r[2], r[3]);
      }
      fence_async_smem();
      bar_consumers();
      if (warp == 0) {
        if (elect_one()) {
          const uint32_t src = sb + kSlotF * kSlot + cta * 8192;
          dsmem_copy(mapa(src, peer), src, 8192, mapa(bars + kBarFX * 8, peer));
        }
        __syncwarp();
      }
      if (w == 0) TS(wg, 6);
    }
    {
      const int ch = panel * 64 + w * 16 + gq;
      const uint32_t fe_bar0 = mapa(bars + kBarFE * 8, 0), fe_bar1 = mapa(bars + kBarFE * 8, 1);
      float acc[16];
#pragma unroll
      for (int i = 0; i < 4; i++) {
        if (i == 2) { mbar_wait_cluster(bars + kBarFX * 8); if (w == 0) TS(wg, 7); }
        mbar_wait(bars + (kBarW + 24 + i) * 8);
        const uint32_t kp = (2 * cta + i) & 3;
        const uint32_t a0 = sb + unit_slot(24 + i) * kSlot + wg * 8192;
        const uint32_t b0 = sb + kSlotF * kSlot + kp * 4096;
        wg_fence();
#pragma unroll
        for (int s = 0; s < 4; s++)
          wgmma_ss_n32(acc, make_desc(a0 + s * 2048, 8192, 1024), make_desc(b0 + s * 32, 16, 1024), (i | s) != 0);
        wg_commit();
        if (i > 0) {
          wg_wait<1>();
          if (lane == 0) mbar_arrive(bars + (kBarE + 24 + i - 1) * 8);
        }
      }
      wg_wait<0>();
      if (lane == 0) mbar_arrive(bars + (kBarE + 27) * 8);
      if (w == 0) TS(wg, 8);
      const uint32_t fe_loc = sb + kSlotFE * kSlot;
      const uint32_t sw = ((ch >> 1) & 3) * 2;
#pragma unroll
      for (int jb = 0; jb < 4; jb++) {
        const uint32_t dstc = jb >> 1;
        const uint32_t pr = (4 * (jb & 1) + q) ^ sw;
        const uint32_t base = mapa(fe_loc, dstc);
        const uint32_t br = dstc ? fe_bar1 : fe_bar0;
        st_async_v2(base + ch * 64 + pr * 8, acc[4 * jb + 0], acc[4 * jb + 1], br);
        st_async_v2(base + (ch + 8) * 64 + pr * 8, acc[4 * jb + 2], acc[4 * jb + 3], br);
      }
      float ga[4];
#pragma unroll
      for (int i = 0; i < 4; i++) {
        mbar_wait(bars + (kBarW + 28 + i) * 8);
        const uint32_t a0 = sb + unit_slot(28 + i) * kSlot + wg * 8192;
        const uint32_t b0 = sb + kOffG + i * 1024;
        wg_fence();
#pragma unroll
        for (int s = 0; s < 4; s++)
          wgmma_ss_n8(ga, make_desc(a0 + s * 2048, 8192, 1024), make_desc(b0 + s * 32, 16, 1024), (i | s) != 0);
        wg_commit();
      }
      wg_wait<0>();
#pragma unroll
      for (int d = 0; d < 2; d++) {
        const uint32_t base = mapa(sb + kOffGE, d);
        const uint32_t br = d ? fe_bar1 : fe_bar0;
        st_async_f32(base + (2 * q) * kGEPitch + ch * 4, ga[0], br);
        st_async_f32(base + (2 * q + 1) * kGEPitch + ch * 4, ga[1], br);
        st_async_f32(base + (2 * q) * kGEPitch + (ch + 8) * 4, ga[2], br);
        st_async_f32(base + (2 * q + 1) * kGEPitch + (ch + 8) * 4, ga[3], br);
      }
      if (w == 0) TS(wg, 9);
    }
    {
      mbar_wait_cluster(bars + kBarFE * 8);
      if (w == 0) TS(wg, 10);
      const uint32_t fe_t = sb + kSlotFE * kSlot + (2 * q) * 64 + (((4 * wg + w) ^ (2 * q)) << 3);
      const uint32_t ge_t = sb + kOffGE + gq * kGEPitch + (2 * q) * 4;
      uint32_t A[64];
      float acc0[64], acc1[64];
#pragma unroll
      for (int kk = 0; kk < 16; kk++) {
        const float2 f0 = lds64(fe_t + kk * 1024), f1 = lds64(fe_t + kk * 1024 + 64);
        const float2 f2 = lds64(fe_t + kk * 1024 + 512), f3 = lds64(fe_t + kk * 1024 + 576);
        const float2 g0 = lds64(ge_t + kk * 64), g1 = lds64(ge_t + kk * 64 + 32);
        A[4 * kk + 0] = pack_bf16(tanh_fast(f0.x + g0.x), tanh_fast(f1.x + g0.y));
        A[4 * kk + 1] = pack_bf16(tanh_fast(f0.y + g0.x), tanh_fast(f1.y + g0.y));
        A[4 * kk + 2] = pack_bf16(tanh_fast(f2.x + g1.x), tanh_fast(f3.x + g1.y));
        A[4 * kk + 3] = pack_bf16(tanh_fast(f2.y + g1.x), tanh_fast(f3.y + g1.y));
        if ((kk & 3) == 0) mbar_wait(bars + (kBarW + 32 + (kk >> 2)) * 8);
        const uint32_t b0 = sb + unit_slot(32 + (kk >> 2)) * kSlot + (kk & 3) * 2048;
        wg_fence();
        wgmma_rs_n128(acc0, A[4 * kk], A[4 * kk + 1], A[4 * kk + 2], A[4 * kk + 3], make_desc(b0, 8192, 1024), kk != 0);
      }
      wg_commit();
      if (w == 0) TS(wg, 11);
#pragma unroll
      for (int kk = 0; kk < 16; kk++) {
        if ((kk & 3) == 0) mbar_wait(bars + (kBarW + 36 + (kk >> 2)) * 8);
        const uint32_t b0 = sb + unit_slot(36 + (kk >> 2)) * kSlot + (kk & 3) * 2048;
        if ((kk & 3) == 0) wg_fence();
        wgmma_rs_n128(acc1, A[4 * kk], A[4 * kk + 1], A[4 * kk + 2], A[4 * kk + 3], make_desc(b0, 8192, 1024), kk != 0);
      }
      wg_commit();
      const int mi = lane >> 3, l8 = lane & 7;
      const int rl = cta * 16 + wg * 8 + 2 * w;
      const int grow = ((b * kT2 + r0 + rl) * 8);
      {
        wg_wait<1>();
        if (w == 0) TS(wg, 12);
        const uint32_t st = sb + (wg ? 1 : 4) * kSlot + w * 4096;
#pragma unroll
        for (int jb = 0; jb < 16; jb += 2) {
          const uint32_t r0_ = pack_bf16(acc0[4 * jb + 0], acc0[4 * jb + 1]), r1_ = pack_bf16(acc0[4 * jb + 2], acc0[4 * jb + 3]);
          const uint32_t r2_ = pack_bf16(acc0[4 * jb + 4], acc0[4 * jb + 5]), r3_ = pack_bf16(acc0[4 * jb + 6], acc0[4 * jb + 7]);
          const int jj = jb + (mi >> 1);
          stsm_x4(st + (mi & 1) * 2048 + (jj >> 3) * 1024 + l8 * 128 + (((jj & 7) ^ l8) << 4), r0_, r1_, r2_, r3_);
        }
        fence_async_smem();
        __syncwarp();
        if (elect_one()) {
          if (rl < rvalid) tma_store_3d(&P.out, st, 0, grow, 0);
          if (rl + 1 < rvalid) tma_store_3d(&P.out, st + 2048, 0, grow + 8, 0);
          asm volatile("cp.async.bulk.commit_group;" ::: "memory");
        }
        __syncwarp();
      }
      {
        wg_wait<0>();
        if (w == 0) TS(wg, 13);
        const uint32_t st = sb + (wg ? 5 : 3) * kSlot + w * 4096;
#pragma unroll
        for (int jb = 0; jb < 16; jb += 2) {
          const uint32_t r0_ = pack_bf16(acc1[4 * jb + 0], acc1[4 * jb + 1]), r1_ = pack_bf16(acc1[4 * jb + 2], acc1[4 * jb + 3]);
          const uint32_t r2_ = pack_bf16(acc1[4 * jb + 4], acc1[4 * jb + 5]), r3_ = pack_bf16(acc1[4 * jb + 6], acc1[4 * jb + 7]);
          const int jj = jb + (mi >> 1);
          stsm_x4(st + (mi & 1) * 2048 + (jj >> 3) * 1024 + l8 * 128 + (((jj & 7) ^ l8) << 4), r0_, r1_, r2_, r3_);
        }
        fence_async_smem();
        __syncwarp();
        if (elect_one()) {
          if (rl < rvalid) tma_store_3d(&P.out, st, 0, grow, 2);
          if (rl + 1 < rvalid) tma_store_3d(&P.out, st + 2048, 0, grow + 8, 2);
          asm volatile("cp.async.bulk.commit_group;" ::: "memory");
          asm volatile("cp.async.bulk.wait_group.read 0;" ::: "memory");
        }
        __syncwarp();
      }
      if (w == 0) TS(wg, 14);
    }
  }
}

typedef CUresult (*EncodeFn)(CUtensorMap*, CUtensorMapDataType, cuuint32_t, void*, const cuuint64_t*, const cuuint64_t*,
                             const cuuint32_t*, const cuuint32_t*, CUtensorMapInterleave, CUtensorMapSwizzle,
                             CUtensorMapL2promotion, CUtensorMapFloatOOBfill);

void make_map3(EncodeFn enc, CUtensorMap* tm, const void* ptr, uint64_t rows, uint32_t box_rows, uint32_t box_panels) {
  cuuint64_t gd[3] = {64, rows, 4};
  cuuint64_t gs[2] = {512, 128};
  cuuint32_t bd[3] = {64, box_rows, box_panels};
  cuuint32_t es[3] = {1, 1, 1};
  enc(tm, CU_TENSOR_MAP_DATA_TYPE_BFLOAT16, 3, const_cast<void*>(ptr), gd, gs, bd, es, CU_TENSOR_MAP_INTERLEAVE_NONE,
      CU_TENSOR_MAP_SWIZZLE_128B, CU_TENSOR_MAP_L2_PROMOTION_L2_256B, CU_TENSOR_MAP_FLOAT_OOB_FILL_NONE);
}

}

extern "C" void kernel_launch(void* const* d_in, const int* in_sizes, int n_in, void* d_out, int out_size) {
  static EncodeFn enc = nullptr;
  if (!enc) {
    cudaDriverEntryPointQueryResult qr;
    cudaGetDriverEntryPoint("cuTensorMapEncodeTiled", (void**)&enc, cudaEnableDefault, &qr);
    cudaFuncSetAttribute(rnnt_joint_kernel, cudaFuncAttributeMaxDynamicSharedMemorySize, kSmemBytes);
  }
  Params P;
  {
    cuuint64_t gd[4] = {256, 2, 2000, 2};
    cuuint64_t gs[3] = {512, 1024, 4000ull * 512};
    cuuint32_t bd[4] = {64, 1, 64, 1};
    cuuint32_t es[4] = {1, 1, 1, 1};
    enc(&P.x, CU_TENSOR_MAP_DATA_TYPE_BFLOAT16, 4, d_in[0], gd, gs, bd, es, CU_TENSOR_MAP_INTERLEAVE_NONE,
        CU_TENSOR_MAP_SWIZZLE_128B, CU_TENSOR_MAP_L2_PROMOTION_L2_256B, CU_TENSOR_MAP_FLOAT_OOB_FILL_NONE);
  }
  make_map3(enc, &P.w1, d_in[1], 768, 64, 2);
  make_map3(enc, &P.w2, d_in[2], 768, 64, 2);
  make_map3(enc, &P.g, d_in[3], 16, 8, 4);
  make_map3(enc, &P.wf, d_in[4], 256, 64, 2);
  make_map3(enc, &P.wg, d_in[5], 256, 64, 2);
  make_map3(enc, &P.wo, d_in[6], 256, 64, 2);
  make_map3(enc, &P.out, d_out, 16000, 8, 2);
  rnnt_joint_kernel<<<kNumClusters * 2, kThreads, kSmemBytes>>>(P);
}
```

```cpp
#include <cuda_runtime.h>
#include <cuda_bf16.h>
#include <cuda.h>
#include <stdint.h>

namespace {

constexpr int kT2 = 1000;
constexpr int kR = 31;
constexpr int kNumCtas = 132;
constexpr int kThreads = 384;
constexpr int kSlot = 16384;

constexpr int kSlotFE = 9, kSlotF = 10, kSlotH = 11;
constexpr int kOffG = 13 * kSlot;
constexpr int kOffGE = kOffG + 4096;
constexpr int kGEPitch = 1056;
constexpr int kGEBytes = 8 * kGEPitch;
constexpr int kOffBar = kOffGE + kGEBytes;
constexpr int kBarX = 0;
constexpr int kBarW = 4;
constexpr int kBarE = 40;
constexpr int kBarHX = 67, kBarFX = 68, kBarFE = 69, kBarG = 70, kBarP0 = 71;
constexpr int kNumBars = 72;
constexpr int kSmemBytes = kOffBar + kNumBars * 8 + 1024;

__device__ float g_ge[2 * kGEBytes / 4];
__device__ unsigned int g_ge_flag[2];
__device__ unsigned int g_cta_count;

#define TS(slot_, idx_) do {} while (0)

__device__ __forceinline__ uint32_t smem_u32(const void* p) { return (uint32_t)__cvta_generic_to_shared(p); }
__device__ __forceinline__ void mbar_init(uint32_t a, uint32_t c) { asm volatile("mbarrier.init.shared.b64 [%0], %1;" ::"r"(a), "r"(c) : "memory"); }
__device__ __forceinline__ void mbar_expect(uint32_t a, uint32_t b) { asm volatile("mbarrier.arrive.expect_tx.shared.b64 _, [%0], %1;" ::"r"(a), "r"(b) : "memory"); }
__device__ __forceinline__ void mbar_arrive(uint32_t a) { asm volatile("mbarrier.arrive.shared.b64 _, [%0];" ::"r"(a) : "memory"); }
__device__ __forceinline__ bool mbar_try(uint32_t a) {
  uint32_t ok;
  asm volatile("{\n.reg .pred p;\nmbarrier.try_wait.parity.shared.b64 p, [%1], 0;\nselp.u32 %0, 1, 0, p;\n}\n" : "=r"(ok) : "r"(a) : "memory");
  return ok != 0;
}
__device__ __forceinline__ bool mbar_try_cluster(uint32_t a) {
  uint32_t ok;
  asm volatile("{\n.reg .pred p;\nmbarrier.try_wait.parity.acquire.cluster.shared.b64 p, [%1], 0;\nselp.u32 %0, 1, 0, p;\n}\n" : "=r"(ok) : "r"(a) : "memory");
  return ok != 0;
}
__device__ __forceinline__ void mbar_wait_slow(uint32_t a) {
  const long long t0 = clock64();
  while (!mbar_try(a)) { if (clock64() - t0 > 4000000ll) break; }
}
__device__ __forceinline__ void mbar_wait_cluster_slow(uint32_t a) {
  const long long t0 = clock64();
  while (!mbar_try_cluster(a)) { if (clock64() - t0 > 4000000ll) break; }
}
__device__ __forceinline__ void mbar_wait(uint32_t a) { if (!mbar_try(a)) mbar_wait_slow(a); }
__device__ __forceinline__ void mbar_wait_cluster(uint32_t a) { if (!mbar_try_cluster(a)) mbar_wait_cluster_slow(a); }
__device__ __forceinline__ uint32_t mapa(uint32_t a, uint32_t r) { uint32_t d; asm volatile("mapa.shared::cluster.u32 %0, %1, %2;" : "=r"(d) : "r"(a), "r"(r)); return d; }
__device__ __forceinline__ bool elect_one() { uint32_t p; asm volatile("{\n.reg .pred P;\nelect.sync _|P, 0xffffffff;\nselp.u32 %0, 1, 0, P;\n}\n" : "=r"(p)); return p != 0; }
__device__ __forceinline__ void fence_async_smem() { asm volatile("fence.proxy.async.shared::cta;" ::: "memory"); }
__device__ __forceinline__ void bar_consumers() { asm volatile("bar.sync 1, 256;" ::: "memory"); }
__device__ __forceinline__ void bar_wg(int wg) { asm volatile("bar.sync %0, 128;" ::"r"(2 + wg) : "memory"); }
__device__ __forceinline__ void cluster_sync_relaxed() { asm volatile("barrier.cluster.arrive.relaxed.aligned;\nbarrier.cluster.wait.aligned;" ::: "memory"); }
__device__ __forceinline__ void wg_fence() { asm volatile("wgmma.fence.sync.aligned;" ::: "memory"); }
__device__ __forceinline__ void wg_commit() { asm volatile("wgmma.commit_group.sync.aligned;" ::: "memory"); }
template <int N> __device__ __forceinline__ void wg_wait() { asm volatile("wgmma.wait_group.sync.aligned %0;" ::"n"(N) : "memory"); }

__device__ __forceinline__ void tma_load_3d(uint32_t dst, const CUtensorMap* tm, uint32_t bar, int c0, int c1, int c2) {
  asm volatile("cp.async.bulk.tensor.3d.shared::cluster.global.mbarrier::complete_tx::bytes [%0], [%1, {%3, %4, %5}], [%2];"
               ::"r"(dst), "l"(tm), "r"(bar), "r"(c0), "r"(c1), "r"(c2) : "memory");
}
__device__ __forceinline__ void tma_load_4d_mc(uint32_t dst, const CUtensorMap* tm, uint32_t bar, int c0, int c1, int c2, int c3, uint16_t mask) {
  asm volatile("cp.async.bulk.tensor.4d.shared::cluster.global.mbarrier::complete_tx::bytes.multicast::cluster [%0], [%1, {%3, %4, %5, %6}], [%2], %7;"
               ::"r"(dst), "l"(tm), "r"(bar), "r"(c0), "r"(c1), "r"(c2), "r"(c3), "h"(mask) : "memory");
}
__device__ __forceinline__ void tma_store_3d(const CUtensorMap* tm, uint32_t src, int c0, int c1, int c2) {
  asm volatile("cp.async.bulk.tensor.3d.global.shared::cta.bulk_group [%0, {%2, %3, %4}], [%1];"
               ::"l"(tm), "r"(src), "r"(c0), "r"(c1), "r"(c2) : "memory");
}
__device__ __forceinline__ void bulk_load(uint32_t dst, const void* src, uint32_t bytes, uint32_t bar) {
  asm volatile("cp.async.bulk.shared::cluster.global.mbarrier::complete_tx::bytes [%0], [%1], %2, [%3];"
               ::"r"(dst), "l"(src), "r"(bytes), "r"(bar) : "memory");
}
__device__ __forceinline__ void dsmem_copy(uint32_t dst_remote, uint32_t src, uint32_t bytes, uint32_t bar_remote) {
  asm volatile("cp.async.bulk.shared::cluster.shared::cta.mbarrier::complete_tx::bytes [%0], [%1], %2, [%3];"
               ::"r"(dst_remote), "r"(src), "r"(bytes), "r"(bar_remote) : "memory");
}
__device__ __forceinline__ void stsm_x4_trans(uint32_t addr, uint32_t r0, uint32_t r1, uint32_t r2, uint32_t r3) {
  asm volatile("stmatrix.sync.aligned.m8n8.x4.trans.shared.b16 [%0], {%1, %2, %3, %4};" ::"r"(addr), "r"(r0), "r"(r1), "r"(r2), "r"(r3) : "memory");
}
__device__ __forceinline__ void stsm_x4(uint32_t addr, uint32_t r0, uint32_t r1, uint32_t r2, uint32_t r3) {
  asm volatile("stmatrix.sync.aligned.m8n8.x4.shared.b16 [%0], {%1, %2, %3, %4};" ::"r"(addr), "r"(r0), "r"(r1), "r"(r2), "r"(r3) : "memory");
}
__device__ __forceinline__ float2 lds64(uint32_t a) { float2 v; asm volatile("ld.shared.v2.f32 {%0, %1}, [%2];" : "=f"(v.x), "=f"(v.y) : "r"(a) : "memory"); return v; }
__device__ __forceinline__ void sts64(uint32_t a, float x, float y) { asm volatile("st.shared.v2.f32 [%0], {%1, %2};" ::"r"(a), "f"(x), "f"(y) : "memory"); }
__device__ __forceinline__ float tanh_fast(float x) { float y; asm("tanh.approx.f32 %0, %1;" : "=f"(y) : "f"(x)); return y; }
__device__ __forceinline__ uint32_t pack_bf16(float lo, float hi) { uint32_t r; asm("cvt.rn.bf16x2.f32 %0, %1, %2;" : "=r"(r) : "f"(hi), "f"(lo)); return r; }
__device__ __forceinline__ float gelu_tanh(float x) {
  const float k0 = 0.7978845608028654f, k1 = 0.7978845608028654f * 0.044715f;
  float u = x * fmaf(x * x, k1, k0);
  float hx = 0.5f * x;
  return fmaf(hx, tanh_fast(u), hx);
}
__device__ __forceinline__ uint64_t make_desc(uint32_t addr, uint32_t lbo, uint32_t sbo) {
  return (uint64_t)((addr & 0x3FFFF) >> 4) | ((uint64_t)(lbo >> 4) << 16) | ((uint64_t)(sbo >> 4) << 32) | ((uint64_t)1 << 62);
}

__device__ __forceinline__ void wgmma_ss_n64(float (&d)[32], uint64_t da, uint64_t db, int scale_d) {
  asm volatile("{\n.reg .pred p;\nsetp.ne.b32 p, %34, 0;\n"
    "wgmma.mma_async.sync.aligned.m64n64k16.f32.bf16.bf16 {%0, %1, %2, %3, %4, %5, %6, %7, %8, %9, %10, %11, %12, %13, %14, %15, %16, %17, %18, %19, %20, %21, %22, %23, %24, %25, %26, %27, %28, %29, %30, %31}, %32, %33, p, 1, 1, 1, 0;\n}\n"
    : "+f"(d[0]), "+f"(d[1]), "+f"(d[2]), "+f"(d[3]), "+f"(d[4]), "+f"(d[5]), "+f"(d[6]), "+f"(d[7]), "+f"(d[8]), "+f"(d[9]), "+f"(d[10]), "+f"(d[11]), "+f"(d[12]), "+f"(d[13]), "+f"(d[14]), "+f"(d[15]), "+f"(d[16]), "+f"(d[17]), "+f"(d[18]), "+f"(d[19]), "+f"(d[20]), "+f"(d[21]), "+f"(d[22]), "+f"(d[23]), "+f"(d[24]), "+f"(d[25]), "+f"(d[26]), "+f"(d[27]), "+f"(d[28]), "+f"(d[29]), "+f"(d[30]), "+f"(d[31])
    : "l"(da), "l"(db), "r"(scale_d));
}

__device__ __forceinline__ void wgmma_ss_n32(float (&d)[16], uint64_t da, uint64_t db, int scale_d) {
  asm volatile("{\n.reg .pred p;\nsetp.ne.b32 p, %18, 0;\n"
    "wgmma.mma_async.sync.aligned.m64n32k16.f32.bf16.bf16 {%0, %1, %2, %3, %4, %5, %6, %7, %8, %9, %10, %11, %12, %13, %14, %15}, %16, %17, p, 1, 1, 1, 0;\n}\n"
    : "+f"(d[0]), "+f"(d[1]), "+f"(d[2]), "+f"(d[3]), "+f"(d[4]), "+f"(d[5]), "+f"(d[6]), "+f"(d[7]), "+f"(d[8]), "+f"(d[9]), "+f"(d[10]), "+f"(d[11]), "+f"(d[12]), "+f"(d[13]), "+f"(d[14]), "+f"(d[15])
    : "l"(da), "l"(db), "r"(scale_d));
}

__device__ __forceinline__ void wgmma_ss_n8(float (&d)[4], uint64_t da, uint64_t db, int scale_d) {
  asm volatile("{\n.reg .pred p;\nsetp.ne.b32 p, %6, 0;\n"
    "wgmma.mma_async.sync.aligned.m64n8k16.f32.bf16.bf16 {%0, %1, %2, %3}, %4, %5, p, 1, 1, 1, 0;\n}\n"
    : "+f"(d[0]), "+f"(d[1]), "+f"(d[2]), "+f"(d[3])
    : "l"(da), "l"(db), "r"(scale_d));
}

__device__ __forceinline__ void wgmma_rs_n128(float (&d)[64], uint32_t a0, uint32_t a1, uint32_t a2, uint32_t a3, uint64_t db, int scale_d) {
  asm volatile("{\n.reg .pred p;\nsetp.ne.b32 p, %69, 0;\n"
    "wgmma.mma_async.sync.aligned.m64n128k16.f32.bf16.bf16 {%0, %1, %2, %3, %4, %5, %6, %7, %8, %9, %10, %11, %12, %13, %14, %15, %16, %17, %18, %19, %20, %21, %22, %23, %24, %25, %26, %27, %28, %29, %30, %31, %32, %33, %34, %35, %36, %37, %38, %39, %40, %41, %42, %43, %44, %45, %46, %47, %48, %49, %50, %51, %52, %53, %54, %55, %56, %57, %58, %59, %60, %61, %62, %63}, {%64, %65, %66, %67}, %68, p, 1, 1, 1;\n}\n"
    : "+f"(d[0]), "+f"(d[1]), "+f"(d[2]), "+f"(d[3]), "+f"(d[4]), "+f"(d[5]), "+f"(d[6]), "+f"(d[7]), "+f"(d[8]), "+f"(d[9]), "+f"(d[10]), "+f"(d[11]), "+f"(d[12]), "+f"(d[13]), "+f"(d[14]), "+f"(d[15]), "+f"(d[16]), "+f"(d[17]), "+f"(d[18]), "+f"(d[19]), "+f"(d[20]), "+f"(d[21]), "+f"(d[22]), "+f"(d[23]), "+f"(d[24]), "+f"(d[25]), "+f"(d[26]), "+f"(d[27]), "+f"(d[28]), "+f"(d[29]), "+f"(d[30]), "+f"(d[31]), "+f"(d[32]), "+f"(d[33]), "+f"(d[34]), "+f"(d[35]), "+f"(d[36]), "+f"(d[37]), "+f"(d[38]), "+f"(d[39]), "+f"(d[40]), "+f"(d[41]), "+f"(d[42]), "+f"(d[43]), "+f"(d[44]), "+f"(d[45]), "+f"(d[46]), "+f"(d[47]), "+f"(d[48]), "+f"(d[49]), "+f"(d[50]), "+f"(d[51]), "+f"(d[52]), "+f"(d[53]), "+f"(d[54]), "+f"(d[55]), "+f"(d[56]), "+f"(d[57]), "+f"(d[58]), "+f"(d[59]), "+f"(d[60]), "+f"(d[61]), "+f"(d[62]), "+f"(d[63])
    : "r"(a0), "r"(a1), "r"(a2), "r"(a3), "l"(db), "r"(scale_d));
}

__host__ __device__ constexpr int unit_slot(int u) {
  constexpr int t[36] = {4, 5, 6, 7, 8, 4, 5, 6, 0, 7, 8, 4,  1, 5, 6, 0, 2, 7, 8, 4, 3, 1, 5, 6,
                         0, 2, 7, 8,  4, 3, 1, 5, 6, 0, 2, 7};
  return t[u];
}
__host__ __device__ constexpr int unit_wait(int u) {
  constexpr int t[36] = {-1, -1, -1, -1, -1, 0, 1, 2, 2, 3, 4, 5,  5, 6, 7, 8, 8, 9, 10, 11, 11, 12, 13, 14,
                         15, 16, 17, 18,  19, 20, 21, 22, 23, 24, 25, 26};
  return t[u];
}

struct Params {
  CUtensorMap x, w1, w2, wf, wg, wo, g, out64, out56;
};

__device__ __forceinline__ void init_bar(uint32_t bars, int i) {
  const uint32_t a = bars + i * 8;
  const bool is_e = (i >= kBarE && i < kBarE + 27);
  mbar_init(a, is_e ? 8 : (i == kBarFE ? 9 : 1));
  if (!is_e) {
    uint32_t bytes = 16384;
    if (i == kBarFX) bytes = 8192;
    if (i == kBarFE) bytes = 8192 + kGEBytes;
    mbar_expect(a, bytes);
  }
}

__global__ void __cluster_dims__(2, 1, 1) __launch_bounds__(kThreads, 1)
rnnt_joint_kernel(const __grid_constant__ Params P) {
  extern __shared__ uint8_t smem_raw[];
  const uint32_t sb = (smem_u32(smem_raw) + 1023u) & ~1023u;
  const uint32_t bars = sb + kOffBar;
  const int warp = threadIdx.x >> 5, lane = threadIdx.x & 31;
  uint32_t cta;
  asm volatile("mov.u32 %0, %%cluster_ctarank;" : "=r"(cta));
  const uint32_t peer = cta ^ 1u;
  const int cl = blockIdx.x >> 1;
  const bool ge_cta = cl < 2;
  const int b = ge_cta ? cl : ((cl - 2) >> 5);
  const int r0 = ge_cta ? 32 * kR : ((cl - 2) & 31) * kR;
  const int rvalid = ge_cta ? kT2 - 32 * kR : kR;

  if (warp >= 8) {
    asm volatile("setmaxnreg.dec.sync.aligned.u32 40;");
    if (warp > 8) {
      if (elect_one()) {
#pragma unroll
        for (int i = 0; i < 6; i++) if (9 + (warp - 1) * 6 + i < kBarG) init_bar(bars, 9 + (warp - 1) * 6 + i);
        asm volatile("fence.mbarrier_init.release.cluster;" ::: "memory");
      }
      __syncwarp();
      cluster_sync_relaxed();
      return;
    }
    TS(2, 0);
    unsigned int ticket = 0;
    if (elect_one()) {
#pragma unroll
      for (int i = 0; i < 9; i++) { mbar_init(bars + i * 8, 1); mbar_expect(bars + i * 8, 16384); }
      if (ge_cta) { mbar_init(bars + kBarG * 8, 1); mbar_expect(bars + kBarG * 8, 4 * 16384 + 4096); mbar_init(bars + kBarP0 * 8, 8); }
      asm volatile("fence.mbarrier_init.release.cluster;" ::: "memory");
      fence_async_smem();
      if (ge_cta) {
        tma_load_3d(sb + kOffG, &P.g, bars + kBarG * 8, 0, b * 8, 0);
#pragma unroll
        for (int i = 0; i < 4; i++) tma_load_3d(sb + (9 + i) * kSlot, &P.wg, bars + kBarG * 8, 0, i * 64, 2 * cta);
      }
#pragma unroll
      for (int u = 0; u < 5; u++)
        tma_load_3d(sb + unit_slot(u) * kSlot, &P.w1, bars + (kBarW + u) * 8, 0, (u % 3) * 256 + (u / 3) * 64, 2 * cta);
    }
    __syncwarp();
    if (lane == 0) ticket = atomicAdd(&g_cta_count, 1u);
    TS(2, 6);
    cluster_sync_relaxed();
    TS(2, 1);
    const int par = cta == 0 ? 1 : 0;
    const int q0 = cta == 0 ? 2 * r0 - 2 : 2 * r0 - 1;
    if (elect_one()) {
#pragma unroll
      for (int p = 0; p < 2; p++)
        tma_load_4d_mc(sb + p * kSlot + cta * 8192, &P.x, bars + (kBarX + p) * 8, p * 64, par, q0, b, (uint16_t)3);
    }
    __syncwarp();
    mbar_wait(bars + kBarX * 8);
    if (ge_cta) mbar_wait(bars + kBarP0 * 8);
    if (elect_one()) {
#pragma unroll
      for (int p = 2; p < 4; p++)
        tma_load_4d_mc(sb + p * kSlot + cta * 8192, &P.x, bars + (kBarX + p) * 8, p * 64, par, q0, b, (uint16_t)3);
    }
    __syncwarp();
#pragma unroll
    for (int u = 5; u < 36; u++) {
      if (unit_wait(u) != unit_wait(u - 1)) mbar_wait(bars + (kBarE + unit_wait(u)) * 8);
      if (u == 27) ticket = __shfl_sync(0xffffffffu, ticket, 0);
      if (elect_one()) {
        const uint32_t dst = sb + unit_slot(u) * kSlot, bar = bars + (kBarW + u) * 8;
        if (u < 12) tma_load_3d(dst, &P.w1, bar, 0, (u % 3) * 256 + (u / 3) * 64, 2 * cta);
        else if (u < 24) tma_load_3d(dst, &P.w2, bar, 0, ((u - 12) % 3) * 256 + ((2 * cta + (u - 12) / 3) & 3) * 64, 2 * cta);
        else if (u < 28) tma_load_3d(dst, &P.wf, bar, 0, ((2 * cta + (u - 24)) & 3) * 64, 2 * cta);
        else tma_load_3d(dst, &P.wo, bar, 0, ((u - 28) & 3) * 64, ((u - 28) >> 2) * 2);
        if (u == 27) {
          const unsigned int want = (ticket / kNumCtas + 1u) * 2u;
          const long long t0 = clock64();
          unsigned int v;
          do {
            asm volatile("ld.acquire.gpu.global.u32 %0, [%1];" : "=r"(v) : "l"(&g_ge_flag[b]) : "memory");
          } while ((int)(v - want) < 0 && clock64() - t0 < 4000000ll);
          asm volatile("fence.proxy.async;" ::: "memory");
          bulk_load(sb + kOffGE, reinterpret_cast<const char*>(g_ge) + b * kGEBytes, kGEBytes, bars + kBarFE * 8);
        }
      }
      __syncwarp();
      if (u == 11) TS(2, 2);
      if (u == 23) TS(2, 3);
      if (u == 27) TS(2, 4);
      if (u == 35) TS(2, 5);
    }
  } else {
    asm volatile("setmaxnreg.inc.sync.aligned.u32 232;");
    const int wg = warp >> 2, w = warp & 3;
    const int gq = lane >> 2, q = lane & 3;
    const uint32_t panel = 2 * cta + wg;
    const int ch = panel * 64 + w * 16 + gq;
    if (elect_one()) {
#pragma unroll
      for (int i = 0; i < 6; i++) init_bar(bars, 9 + warp * 6 + i);
      asm volatile("fence.mbarrier_init.release.cluster;" ::: "memory");
    }
    __syncwarp();
    cluster_sync_relaxed();
    if (w == 0) TS(wg, 0);

    if (ge_cta) {
      float ga[4];
      mbar_wait(bars + kBarG * 8);
      wg_fence();
#pragma unroll
      for (int i = 0; i < 4; i++) {
        const uint32_t a0 = sb + (9 + i) * kSlot + wg * 8192;
        const uint32_t b0 = sb + kOffG + i * 1024;
#pragma unroll
        for (int s = 0; s < 4; s++)
          wgmma_ss_n8(ga, make_desc(a0 + s * 2048, 8192, 1024), make_desc(b0 + s * 32, 16, 1024), (i | s) != 0);
      }
      wg_commit();
      wg_wait<0>();
      if (lane == 0) mbar_arrive(bars + kBarP0 * 8);
      float* gp = g_ge + b * (kGEBytes / 4);
      gp[(2 * q) * (kGEPitch / 4) + ch] = ga[0];
      gp[(2 * q + 1) * (kGEPitch / 4) + ch] = ga[1];
      gp[(2 * q) * (kGEPitch / 4) + ch + 8] = ga[2];
      gp[(2 * q + 1) * (kGEPitch / 4) + ch + 8] = ga[3];
      __threadfence();
      bar_consumers();
      if (threadIdx.x == 0) asm volatile("red.release.gpu.global.add.u32 [%0], 1;" ::"l"(&g_ge_flag[b]) : "memory");
    }

    {
      float acc[32];
#pragma unroll
      for (int u = 0; u < 12; u++) {
        const int p = u / 3, tap = u % 3;
        if (tap == 0) mbar_wait(bars + (kBarX + p) * 8);
        mbar_wait(bars + (kBarW + u) * 8);
        if (u == 0 && w == 0) TS(wg, 1);
        const uint32_t a0 = sb + unit_slot(u) * kSlot + wg * 8192;
        const uint32_t b0 = sb + p * kSlot + (tap == 1 ? 8192 : (tap == 2 ? 128 : 0));
        wg_fence();
#pragma unroll
        for (int s = 0; s < 4; s++)
          wgmma_ss_n64(acc, make_desc(a0 + s * 2048, 8192, 1024), make_desc(b0 + s * 32, 16, 1024), (u | s) != 0);
        wg_commit();
        if (u > 0) {
          wg_wait<1>();
          if (lane == 0) mbar_arrive(bars + (kBarE + u - 1) * 8);
        }
      }
      wg_wait<0>();
      if (lane == 0) mbar_arrive(bars + (kBarE + 11) * 8);
      if (w == 0) TS(wg, 2);
      const uint32_t hp = sb + kSlotH * kSlot + panel * 8192;
      const int mi = lane >> 3, l8 = lane & 7;
#pragma unroll
      for (int jb = 0; jb < 8; jb += 2) {
        uint32_t r[4];
#pragma unroll
        for (int t = 0; t < 2; t++) {
          r[2 * t + 0] = pack_bf16(gelu_tanh(acc[4 * (jb + t) + 0]), gelu_tanh(acc[4 * (jb + t) + 1]));
          r[2 * t + 1] = pack_bf16(gelu_tanh(acc[4 * (jb + t) + 2]), gelu_tanh(acc[4 * (jb + t) + 3]));
        }
        const int n = 8 * (jb + (mi >> 1)) + l8;
        const int row = n >> 1, chunk = 2 * w + (mi & 1);
        stsm_x4_trans(hp + (n & 1) * 4096 + row * 128 + ((chunk ^ (row & 7)) << 4), r[0], r[1], r[2], r[3]);
      }
      fence_async_smem();
      bar_consumers();
      if (warp == 0) {
        if (elect_one()) {
          const uint32_t src = sb + kSlotH * kSlot + cta * 16384;
          dsmem_copy(mapa(src, peer), src, 16384, mapa(bars + kBarHX * 8, peer));
        }
        __syncwarp();
      }
      if (w == 0) TS(wg, 3);
    }
    {
      float acc[16];
#pragma unroll
      for (int v = 0; v < 12; v++) {
        const int i = v / 3, tap = v % 3;
        if (v == 6) { mbar_wait_cluster(bars + kBarHX * 8); if (w == 0) TS(wg, 4); }
        mbar_wait(bars + (kBarW + 12 + v) * 8);
        const uint32_t kp = (2 * cta + i) & 3;
        const uint32_t a0 = sb + unit_slot(12 + v) * kSlot + wg * 8192;
        const uint32_t b0 = sb + kSlotH * kSlot + kp * 8192 + (tap == 1 ? 4096 : (tap == 2 ? 128 : 0));
        wg_fence();
#pragma unroll
        for (int s = 0; s < 4; s++)
          wgmma_ss_n32(acc, make_desc(a0 + s * 2048, 8192, 1024), make_desc(b0 + s * 32, 16, 1024), (v | s) != 0);
        wg_commit();
        if (v > 0) {
          wg_wait<1>();
          if (lane == 0) mbar_arrive(bars + (kBarE + 12 + v - 1) * 8);
        }
      }
      wg_wait<0>();
      if (lane == 0) mbar_arrive(bars + (kBarE + 23) * 8);
      if (w == 0) TS(wg, 5);
      const uint32_t fp = sb + kSlotF * kSlot + panel * 4096;
      const int mi = lane >> 3, l8 = lane & 7;
#pragma unroll
      for (int jb = 0; jb < 4; jb += 2) {
        uint32_t r[4];
#pragma unroll
        for (int t = 0; t < 2; t++) {
          r[2 * t + 0] = pack_bf16(gelu_tanh(acc[4 * (jb + t) + 0]), gelu_tanh(acc[4 * (jb + t) + 1]));
          r[2 * t + 1] = pack_bf16(gelu_tanh(acc[4 * (jb + t) + 2]), gelu_tanh(acc[4 * (jb + t) + 3]));
        }
        const int n = 8 * (jb + (mi >> 1)) + l8;
        const int chunk = 2 * w + (mi & 1);
        stsm_x4_trans(fp + n * 128 + ((chunk ^ (n & 7)) << 4), r[0], r[1], r[2], r[3]);
      }
      fence_async_smem();
      bar_consumers();
      if (warp == 0) {
        if (elect_one()) {
          const uint32_t src = sb + kSlotF * kSlot + cta * 8192;
          dsmem_copy(mapa(src, peer), src, 8192, mapa(bars + kBarFX * 8, peer));
        }
        __syncwarp();
      }
      if (w == 0) TS(wg, 6);
    }
    {
      float acc[16];
#pragma unroll
      for (int i = 0; i < 4; i++) {
        if (i == 2) { mbar_wait_cluster(bars + kBarFX * 8); if (w == 0) TS(wg, 7); }
        mbar_wait(bars + (kBarW + 24 + i) * 8);
        const uint32_t kp = (2 * cta + i) & 3;
        const uint32_t a0 = sb + unit_slot(24 + i) * kSlot + wg * 8192;
        const uint32_t b0 = sb + kSlotF * kSlot + kp * 4096;
        wg_fence();
#pragma unroll
        for (int s = 0; s < 4; s++)
          wgmma_ss_n32(acc, make_desc(a0 + s * 2048, 8192, 1024), make_desc(b0 + s * 32, 16, 1024), (i | s) != 0);
        wg_commit();
        if (i > 0) {
          wg_wait<1>();
          if (lane == 0) mbar_arrive(bars + (kBarE + 24 + i - 1) * 8);
        }
      }
      wg_wait<0>();
      if (w == 0) TS(wg, 8);
      const uint32_t sw = ((ch >> 1) & 3) * 2;
      const uint32_t own = sb + kSlotFE * kSlot + ch * 64;
      const uint32_t stg = sb + kSlotH * kSlot + (ch - (int)cta * 128) * 64;
#pragma unroll
      for (int jb = 0; jb < 4; jb++) {
        const uint32_t base = ((uint32_t)(jb >> 1) == cta) ? own : stg;
        const uint32_t pr = (4 * (jb & 1) + q) ^ sw;
        sts64(base + pr * 8, acc[4 * jb + 0], acc[4 * jb + 1]);
        sts64(base + 512 + pr * 8, acc[4 * jb + 2], acc[4 * jb + 3]);
      }
      fence_async_smem();
      bar_wg(wg);
      if (w == 0) {
        if (elect_one())
          dsmem_copy(mapa(sb + kSlotFE * kSlot + panel * 4096, peer), sb + kSlotH * kSlot + wg * 4096, 4096, mapa(bars + kBarFE * 8, peer));
        __syncwarp();
      }
      if (lane == 0) mbar_arrive(bars + kBarFE * 8);
      if (w == 0) TS(wg, 9);
    }
    const int rl0 = cta * 16 + wg * 8;
    mbar_wait_cluster(bars + kBarFE * 8);
    asm volatile("barrier.cluster.arrive.relaxed.aligned;" ::: "memory");
    if (rl0 < rvalid) {
      if (w == 0) TS(wg, 10);
      const uint32_t fe_t = sb + kSlotFE * kSlot + (2 * q) * 64 + (((4 * wg + w) ^ (2 * q)) << 3);
      const uint32_t ge_t = sb + kOffGE + gq * kGEPitch + (2 * q) * 4;
      uint32_t A[64];
      float acc0[64], acc1[64];
      float2 f0, f1, f2, f3, g0, g1;
      f0 = lds64(fe_t); f1 = lds64(fe_t + 64); f2 = lds64(fe_t + 512); f3 = lds64(fe_t + 576);
      g0 = lds64(ge_t); g1 = lds64(ge_t + 32);
#pragma unroll
      for (int kk = 0; kk < 16; kk++) {
        const float s0 = f0.x + g0.x, s1 = f1.x + g0.y, s2 = f0.y + g0.x, s3 = f1.y + g0.y;
        const float s4 = f2.x + g1.x, s5 = f3.x + g1.y, s6 = f2.y + g1.x, s7 = f3.y + g1.y;
        if (kk < 15) {
          f0 = lds64(fe_t + (kk + 1) * 1024); f1 = lds64(fe_t + (kk + 1) * 1024 + 64);
          f2 = lds64(fe_t + (kk + 1) * 1024 + 512); f3 = lds64(fe_t + (kk + 1) * 1024 + 576);
          g0 = lds64(ge_t + (kk + 1) * 64); g1 = lds64(ge_t + (kk + 1) * 64 + 32);
        }
        A[4 * kk + 0] = pack_bf16(tanh_fast(s0), tanh_fast(s1));
        A[4 * kk + 1] = pack_bf16(tanh_fast(s2), tanh_fast(s3));
        A[4 * kk + 2] = pack_bf16(tanh_fast(s4), tanh_fast(s5));
        A[4 * kk + 3] = pack_bf16(tanh_fast(s6), tanh_fast(s7));
        if ((kk & 3) == 0) mbar_wait(bars + (kBarW + 28 + (kk >> 2)) * 8);
        const uint32_t b0 = sb + unit_slot(28 + (kk >> 2)) * kSlot + (kk & 3) * 2048;
        wg_fence();
        wgmma_rs_n128(acc0, A[4 * kk], A[4 * kk + 1], A[4 * kk + 2], A[4 * kk + 3], make_desc(b0, 8192, 1024), kk != 0);
      }
      wg_commit();
      if (w == 0) TS(wg, 11);
      const int mi = lane >> 3, l8 = lane & 7;
      const bool full = rl0 + 8 <= rvalid;
      const CUtensorMap* omap = full ? &P.out64 : &P.out56;
      const int grow = (b * kT2 + r0 + rl0) * 8;
      const uint32_t st_row = (16 * w + (mi & 1) * 8 + l8) * 128;
#pragma unroll
      for (int kk = 0; kk < 8; kk++) {
        if ((kk & 3) == 0) { mbar_wait(bars + (kBarW + 32 + (kk >> 2)) * 8); wg_fence(); }
        const uint32_t b0 = sb + unit_slot(32 + (kk >> 2)) * kSlot + (kk & 3) * 2048;
        wgmma_rs_n128(acc1, A[4 * kk], A[4 * kk + 1], A[4 * kk + 2], A[4 * kk + 3], make_desc(b0, 8192, 1024), kk != 0);
      }
      wg_commit();
      {
        wg_wait<1>();
        if (w == 0) TS(wg, 12);
        const uint32_t st = sb + (wg ? 12 : 8) * kSlot;
#pragma unroll
        for (int jb = 0; jb < 16; jb += 2) {
          const uint32_t r0_ = pack_bf16(acc0[4 * jb + 0], acc0[4 * jb + 1]), r1_ = pack_bf16(acc0[4 * jb + 2], acc0[4 * jb + 3]);
          const uint32_t r2_ = pack_bf16(acc0[4 * jb + 4], acc0[4 * jb + 5]), r3_ = pack_bf16(acc0[4 * jb + 6], acc0[4 * jb + 7]);
          const int jj = jb + (mi >> 1);
          stsm_x4(st + (jj >> 3) * 8192 + st_row + (((jj & 7) ^ l8) << 4), r0_, r1_, r2_, r3_);
        }
        fence_async_smem();
        bar_wg(wg);
        if (w == 0) {
          if (elect_one()) {
            tma_store_3d(omap, st, 0, grow, 0);
            tma_store_3d(omap, st + 8192, 0, grow, 1);
            asm volatile("cp.async.bulk.commit_group;" ::: "memory");
          }
          __syncwarp();
        }
      }
#pragma unroll
      for (int kk = 8; kk < 16; kk++) {
        if ((kk & 3) == 0) { mbar_wait(bars + (kBarW + 32 + (kk >> 2)) * 8); wg_fence(); }
        const uint32_t b0 = sb + unit_slot(32 + (kk >> 2)) * kSlot + (kk & 3) * 2048;
        wgmma_rs_n128(acc1, A[4 * kk], A[4 * kk + 1], A[4 * kk + 2], A[4 * kk + 3], make_desc(b0, 8192, 1024), 1);
      }
      wg_commit();
      {
        wg_wait<0>();
        if (w == 0) TS(wg, 13);
        const uint32_t st = sb + (wg ? 12 : 8) * kSlot;
        if (w == 0) {
          if (elect_one()) asm volatile("cp.async.bulk.wait_group.read 0;" ::: "memory");
          __syncwarp();
        }
        bar_wg(wg);
#pragma unroll
        for (int jb = 0; jb < 16; jb += 2) {
          const uint32_t r0_ = pack_bf16(acc1[4 * jb + 0], acc1[4 * jb + 1]), r1_ = pack_bf16(acc1[4 * jb + 2], acc1[4 * jb + 3]);
          const uint32_t r2_ = pack_bf16(acc1[4 * jb + 4], acc1[4 * jb + 5]), r3_ = pack_bf16(acc1[4 * jb + 6], acc1[4 * jb + 7]);
          const int jj = jb + (mi >> 1);
          stsm_x4(st + (jj >> 3) * 8192 + st_row + (((jj & 7) ^ l8) << 4), r0_, r1_, r2_, r3_);
        }
        fence_async_smem();
        bar_wg(wg);
        if (w == 0) {
          if (elect_one()) {
            tma_store_3d(omap, st, 0, grow, 2);
            tma_store_3d(omap, st + 8192, 0, grow, 3);
            asm volatile("cp.async.bulk.commit_group;" ::: "memory");
            asm volatile("cp.async.bulk.wait_group.read 0;" ::: "memory");
          }
          __syncwarp();
        }
      }
      if (w == 0) TS(wg, 14);
    }
    asm volatile("barrier.cluster.wait.aligned;" ::: "memory");
  }
}

typedef CUresult (*EncodeFn)(CUtensorMap*, CUtensorMapDataType, cuuint32_t, void*, const cuuint64_t*, const cuuint64_t*,
                             const cuuint32_t*, const cuuint32_t*, CUtensorMapInterleave, CUtensorMapSwizzle,
                             CUtensorMapL2promotion, CUtensorMapFloatOOBfill);

void make_map3(EncodeFn enc, CUtensorMap* tm, const void* ptr, uint64_t rows, uint32_t box_rows, uint32_t box_panels) {
  cuuint64_t gd[3] = {64, rows, 4};
  cuuint64_t gs[2] = {512, 128};
  cuuint32_t bd[3] = {64, box_rows, box_panels};
  cuuint32_t es[3] = {1, 1, 1};
  enc(tm, CU_TENSOR_MAP_DATA_TYPE_BFLOAT16, 3, const_cast<void*>(ptr), gd, gs, bd, es, CU_TENSOR_MAP_INTERLEAVE_NONE,
      CU_TENSOR_MAP_SWIZZLE_128B, CU_TENSOR_MAP_L2_PROMOTION_L2_256B, CU_TENSOR_MAP_FLOAT_OOB_FILL_NONE);
}

}

extern "C" void kernel_launch(void* const* d_in, const int* in_sizes, int n_in, void* d_out, int out_size) {
  static EncodeFn enc = nullptr;
  if (!enc) {
    cudaDriverEntryPointQueryResult qr;
    cudaGetDriverEntryPoint("cuTensorMapEncodeTiled", (void**)&enc, cudaEnableDefault, &qr);
    cudaFuncSetAttribute(rnnt_joint_kernel, cudaFuncAttributeMaxDynamicSharedMemorySize, kSmemBytes);
  }
  Params P;
  {
    cuuint64_t gd[4] = {256, 2, 2000, 2};
    cuuint64_t gs[3] = {512, 1024, 4000ull * 512};
    cuuint32_t bd[4] = {64, 1, 64, 1};
    cuuint32_t es[4] = {1, 1, 1, 1};
    enc(&P.x, CU_TENSOR_MAP_DATA_TYPE_BFLOAT16, 4, d_in[0], gd, gs, bd, es, CU_TENSOR_MAP_INTERLEAVE_NONE,
        CU_TENSOR_MAP_SWIZZLE_128B, CU_TENSOR_MAP_L2_PROMOTION_L2_256B, CU_TENSOR_MAP_FLOAT_OOB_FILL_NONE);
  }
  make_map3(enc, &P.w1, d_in[1], 768, 64, 2);
  make_map3(enc, &P.w2, d_in[2], 768, 64, 2);
  make_map3(enc, &P.g, d_in[3], 16, 8, 4);
  make_map3(enc, &P.wf, d_in[4], 256, 64, 2);
  make_map3(enc, &P.wg, d_in[5], 256, 64, 2);
  make_map3(enc, &P.wo, d_in[6], 256, 64, 2);
  make_map3(enc, &P.out64, d_out, 16000, 64, 1);
  make_map3(enc, &P.out56, d_out, 16000, 56, 1);
  rnnt_joint_kernel<<<kNumCtas, kThreads, kSmemBytes>>>(P);
}
```

```cpp
#include <cuda_runtime.h>
#include <cuda_bf16.h>
#include <cuda.h>
#include <stdint.h>

namespace {

constexpr int kT2 = 1000;
constexpr int kR = 31;
constexpr int kNumCtas = 132;
constexpr int kThreads = 384;
constexpr int kSlot = 16384;

constexpr int kSlotFE = 9, kSlotF = 10, kSlotH = 11;
constexpr int kOffG = 13 * kSlot;
constexpr int kOffGE = kOffG + 4096;
constexpr int kGEPitch = 1056;
constexpr int kGEBytes = 8 * kGEPitch;
constexpr int kOffBar = kOffGE + kGEBytes;
constexpr int kBarX = 0;
constexpr int kBarW = 4;
constexpr int kBarE = 40;
constexpr int kBarHX = 67, kBarFX = 68, kBarFE = 69, kBarG = 70, kBarP0 = 71;
constexpr int kNumBars = 72;
constexpr int kSmemBytes = kOffBar + kNumBars * 8 + 1024;

__device__ float g_ge[2 * kGEBytes / 4];
__device__ unsigned int g_ge_flag[2];
__device__ unsigned int g_cta_count;

#define TS(slot_, idx_) do {} while (0)

__device__ __forceinline__ uint32_t smem_u32(const void* p) { return (uint32_t)__cvta_generic_to_shared(p); }
__device__ __forceinline__ void mbar_init(uint32_t a, uint32_t c) { asm volatile("mbarrier.init.shared.b64 [%0], %1;" ::"r"(a), "r"(c) : "memory"); }
__device__ __forceinline__ void mbar_expect(uint32_t a, uint32_t b) { asm volatile("mbarrier.arrive.expect_tx.shared.b64 _, [%0], %1;" ::"r"(a), "r"(b) : "memory"); }
__device__ __forceinline__ void mbar_arrive(uint32_t a) { asm volatile("mbarrier.arrive.shared.b64 _, [%0];" ::"r"(a) : "memory"); }
__device__ __forceinline__ bool mbar_try(uint32_t a) {
  uint32_t ok;
  asm volatile("{\n.reg .pred p;\nmbarrier.try_wait.parity.shared.b64 p, [%1], 0;\nselp.u32 %0, 1, 0, p;\n}\n" : "=r"(ok) : "r"(a) : "memory");
  return ok != 0;
}
__device__ __forceinline__ bool mbar_try_cluster(uint32_t a) {
  uint32_t ok;
  asm volatile("{\n.reg .pred p;\nmbarrier.try_wait.parity.acquire.cluster.shared.b64 p, [%1], 0;\nselp.u32 %0, 1, 0, p;\n}\n" : "=r"(ok) : "r"(a) : "memory");
  return ok != 0;
}
__device__ __forceinline__ void mbar_wait_slow(uint32_t a) {
  const long long t0 = clock64();
  while (!mbar_try(a)) { if (clock64() - t0 > 4000000ll) break; }
}
__device__ __forceinline__ void mbar_wait_cluster_slow(uint32_t a) {
  const long long t0 = clock64();
  while (!mbar_try_cluster(a)) { if (clock64() - t0 > 4000000ll) break; }
}
__device__ __forceinline__ void mbar_wait(uint32_t a) { if (!mbar_try(a)) mbar_wait_slow(a); }
__device__ __forceinline__ void mbar_wait_cluster(uint32_t a) { if (!mbar_try_cluster(a)) mbar_wait_cluster_slow(a); }
__device__ __forceinline__ uint32_t mapa(uint32_t a, uint32_t r) { uint32_t d; asm volatile("mapa.shared::cluster.u32 %0, %1, %2;" : "=r"(d) : "r"(a), "r"(r)); return d; }
__device__ __forceinline__ bool elect_one() { uint32_t p; asm volatile("{\n.reg .pred P;\nelect.sync _|P, 0xffffffff;\nselp.u32 %0, 1, 0, P;\n}\n" : "=r"(p)); return p != 0; }
__device__ __forceinline__ void fence_async_smem() { asm volatile("fence.proxy.async.shared::cta;" ::: "memory"); }
__device__ __forceinline__ void bar_consumers() { asm volatile("bar.sync 1, 256;" ::: "memory"); }
__device__ __forceinline__ void bar_wg(int wg) { asm volatile("bar.sync %0, 128;" ::"r"(2 + wg) : "memory"); }
__device__ __forceinline__ void cluster_sync_relaxed() { asm volatile("barrier.cluster.arrive.relaxed.aligned;\nbarrier.cluster.wait.aligned;" ::: "memory"); }
__device__ __forceinline__ void wg_fence() { asm volatile("wgmma.fence.sync.aligned;" ::: "memory"); }
__device__ __forceinline__ void wg_commit() { asm volatile("wgmma.commit_group.sync.aligned;" ::: "memory"); }
template <int N> __device__ __forceinline__ void wg_wait() { asm volatile("wgmma.wait_group.sync.aligned %0;" ::"n"(N) : "memory"); }

__device__ __forceinline__ void tma_load_3d(uint32_t dst, const CUtensorMap* tm, uint32_t bar, int c0, int c1, int c2) {
  asm volatile("cp.async.bulk.tensor.3d.shared::cluster.global.mbarrier::complete_tx::bytes [%0], [%1, {%3, %4, %5}], [%2];"
               ::"r"(dst), "l"(tm), "r"(bar), "r"(c0), "r"(c1), "r"(c2) : "memory");
}
__device__ __forceinline__ void tma_load_4d_mc(uint32_t dst, const CUtensorMap* tm, uint32_t bar, int c0, int c1, int c2, int c3, uint16_t mask) {
  asm volatile("cp.async.bulk.tensor.4d.shared::cluster.global.mbarrier::complete_tx::bytes.multicast::cluster [%0], [%1, {%3, %4, %5, %6}], [%2], %7;"
               ::"r"(dst), "l"(tm), "r"(bar), "r"(c0), "r"(c1), "r"(c2), "r"(c3), "h"(mask) : "memory");
}
__device__ __forceinline__ void tma_store_3d(const CUtensorMap* tm, uint32_t src, int c0, int c1, int c2) {
  asm volatile("cp.async.bulk.tensor.3d.global.shared::cta.bulk_group [%0, {%2, %3, %4}], [%1];"
               ::"l"(tm), "r"(src), "r"(c0), "r"(c1), "r"(c2) : "memory");
}
__device__ __forceinline__ void bulk_load(uint32_t dst, const void* src, uint32_t bytes, uint32_t bar) {
  asm volatile("cp.async.bulk.shared::cluster.global.mbarrier::complete_tx::bytes [%0], [%1], %2, [%3];"
               ::"r"(dst), "l"(src), "r"(bytes), "r"(bar) : "memory");
}
__device__ __forceinline__ void dsmem_copy(uint32_t dst_remote, uint32_t src, uint32_t bytes, uint32_t bar_remote) {
  asm volatile("cp.async.bulk.shared::cluster.shared::cta.mbarrier::complete_tx::bytes [%0], [%1], %2, [%3];"
               ::"r"(dst_remote), "r"(src), "r"(bytes), "r"(bar_remote) : "memory");
}
__device__ __forceinline__ void stsm_x4_trans(uint32_t addr, uint32_t r0, uint32_t r1, uint32_t r2, uint32_t r3) {
  asm volatile("stmatrix.sync.aligned.m8n8.x4.trans.shared.b16 [%0], {%1, %2, %3, %4};" ::"r"(addr), "r"(r0), "r"(r1), "r"(r2), "r"(r3) : "memory");
}
__device__ __forceinline__ void stsm_x4(uint32_t addr, uint32_t r0, uint32_t r1, uint32_t r2, uint32_t r3) {
  asm volatile("stmatrix.sync.aligned.m8n8.x4.shared.b16 [%0], {%1, %2, %3, %4};" ::"r"(addr), "r"(r0), "r"(r1), "r"(r2), "r"(r3) : "memory");
}
__device__ __forceinline__ float2 lds64(uint32_t a) { float2 v; asm volatile("ld.shared.v2.f32 {%0, %1}, [%2];" : "=f"(v.x), "=f"(v.y) : "r"(a) : "memory"); return v; }
__device__ __forceinline__ void sts64(uint32_t a, float x, float y) { asm volatile("st.shared.v2.f32 [%0], {%1, %2};" ::"r"(a), "f"(x), "f"(y) : "memory"); }
__device__ __forceinline__ float tanh_fast(float x) { float y; asm("tanh.approx.f32 %0, %1;" : "=f"(y) : "f"(x)); return y; }
__device__ __forceinline__ uint32_t pack_bf16(float lo, float hi) { uint32_t r; asm("cvt.rn.bf16x2.f32 %0, %1, %2;" : "=r"(r) : "f"(hi), "f"(lo)); return r; }
__device__ __forceinline__ float gelu_tanh(float x) {
  const float k0 = 0.7978845608028654f, k1 = 0.7978845608028654f * 0.044715f;
  float u = x * fmaf(x * x, k1, k0);
  float hx = 0.5f * x;
  return fmaf(hx, tanh_fast(u), hx);
}
__device__ __forceinline__ uint64_t make_desc(uint32_t addr, uint32_t lbo, uint32_t sbo) {
  return (uint64_t)((addr & 0x3FFFF) >> 4) | ((uint64_t)(lbo >> 4) << 16) | ((uint64_t)(sbo >> 4) << 32) | ((uint64_t)1 << 62);
}

__device__ __forceinline__ void wgmma_ss_n64(float (&d)[32], uint64_t da, uint64_t db, int scale_d) {
  asm volatile("{\n.reg .pred p;\nsetp.ne.b32 p, %34, 0;\n"
    "wgmma.mma_async.sync.aligned.m64n64k16.f32.bf16.bf16 {%0, %1, %2, %3, %4, %5, %6, %7, %8, %9, %10, %11, %12, %13, %14, %15, %16, %17, %18, %19, %20, %21, %22, %23, %24, %25, %26, %27, %28, %29, %30, %31}, %32, %33, p, 1, 1, 1, 0;\n}\n"
    : "+f"(d[0]), "+f"(d[1]), "+f"(d[2]), "+f"(d[3]), "+f"(d[4]), "+f"(d[5]), "+f"(d[6]), "+f"(d[7]), "+f"(d[8]), "+f"(d[9]), "+f"(d[10]), "+f"(d[11]), "+f"(d[12]), "+f"(d[13]), "+f"(d[14]), "+f"(d[15]), "+f"(d[16]), "+f"(d[17]), "+f"(d[18]), "+f"(d[19]), "+f"(d[20]), "+f"(d[21]), "+f"(d[22]), "+f"(d[23]), "+f"(d[24]), "+f"(d[25]), "+f"(d[26]), "+f"(d[27]), "+f"(d[28]), "+f"(d[29]), "+f"(d[30]), "+f"(d[31])
    : "l"(da), "l"(db), "r"(scale_d));
}

__device__ __forceinline__ void wgmma_ss_n32(float (&d)[16], uint64_t da, uint64_t db, int scale_d) {
  asm volatile("{\n.reg .pred p;\nsetp.ne.b32 p, %18, 0;\n"
    "wgmma.mma_async.sync.aligned.m64n32k16.f32.bf16.bf16 {%0, %1, %2, %3, %4, %5, %6, %7, %8, %9, %10, %11, %12, %13, %14, %15}, %16, %17, p, 1, 1, 1, 0;\n}\n"
    : "+f"(d[0]), "+f"(d[1]), "+f"(d[2]), "+f"(d[3]), "+f"(d[4]), "+f"(d[5]), "+f"(d[6]), "+f"(d[7]), "+f"(d[8]), "+f"(d[9]), "+f"(d[10]), "+f"(d[11]), "+f"(d[12]), "+f"(d[13]), "+f"(d[14]), "+f"(d[15])
    : "l"(da), "l"(db), "r"(scale_d));
}

__device__ __forceinline__ void wgmma_ss_n8(float (&d)[4], uint64_t da, uint64_t db, int scale_d) {
  asm volatile("{\n.reg .pred p;\nsetp.ne.b32 p, %6, 0;\n"
    "wgmma.mma_async.sync.aligned.m64n8k16.f32.bf16.bf16 {%0, %1, %2, %3}, %4, %5, p, 1, 1, 1, 0;\n}\n"
    : "+f"(d[0]), "+f"(d[1]), "+f"(d[2]), "+f"(d[3])
    : "l"(da), "l"(db), "r"(scale_d));
}

__device__ __forceinline__ void wgmma_rs_n128(float (&d)[64], uint32_t a0, uint32_t a1, uint32_t a2, uint32_t a3, uint64_t db, int scale_d) {
  asm volatile("{\n.reg .pred p;\nsetp.ne.b32 p, %69, 0;\n"
    "wgmma.mma_async.sync.aligned.m64n128k16.f32.bf16.bf16 {%0, %1, %2, %3, %4, %5, %6, %7, %8, %9, %10, %11, %12, %13, %14, %15, %16, %17, %18, %19, %20, %21, %22, %23, %24, %25, %26, %27, %28, %29, %30, %31, %32, %33, %34, %35, %36, %37, %38, %39, %40, %41, %42, %43, %44, %45, %46, %47, %48, %49, %50, %51, %52, %53, %54, %55, %56, %57, %58, %59, %60, %61, %62, %63}, {%64, %65, %66, %67}, %68, p, 1, 1, 1;\n}\n"
    : "+f"(d[0]), "+f"(d[1]), "+f"(d[2]), "+f"(d[3]), "+f"(d[4]), "+f"(d[5]), "+f"(d[6]), "+f"(d[7]), "+f"(d[8]), "+f"(d[9]), "+f"(d[10]), "+f"(d[11]), "+f"(d[12]), "+f"(d[13]), "+f"(d[14]), "+f"(d[15]), "+f"(d[16]), "+f"(d[17]), "+f"(d[18]), "+f"(d[19]), "+f"(d[20]), "+f"(d[21]), "+f"(d[22]), "+f"(d[23]), "+f"(d[24]), "+f"(d[25]), "+f"(d[26]), "+f"(d[27]), "+f"(d[28]), "+f"(d[29]), "+f"(d[30]), "+f"(d[31]), "+f"(d[32]), "+f"(d[33]), "+f"(d[34]), "+f"(d[35]), "+f"(d[36]), "+f"(d[37]), "+f"(d[38]), "+f"(d[39]), "+f"(d[40]), "+f"(d[41]), "+f"(d[42]), "+f"(d[43]), "+f"(d[44]), "+f"(d[45]), "+f"(d[46]), "+f"(d[47]), "+f"(d[48]), "+f"(d[49]), "+f"(d[50]), "+f"(d[51]), "+f"(d[52]), "+f"(d[53]), "+f"(d[54]), "+f"(d[55]), "+f"(d[56]), "+f"(d[57]), "+f"(d[58]), "+f"(d[59]), "+f"(d[60]), "+f"(d[61]), "+f"(d[62]), "+f"(d[63])
    : "r"(a0), "r"(a1), "r"(a2), "r"(a3), "l"(db), "r"(scale_d));
}

__host__ __device__ constexpr int unit_slot(int u) {
  constexpr int t[36] = {4, 5, 6, 7, 8, 4, 5, 6, 0, 7, 8, 4,  1, 5, 6, 0, 2, 7, 8, 4, 3, 1, 5, 6,
                         0, 2, 7, 8,  4, 3, 1, 5, 6, 0, 2, 7};
  return t[u];
}
__host__ __device__ constexpr int unit_wait(int u) {
  constexpr int t[36] = {-1, -1, -1, -1, -1, 0, 1, 2, 2, 3, 4, 5,  5, 6, 7, 8, 8, 9, 10, 11, 11, 12, 13, 14,
                         15, 16, 17, 18,  19, 20, 21, 22, 23, 24, 25, 26};
  return t[u];
}

struct Params {
  CUtensorMap x, w1, w2, wf, wg, wo, g, out64, out56;
};

__device__ __forceinline__ void init_bar(uint32_t bars, int i) {
  const uint32_t a = bars + i * 8;
  const bool is_e = (i >= kBarE && i < kBarE + 27);
  mbar_init(a, is_e ? 8 : (i == kBarFE ? 9 : 1));
  if (!is_e) {
    uint32_t bytes = 16384;
    if (i == kBarFX) bytes = 8192;
    if (i == kBarFE) bytes = 8192 + kGEBytes;
    mbar_expect(a, bytes);
  }
}

__global__ void __cluster_dims__(2, 1, 1) __launch_bounds__(kThreads, 1)
rnnt_joint_kernel(const __grid_constant__ Params P) {
  extern __shared__ uint8_t smem_raw[];
  const uint32_t sb = (smem_u32(smem_raw) + 1023u) & ~1023u;
  const uint32_t bars = sb + kOffBar;
  const int warp = threadIdx.x >> 5, lane = threadIdx.x & 31;
  uint32_t cta;
  asm volatile("mov.u32 %0, %%cluster_ctarank;" : "=r"(cta));
  const uint32_t peer = cta ^ 1u;
  const int cl = blockIdx.x >> 1;
  const bool ge_cta = cl < 2;
  const int b = ge_cta ? cl : ((cl - 2) >> 5);
  const int r0 = ge_cta ? 32 * kR : ((cl - 2) & 31) * kR;
  const int rvalid = ge_cta ? kT2 - 32 * kR : kR;

  if (warp >= 8) {
    asm volatile("setmaxnreg.dec.sync.aligned.u32 40;");
    if (warp > 8) {
      if (elect_one()) {
#pragma unroll
        for (int i = 0; i < 6; i++) if (9 + (warp - 1) * 6 + i < kBarG) init_bar(bars, 9 + (warp - 1) * 6 + i);
        asm volatile("fence.mbarrier_init.release.cluster;" ::: "memory");
      }
      __syncwarp();
      cluster_sync_relaxed();
      return;
    }
    TS(2, 0);
    unsigned int ticket = 0;
    if (elect_one()) {
#pragma unroll
      for (int i = 0; i < 9; i++) { mbar_init(bars + i * 8, 1); mbar_expect(bars + i * 8, 16384); }
      if (ge_cta) { mbar_init(bars + kBarG * 8, 1); mbar_expect(bars + kBarG * 8, 4 * 16384 + 4096); mbar_init(bars + kBarP0 * 8, 8); }
      TS(2, 7);
      asm volatile("fence.mbarrier_init.release.cluster;" ::: "memory");
      fence_async_smem();
      TS(2, 8);
      if (ge_cta) {
        tma_load_3d(sb + kOffG, &P.g, bars + kBarG * 8, 0, b * 8, 0);
#pragma unroll
        for (int i = 0; i < 4; i++) tma_load_3d(sb + (9 + i) * kSlot, &P.wg, bars + kBarG * 8, 0, i * 64, 2 * cta);
      }
#pragma unroll
      for (int u = 0; u < 5; u++)
      {
        tma_load_3d(sb + unit_slot(u) * kSlot, &P.w1, bars + (kBarW + u) * 8, 0, (u % 3) * 256 + (u / 3) * 64, 2 * cta);
        if (u == 0) TS(2, 9);
      }
      TS(2, 10);
    }
    __syncwarp();
    if (lane == 0) ticket = atomicAdd(&g_cta_count, 1u);
    TS(2, 6);
    cluster_sync_relaxed();
    TS(2, 1);
    const int par = cta == 0 ? 1 : 0;
    const int q0 = cta == 0 ? 2 * r0 - 2 : 2 * r0 - 1;
    if (elect_one()) {
#pragma unroll
      for (int p = 0; p < 2; p++)
        tma_load_4d_mc(sb + p * kSlot + cta * 8192, &P.x, bars + (kBarX + p) * 8, p * 64, par, q0, b, (uint16_t)3);
    }
    __syncwarp();
    mbar_wait(bars + kBarX * 8);
    if (ge_cta) mbar_wait(bars + kBarP0 * 8);
    if (elect_one()) {
#pragma unroll
      for (int p = 2; p < 4; p++)
        tma_load_4d_mc(sb + p * kSlot + cta * 8192, &P.x, bars + (kBarX + p) * 8, p * 64, par, q0, b, (uint16_t)3);
    }
    __syncwarp();
#pragma unroll
    for (int u = 5; u < 36; u++) {
      if (unit_wait(u) != unit_wait(u - 1)) mbar_wait(bars + (kBarE + unit_wait(u)) * 8);
      if (u == 27) ticket = __shfl_sync(0xffffffffu, ticket, 0);
      if (elect_one()) {
        const uint32_t dst = sb + unit_slot(u) * kSlot, bar = bars + (kBarW + u) * 8;
        if (u < 12) tma_load_3d(dst, &P.w1, bar, 0, (u % 3) * 256 + (u / 3) * 64, 2 * cta);
        else if (u < 24) tma_load_3d(dst, &P.w2, bar, 0, ((u - 12) % 3) * 256 + ((2 * cta + (u - 12) / 3) & 3) * 64, 2 * cta);
        else if (u < 28) tma_load_3d(dst, &P.wf, bar, 0, ((2 * cta + (u - 24)) & 3) * 64, 2 * cta);
        else tma_load_3d(dst, &P.wo, bar, 0, ((u - 28) & 3) * 64, ((u - 28) >> 2) * 2);
        if (u == 27) {
          const unsigned int want = (ticket / kNumCtas + 1u) * 2u;
          const long long t0 = clock64();
          unsigned int v;
          do {
            asm volatile("ld.acquire.gpu.global.u32 %0, [%1];" : "=r"(v) : "l"(&g_ge_flag[b]) : "memory");
          } while ((int)(v - want) < 0 && clock64() - t0 < 4000000ll);
          asm volatile("fence.proxy.async;" ::: "memory");
          bulk_load(sb + kOffGE, reinterpret_cast<const char*>(g_ge) + b * kGEBytes, kGEBytes, bars + kBarFE * 8);
        }
      }
      __syncwarp();
      if (u == 11) TS(2, 2);
      if (u == 23) TS(2, 3);
      if (u == 27) TS(2, 4);
      if (u == 35) TS(2, 5);
    }
  } else {
    asm volatile("setmaxnreg.inc.sync.aligned.u32 232;");
    const int wg = warp >> 2, w = warp & 3;
    const int gq = lane >> 2, q = lane & 3;
    const uint32_t panel = 2 * cta + wg;
    const int ch = panel * 64 + w * 16 + gq;
    if (elect_one()) {
#pragma unroll
      for (int i = 0; i < 6; i++) init_bar(bars, 9 + warp * 6 + i);
      asm volatile("fence.mbarrier_init.release.cluster;" ::: "memory");
    }
    __syncwarp();
    cluster_sync_relaxed();
    if (w == 0) TS(wg, 0);

    if (ge_cta) {
      float ga[4];
      mbar_wait(bars + kBarG * 8);
      wg_fence();
#pragma unroll
      for (int i = 0; i < 4; i++) {
        const uint32_t a0 = sb + (9 + i) * kSlot + wg * 8192;
        const uint32_t b0 = sb + kOffG + i * 1024;
#pragma unroll
        for (int s = 0; s < 4; s++)
          wgmma_ss_n8(ga, make_desc(a0 + s * 2048, 8192, 1024), make_desc(b0 + s * 32, 16, 1024), (i | s) != 0);
      }
      wg_commit();
      wg_wait<0>();
      if (lane == 0) mbar_arrive(bars + kBarP0 * 8);
      float* gp = g_ge + b * (kGEBytes / 4);
      gp[(2 * q) * (kGEPitch / 4) + ch] = ga[0];
      gp[(2 * q + 1) * (kGEPitch / 4) + ch] = ga[1];
      gp[(2 * q) * (kGEPitch / 4) + ch + 8] = ga[2];
      gp[(2 * q + 1) * (kGEPitch / 4) + ch + 8] = ga[3];
      __threadfence();
      bar_consumers();
      if (threadIdx.x == 0) asm volatile("red.release.gpu.global.add.u32 [%0], 1;" ::"l"(&g_ge_flag[b]) : "memory");
    }

    {
      float acc[32];
#pragma unroll
      for (int u = 0; u < 12; u++) {
        const int p = u / 3, tap = u % 3;
        if (tap == 0) mbar_wait(bars + (kBarX + p) * 8);
        mbar_wait(bars + (kBarW + u) * 8);
        if (u == 0 && w == 0) TS(wg, 1);
        const uint32_t a0 = sb + unit_slot(u) * kSlot + wg * 8192;
        const uint32_t b0 = sb + p * kSlot + (tap == 1 ? 8192 : (tap == 2 ? 128 : 0));
        wg_fence();
#pragma unroll
        for (int s = 0; s < 4; s++)
          wgmma_ss_n64(acc, make_desc(a0 + s * 2048, 8192, 1024), make_desc(b0 + s * 32, 16, 1024), (u | s) != 0);
        wg_commit();
        if (u > 0) {
          wg_wait<1>();
          if (lane == 0) mbar_arrive(bars + (kBarE + u - 1) * 8);
        }
      }
      wg_wait<0>();
      if (lane == 0) mbar_arrive(bars + (kBarE + 11) * 8);
      if (w == 0) TS(wg, 2);
      const uint32_t hp = sb + kSlotH * kSlot + panel * 8192;
      const int mi = lane >> 3, l8 = lane & 7;
#pragma unroll
      for (int jb = 0; jb < 8; jb += 2) {
        uint32_t r[4];
#pragma unroll
        for (int t = 0; t < 2; t++) {
          r[2 * t + 0] = pack_bf16(gelu_tanh(acc[4 * (jb + t) + 0]), gelu_tanh(acc[4 * (jb + t) + 1]));
          r[2 * t + 1] = pack_bf16(gelu_tanh(acc[4 * (jb + t) + 2]), gelu_tanh(acc[4 * (jb + t) + 3]));
        }
        const int n = 8 * (jb + (mi >> 1)) + l8;
        const int row = n >> 1, chunk = 2 * w + (mi & 1);
        stsm_x4_trans(hp + (n & 1) * 4096 + row * 128 + ((chunk ^ (row & 7)) << 4), r[0], r[1], r[2], r[3]);
      }
      fence_async_smem();
      bar_consumers();
      if (warp == 0) {
        if (elect_one()) {
          const uint32_t src = sb + kSlotH * kSlot + cta * 16384;
          dsmem_copy(mapa(src, peer), src, 16384, mapa(bars + kBarHX * 8, peer));
        }
        __syncwarp();
      }
      if (w == 0) TS(wg, 3);
    }
    {
      float acc[16];
#pragma unroll
      for (int v = 0; v < 12; v++) {
        const int i = v / 3, tap = v % 3;
        if (v == 6) { mbar_wait_cluster(bars + kBarHX * 8); if (w == 0) TS(wg, 4); }
        mbar_wait(bars + (kBarW + 12 + v) * 8);
        const uint32_t kp = (2 * cta + i) & 3;
        const uint32_t a0 = sb + unit_slot(12 + v) * kSlot + wg * 8192;
        const uint32_t b0 = sb + kSlotH * kSlot + kp * 8192 + (tap == 1 ? 4096 : (tap == 2 ? 128 : 0));
        wg_fence();
#pragma unroll
        for (int s = 0; s < 4; s++)
          wgmma_ss_n32(acc, make_desc(a0 + s * 2048, 8192, 1024), make_desc(b0 + s * 32, 16, 1024), (v | s) != 0);
        wg_commit();
        if (v > 0) {
          wg_wait<1>();
          if (lane == 0) mbar_arrive(bars + (kBarE + 12 + v - 1) * 8);
        }
      }
      wg_wait<0>();
      if (lane == 0) mbar_arrive(bars + (kBarE + 23) * 8);
      if (w == 0) TS(wg, 5);
      const uint32_t fp = sb + kSlotF * kSlot + panel * 4096;
      const int mi = lane >> 3, l8 = lane & 7;
#pragma unroll
      for (int jb = 0; jb < 4; jb += 2) {
        uint32_t r[4];
#pragma unroll
        for (int t = 0; t < 2; t++) {
          r[2 * t + 0] = pack_bf16(gelu_tanh(acc[4 * (jb + t) + 0]), gelu_tanh(acc[4 * (jb + t) + 1]));
          r[2 * t + 1] = pack_bf16(gelu_tanh(acc[4 * (jb + t) + 2]), gelu_tanh(acc[4 * (jb + t) + 3]));
        }
        const int n = 8 * (jb + (mi >> 1)) + l8;
        const int chunk = 2 * w + (mi & 1);
        stsm_x4_trans(fp + n * 128 + ((chunk ^ (n & 7)) << 4), r[0], r[1], r[2], r[3]);
      }
      fence_async_smem();
      bar_consumers();
      if (warp == 0) {
        if (elect_one()) {
          const uint32_t src = sb + kSlotF * kSlot + cta * 8192;
          dsmem_copy(mapa(src, peer), src, 8192, mapa(bars + kBarFX * 8, peer));
        }
        __syncwarp();
      }
      if (w == 0) TS(wg, 6);
    }
    {
      float acc[16];
#pragma unroll
      for (int i = 0; i < 4; i++) {
        if (i == 2) { mbar_wait_cluster(bars + kBarFX * 8); if (w == 0) TS(wg, 7); }
        mbar_wait(bars + (kBarW + 24 + i) * 8);
        const uint32_t kp = (2 * cta + i) & 3;
        const uint32_t a0 = sb + unit_slot(24 + i) * kSlot + wg * 8192;
        const uint32_t b0 = sb + kSlotF * kSlot + kp * 4096;
        wg_fence();
#pragma unroll
        for (int s = 0; s < 4; s++)
          wgmma_ss_n32(acc, make_desc(a0 + s * 2048, 8192, 1024), make_desc(b0 + s * 32, 16, 1024), (i | s) != 0);
        wg_commit();
        if (i > 0) {
          wg_wait<1>();
          if (lane == 0) mbar_arrive(bars + (kBarE + 24 + i - 1) * 8);
        }
      }
      wg_wait<0>();
      if (w == 0) TS(wg, 8);
      const uint32_t sw = ((ch >> 1) & 3) * 2;
      const uint32_t own = sb + kSlotFE * kSlot + ch * 64;
      const uint32_t stg = sb + kSlotH * kSlot + (ch - (int)cta * 128) * 64;
#pragma unroll
      for (int jb = 0; jb < 4; jb++) {
        const uint32_t base = ((uint32_t)(jb >> 1) == cta) ? own : stg;
        const uint32_t pr = (4 * (jb & 1) + q) ^ sw;
        sts64(base + pr * 8, acc[4 * jb + 0], acc[4 * jb + 1]);
        sts64(base + 512 + pr * 8, acc[4 * jb + 2], acc[4 * jb + 3]);
      }
      fence_async_smem();
      bar_wg(wg);
      if (w == 0) {
        if (elect_one())
          dsmem_copy(mapa(sb + kSlotFE * kSlot + panel * 4096, peer), sb + kSlotH * kSlot + wg * 4096, 4096, mapa(bars + kBarFE * 8, peer));
        __syncwarp();
      }
      if (lane == 0) mbar_arrive(bars + kBarFE * 8);
      if (w == 0) TS(wg, 9);
    }
    const int rl0 = cta * 16 + wg * 8;
    mbar_wait_cluster(bars + kBarFE * 8);
    asm volatile("barrier.cluster.arrive.relaxed.aligned;" ::: "memory");
    if (wg == 1) asm volatile("bar.sync 4, 256;" ::: "memory");
    if (rl0 < rvalid) {
      if (w == 0) TS(wg, 10);
      const uint32_t fe_t = sb + kSlotFE * kSlot + (2 * q) * 64 + (((4 * wg + w) ^ (2 * q)) << 3);
      const uint32_t ge_t = sb + kOffGE + gq * kGEPitch + (2 * q) * 4;
      uint32_t A[64];
      float acc0[64], acc1[64];
#pragma unroll
      for (int g4 = 0; g4 < 4; g4++) {
#pragma unroll
        for (int k4 = 0; k4 < 4; k4++) {
          const int kk = g4 * 4 + k4;
          const float2 f0 = lds64(fe_t + kk * 1024), f1 = lds64(fe_t + kk * 1024 + 64);
          const float2 f2 = lds64(fe_t + kk * 1024 + 512), f3 = lds64(fe_t + kk * 1024 + 576);
          const float2 g0 = lds64(ge_t + kk * 64), g1 = lds64(ge_t + kk * 64 + 32);
          A[4 * kk + 0] = pack_bf16(tanh_fast(f0.x + g0.x), tanh_fast(f1.x + g0.y));
          A[4 * kk + 1] = pack_bf16(tanh_fast(f0.y + g0.x), tanh_fast(f1.y + g0.y));
          A[4 * kk + 2] = pack_bf16(tanh_fast(f2.x + g1.x), tanh_fast(f3.x + g1.y));
          A[4 * kk + 3] = pack_bf16(tanh_fast(f2.y + g1.x), tanh_fast(f3.y + g1.y));
        }
        if (g4 == 3 && wg == 0) asm volatile("bar.arrive 4, 256;" ::: "memory");
        mbar_wait(bars + (kBarW + 28 + g4) * 8);
        const uint32_t b0 = sb + unit_slot(28 + g4) * kSlot;
        wg_fence();
#pragma unroll
        for (int k4 = 0; k4 < 4; k4++) {
          const int kk = g4 * 4 + k4;
          wgmma_rs_n128(acc0, A[4 * kk], A[4 * kk + 1], A[4 * kk + 2], A[4 * kk + 3], make_desc(b0 + k4 * 2048, 8192, 1024), kk != 0);
        }
        wg_commit();
      }
      if (w == 0) TS(wg, 11);
      const int mi = lane >> 3, l8 = lane & 7;
      const bool full = rl0 + 8 <= rvalid;
      const CUtensorMap* omap = full ? &P.out64 : &P.out56;
      const int grow = (b * kT2 + r0 + rl0) * 8;
      const uint32_t st_row = (16 * w + (mi & 1) * 8 + l8) * 128;
      const uint32_t st = sb + (wg ? 12 : 8) * kSlot;
#pragma unroll
      for (int kk = 0; kk < 4; kk++) {
        if ((kk & 3) == 0) { mbar_wait(bars + (kBarW + 32 + (kk >> 2)) * 8); wg_fence(); }
        const uint32_t b0 = sb + unit_slot(32 + (kk >> 2)) * kSlot + (kk & 3) * 2048;
        wgmma_rs_n128(acc1, A[4 * kk], A[4 * kk + 1], A[4 * kk + 2], A[4 * kk + 3], make_desc(b0, 8192, 1024), kk != 0);
      }
      wg_commit();
      {
        wg_wait<1>();
        if (w == 0) TS(wg, 12);
#pragma unroll
        for (int jb = 0; jb < 16; jb += 2) {
          const uint32_t r0_ = pack_bf16(acc0[4 * jb + 0], acc0[4 * jb + 1]), r1_ = pack_bf16(acc0[4 * jb + 2], acc0[4 * jb + 3]);
          const uint32_t r2_ = pack_bf16(acc0[4 * jb + 4], acc0[4 * jb + 5]), r3_ = pack_bf16(acc0[4 * jb + 6], acc0[4 * jb + 7]);
          const int jj = jb + (mi >> 1);
          stsm_x4(st + (jj >> 3) * 8192 + st_row + (((jj & 7) ^ l8) << 4), r0_, r1_, r2_, r3_);
        }
        fence_async_smem();
        bar_wg(wg);
        if (w == 0) {
          if (elect_one()) {
            tma_store_3d(omap, st, 0, grow, 0);
            tma_store_3d(omap, st + 8192, 0, grow, 1);
            asm volatile("cp.async.bulk.commit_group;" ::: "memory");
          }
          __syncwarp();
        }
      }
#pragma unroll
      for (int kk = 4; kk < 16; kk++) {
        if ((kk & 3) == 0) { mbar_wait(bars + (kBarW + 32 + (kk >> 2)) * 8); wg_fence(); }
        const uint32_t b0 = sb + unit_slot(32 + (kk >> 2)) * kSlot + (kk & 3) * 2048;
        wgmma_rs_n128(acc1, A[4 * kk], A[4 * kk + 1], A[4 * kk + 2], A[4 * kk + 3], make_desc(b0, 8192, 1024), 1);
      }
      wg_commit();
      {
        wg_wait<0>();
        if (w == 0) TS(wg, 13);
        const uint32_t st2 = wg ? st : sb + kSlotF * kSlot;
        if (wg == 1) {
          if (w == 0) {
            if (elect_one()) asm volatile("cp.async.bulk.wait_group.read 0;" ::: "memory");
            __syncwarp();
          }
          bar_wg(wg);
        }
#pragma unroll
        for (int jb = 0; jb < 16; jb += 2) {
          const uint32_t r0_ = pack_bf16(acc1[4 * jb + 0], acc1[4 * jb + 1]), r1_ = pack_bf16(acc1[4 * jb + 2], acc1[4 * jb + 3]);
          const uint32_t r2_ = pack_bf16(acc1[4 * jb + 4], acc1[4 * jb + 5]), r3_ = pack_bf16(acc1[4 * jb + 6], acc1[4 * jb + 7]);
          const int jj = jb + (mi >> 1);
          stsm_x4(st2 + (jj >> 3) * 8192 + st_row + (((jj & 7) ^ l8) << 4), r0_, r1_, r2_, r3_);
        }
        fence_async_smem();
        bar_wg(wg);
        if (w == 0) {
          if (elect_one()) {
            tma_store_3d(omap, st2, 0, grow, 2);
            tma_store_3d(omap, st2 + 8192, 0, grow, 3);
            asm volatile("cp.async.bulk.commit_group;" ::: "memory");
            asm volatile("cp.async.bulk.wait_group.read 0;" ::: "memory");
          }
          __syncwarp();
        }
      }
      if (w == 0) TS(wg, 14);
    } else if (wg == 0) {
      asm volatile("bar.arrive 4, 256;" ::: "memory");
    }
    asm volatile("barrier.cluster.wait.aligned;" ::: "memory");
  }
}

typedef CUresult (*EncodeFn)(CUtensorMap*, CUtensorMapDataType, cuuint32_t, void*, const cuuint64_t*, const cuuint64_t*,
                             const cuuint32_t*, const cuuint32_t*, CUtensorMapInterleave, CUtensorMapSwizzle,
                             CUtensorMapL2promotion, CUtensorMapFloatOOBfill);

void make_map3(EncodeFn enc, CUtensorMap* tm, const void* ptr, uint64_t rows, uint32_t box_rows, uint32_t box_panels) {
  cuuint64_t gd[3] = {64, rows, 4};
  cuuint64_t gs[2] = {512, 128};
  cuuint32_t bd[3] = {64, box_rows, box_panels};
  cuuint32_t es[3] = {1, 1, 1};
  enc(tm, CU_TENSOR_MAP_DATA_TYPE_BFLOAT16, 3, const_cast<void*>(ptr), gd, gs, bd, es, CU_TENSOR_MAP_INTERLEAVE_NONE,
      CU_TENSOR_MAP_SWIZZLE_128B, CU_TENSOR_MAP_L2_PROMOTION_L2_256B, CU_TENSOR_MAP_FLOAT_OOB_FILL_NONE);
}

}

extern "C" void kernel_launch(void* const* d_in, const int* in_sizes, int n_in, void* d_out, int out_size) {
  static EncodeFn enc = nullptr;
  if (!enc) {
    cudaDriverEntryPointQueryResult qr;
    cudaGetDriverEntryPoint("cuTensorMapEncodeTiled", (void**)&enc, cudaEnableDefault, &qr);
    cudaFuncSetAttribute(rnnt_joint_kernel, cudaFuncAttributeMaxDynamicSharedMemorySize, kSmemBytes);
  }
  Params P;
  {
    cuuint64_t gd[4] = {256, 2, 2000, 2};
    cuuint64_t gs[3] = {512, 1024, 4000ull * 512};
    cuuint32_t bd[4] = {64, 1, 64, 1};
    cuuint32_t es[4] = {1, 1, 1, 1};
    enc(&P.x, CU_TENSOR_MAP_DATA_TYPE_BFLOAT16, 4, d_in[0], gd, gs, bd, es, CU_TENSOR_MAP_INTERLEAVE_NONE,
        CU_TENSOR_MAP_SWIZZLE_128B, CU_TENSOR_MAP_L2_PROMOTION_L2_256B, CU_TENSOR_MAP_FLOAT_OOB_FILL_NONE);
  }
  make_map3(enc, &P.w1, d_in[1], 768, 64, 2);
  make_map3(enc, &P.w2, d_in[2], 768, 64, 2);
  make_map3(enc, &P.g, d_in[3], 16, 8, 4);
  make_map3(enc, &P.wf, d_in[4], 256, 64, 2);
  make_map3(enc, &P.wg, d_in[5], 256, 64, 2);
  make_map3(enc, &P.wo, d_in[6], 256, 64, 2);
  make_map3(enc, &P.out64, d_out, 16000, 64, 1);
  make_map3(enc, &P.out56, d_out, 16000, 56, 1);
  rnnt_joint_kernel<<<kNumCtas, kThreads, kSmemBytes>>>(P);
}
```

```cpp
#include <cuda_runtime.h>
#include <cuda_bf16.h>
#include <cuda.h>
#include <stdint.h>

namespace {

constexpr int kT2 = 1000;
constexpr int kR = 31;
constexpr int kNumCtas = 132;
constexpr int kThreads = 384;
constexpr int kSlot = 16384;

constexpr int kSlotFE = 9, kSlotF = 10, kSlotH = 11;
constexpr int kOffG = 13 * kSlot;
constexpr int kOffGE = kOffG + 4096;
constexpr int kGEPitch = 1056;
constexpr int kGEBytes = 8 * kGEPitch;
constexpr int kOffBar = kOffGE + kGEBytes;
constexpr int kBarX = 0;
constexpr int kBarW = 4;
constexpr int kBarE = 40;
constexpr int kBarHX = 67, kBarFX = 68, kBarFE = 69, kBarG = 70, kBarP0 = 71;
constexpr int kNumBars = 72;
constexpr int kSmemBytes = kOffBar + kNumBars * 8 + 1024;

__device__ float g_ge[2 * kGEBytes / 4];
__device__ unsigned int g_ge_flag[2];
__device__ unsigned int g_cta_count;

#define TS(slot_, idx_) do {} while (0)

__device__ __forceinline__ uint32_t smem_u32(const void* p) { return (uint32_t)__cvta_generic_to_shared(p); }
__device__ __forceinline__ void mbar_init(uint32_t a, uint32_t c) { asm volatile("mbarrier.init.shared.b64 [%0], %1;" ::"r"(a), "r"(c) : "memory"); }
__device__ __forceinline__ void mbar_expect(uint32_t a, uint32_t b) { asm volatile("mbarrier.arrive.expect_tx.shared.b64 _, [%0], %1;" ::"r"(a), "r"(b) : "memory"); }
__device__ __forceinline__ void mbar_arrive(uint32_t a) { asm volatile("mbarrier.arrive.shared.b64 _, [%0];" ::"r"(a) : "memory"); }
__device__ __forceinline__ bool mbar_try(uint32_t a) {
  uint32_t ok;
  asm volatile("{\n.reg .pred p;\nmbarrier.try_wait.parity.shared.b64 p, [%1], 0;\nselp.u32 %0, 1, 0, p;\n}\n" : "=r"(ok) : "r"(a) : "memory");
  return ok != 0;
}
__device__ __forceinline__ bool mbar_try_cluster(uint32_t a) {
  uint32_t ok;
  asm volatile("{\n.reg .pred p;\nmbarrier.try_wait.parity.acquire.cluster.shared.b64 p, [%1], 0;\nselp.u32 %0, 1, 0, p;\n}\n" : "=r"(ok) : "r"(a) : "memory");
  return ok != 0;
}
__device__ __forceinline__ void mbar_wait_slow(uint32_t a) {
  const long long t0 = clock64();
  while (!mbar_try(a)) { if (clock64() - t0 > 4000000ll) break; }
}
__device__ __forceinline__ void mbar_wait_cluster_slow(uint32_t a) {
  const long long t0 = clock64();
  while (!mbar_try_cluster(a)) { if (clock64() - t0 > 4000000ll) break; }
}
__device__ __forceinline__ void mbar_wait(uint32_t a) { if (!mbar_try(a)) mbar_wait_slow(a); }
__device__ __forceinline__ void mbar_wait_cluster(uint32_t a) { if (!mbar_try_cluster(a)) mbar_wait_cluster_slow(a); }
__device__ __forceinline__ uint32_t mapa(uint32_t a, uint32_t r) { uint32_t d; asm volatile("mapa.shared::cluster.u32 %0, %1, %2;" : "=r"(d) : "r"(a), "r"(r)); return d; }
__device__ __forceinline__ bool elect_one() { uint32_t p; asm volatile("{\n.reg .pred P;\nelect.sync _|P, 0xffffffff;\nselp.u32 %0, 1, 0, P;\n}\n" : "=r"(p)); return p != 0; }
__device__ __forceinline__ void fence_async_smem() { asm volatile("fence.proxy.async.shared::cta;" ::: "memory"); }
__device__ __forceinline__ void bar_consumers() { asm volatile("bar.sync 1, 256;" ::: "memory"); }
__device__ __forceinline__ void bar_wg(int wg) { asm volatile("bar.sync %0, 128;" ::"r"(2 + wg) : "memory"); }
__device__ __forceinline__ void cluster_sync_relaxed() { asm volatile("barrier.cluster.arrive.relaxed.aligned;\nbarrier.cluster.wait.aligned;" ::: "memory"); }
__device__ __forceinline__ void wg_fence() { asm volatile("wgmma.fence.sync.aligned;" ::: "memory"); }
__device__ __forceinline__ void wg_commit() { asm volatile("wgmma.commit_group.sync.aligned;" ::: "memory"); }
template <int N> __device__ __forceinline__ void wg_wait() { asm volatile("wgmma.wait_group.sync.aligned %0;" ::"n"(N) : "memory"); }

__device__ __forceinline__ void tma_load_3d(uint32_t dst, const CUtensorMap* tm, uint32_t bar, int c0, int c1, int c2) {
  asm volatile("cp.async.bulk.tensor.3d.shared::cluster.global.mbarrier::complete_tx::bytes [%0], [%1, {%3, %4, %5}], [%2];"
               ::"r"(dst), "l"(tm), "r"(bar), "r"(c0), "r"(c1), "r"(c2) : "memory");
}
__device__ __forceinline__ void tma_load_4d_mc(uint32_t dst, const CUtensorMap* tm, uint32_t bar, int c0, int c1, int c2, int c3, uint16_t mask) {
  asm volatile("cp.async.bulk.tensor.4d.shared::cluster.global.mbarrier::complete_tx::bytes.multicast::cluster [%0], [%1, {%3, %4, %5, %6}], [%2], %7;"
               ::"r"(dst), "l"(tm), "r"(bar), "r"(c0), "r"(c1), "r"(c2), "r"(c3), "h"(mask) : "memory");
}
__device__ __forceinline__ void tma_store_3d(const CUtensorMap* tm, uint32_t src, int c0, int c1, int c2) {
  asm volatile("cp.async.bulk.tensor.3d.global.shared::cta.bulk_group [%0, {%2, %3, %4}], [%1];"
               ::"l"(tm), "r"(src), "r"(c0), "r"(c1), "r"(c2) : "memory");
}
__device__ __forceinline__ void bulk_load(uint32_t dst, const void* src, uint32_t bytes, uint32_t bar) {
  asm volatile("cp.async.bulk.shared::cluster.global.mbarrier::complete_tx::bytes [%0], [%1], %2, [%3];"
               ::"r"(dst), "l"(src), "r"(bytes), "r"(bar) : "memory");
}
__device__ __forceinline__ void dsmem_copy(uint32_t dst_remote, uint32_t src, uint32_t bytes, uint32_t bar_remote) {
  asm volatile("cp.async.bulk.shared::cluster.shared::cta.mbarrier::complete_tx::bytes [%0], [%1], %2, [%3];"
               ::"r"(dst_remote), "r"(src), "r"(bytes), "r"(bar_remote) : "memory");
}
__device__ __forceinline__ void stsm_x4_trans(uint32_t addr, uint32_t r0, uint32_t r1, uint32_t r2, uint32_t r3) {
  asm volatile("stmatrix.sync.aligned.m8n8.x4.trans.shared.b16 [%0], {%1, %2, %3, %4};" ::"r"(addr), "r"(r0), "r"(r1), "r"(r2), "r"(r3) : "memory");
}
__device__ __forceinline__ void stsm_x4(uint32_t addr, uint32_t r0, uint32_t r1, uint32_t r2, uint32_t r3) {
  asm volatile("stmatrix.sync.aligned.m8n8.x4.shared.b16 [%0], {%1, %2, %3, %4};" ::"r"(addr), "r"(r0), "r"(r1), "r"(r2), "r"(r3) : "memory");
}
__device__ __forceinline__ float2 lds64(uint32_t a) { float2 v; asm volatile("ld.shared.v2.f32 {%0, %1}, [%2];" : "=f"(v.x), "=f"(v.y) : "r"(a) : "memory"); return v; }
__device__ __forceinline__ void sts64(uint32_t a, float x, float y) { asm volatile("st.shared.v2.f32 [%0], {%1, %2};" ::"r"(a), "f"(x), "f"(y) : "memory"); }
__device__ __forceinline__ float tanh_fast(float x) { float y; asm("tanh.approx.f32 %0, %1;" : "=f"(y) : "f"(x)); return y; }
__device__ __forceinline__ uint32_t pack_bf16(float lo, float hi) { uint32_t r; asm("cvt.rn.bf16x2.f32 %0, %1, %2;" : "=r"(r) : "f"(hi), "f"(lo)); return r; }
__device__ __forceinline__ float gelu_tanh(float x) {
  const float k0 = 0.7978845608028654f, k1 = 0.7978845608028654f * 0.044715f;
  float u = x * fmaf(x * x, k1, k0);
  float hx = 0.5f * x;
  return fmaf(hx, tanh_fast(u), hx);
}
__device__ __forceinline__ uint64_t make_desc(uint32_t addr, uint32_t lbo, uint32_t sbo) {
  return (uint64_t)((addr & 0x3FFFF) >> 4) | ((uint64_t)(lbo >> 4) << 16) | ((uint64_t)(sbo >> 4) << 32) | ((uint64_t)1 << 62);
}

__device__ __forceinline__ uint32_t desc_lo(uint32_t addr, uint32_t lbo) { return ((addr & 0x3FFFF) >> 4) | ((lbo >> 4) << 16); }
__device__ __forceinline__ uint64_t desc_at(uint32_t lo, uint32_t off) { return ((uint64_t)0x40000040u << 32) | (uint64_t)(lo + (off >> 4)); }

__device__ __forceinline__ void wgmma_ss_n64(float (&d)[32], uint64_t da, uint64_t db, int scale_d) {
  asm volatile("{\n.reg .pred p;\nsetp.ne.b32 p, %34, 0;\n"
    "wgmma.mma_async.sync.aligned.m64n64k16.f32.bf16.bf16 {%0, %1, %2, %3, %4, %5, %6, %7, %8, %9, %10, %11, %12, %13, %14, %15, %16, %17, %18, %19, %20, %21, %22, %23, %24, %25, %26, %27, %28, %29, %30, %31}, %32, %33, p, 1, 1, 1, 0;\n}\n"
    : "+f"(d[0]), "+f"(d[1]), "+f"(d[2]), "+f"(d[3]), "+f"(d[4]), "+f"(d[5]), "+f"(d[6]), "+f"(d[7]), "+f"(d[8]), "+f"(d[9]), "+f"(d[10]), "+f"(d[11]), "+f"(d[12]), "+f"(d[13]), "+f"(d[14]), "+f"(d[15]), "+f"(d[16]), "+f"(d[17]), "+f"(d[18]), "+f"(d[19]), "+f"(d[20]), "+f"(d[21]), "+f"(d[22]), "+f"(d[23]), "+f"(d[24]), "+f"(d[25]), "+f"(d[26]), "+f"(d[27]), "+f"(d[28]), "+f"(d[29]), "+f"(d[30]), "+f"(d[31])
    : "l"(da), "l"(db), "r"(scale_d));
}

__device__ __forceinline__ void wgmma_ss_n32(float (&d)[16], uint64_t da, uint64_t db, int scale_d) {
  asm volatile("{\n.reg .pred p;\nsetp.ne.b32 p, %18, 0;\n"
    "wgmma.mma_async.sync.aligned.m64n32k16.f32.bf16.bf16 {%0, %1, %2, %3, %4, %5, %6, %7, %8, %9, %10, %11, %12, %13, %14, %15}, %16, %17, p, 1, 1, 1, 0;\n}\n"
    : "+f"(d[0]), "+f"(d[1]), "+f"(d[2]), "+f"(d[3]), "+f"(d[4]), "+f"(d[5]), "+f"(d[6]), "+f"(d[7]), "+f"(d[8]), "+f"(d[9]), "+f"(d[10]), "+f"(d[11]), "+f"(d[12]), "+f"(d[13]), "+f"(d[14]), "+f"(d[15])
    : "l"(da), "l"(db), "r"(scale_d));
}

__device__ __forceinline__ void wgmma_ss_n8(float (&d)[4], uint64_t da, uint64_t db, int scale_d) {
  asm volatile("{\n.reg .pred p;\nsetp.ne.b32 p, %6, 0;\n"
    "wgmma.mma_async.sync.aligned.m64n8k16.f32.bf16.bf16 {%0, %1, %2, %3}, %4, %5, p, 1, 1, 1, 0;\n}\n"
    : "+f"(d[0]), "+f"(d[1]), "+f"(d[2]), "+f"(d[3])
    : "l"(da), "l"(db), "r"(scale_d));
}

__device__ __forceinline__ void wgmma_rs_n64(float (&d)[32], uint32_t a0, uint32_t a1, uint32_t a2, uint32_t a3, uint64_t db, int scale_d) {
  asm volatile("{\n.reg .pred p;\nsetp.ne.b32 p, %37, 0;\n"
    "wgmma.mma_async.sync.aligned.m64n64k16.f32.bf16.bf16 {%0, %1, %2, %3, %4, %5, %6, %7, %8, %9, %10, %11, %12, %13, %14, %15, %16, %17, %18, %19, %20, %21, %22, %23, %24, %25, %26, %27, %28, %29, %30, %31}, {%32, %33, %34, %35}, %36, p, 1, 1, 1;\n}\n"
    : "+f"(d[0]), "+f"(d[1]), "+f"(d[2]), "+f"(d[3]), "+f"(d[4]), "+f"(d[5]), "+f"(d[6]), "+f"(d[7]), "+f"(d[8]), "+f"(d[9]), "+f"(d[10]), "+f"(d[11]), "+f"(d[12]), "+f"(d[13]), "+f"(d[14]), "+f"(d[15]), "+f"(d[16]), "+f"(d[17]), "+f"(d[18]), "+f"(d[19]), "+f"(d[20]), "+f"(d[21]), "+f"(d[22]), "+f"(d[23]), "+f"(d[24]), "+f"(d[25]), "+f"(d[26]), "+f"(d[27]), "+f"(d[28]), "+f"(d[29]), "+f"(d[30]), "+f"(d[31])
    : "r"(a0), "r"(a1), "r"(a2), "r"(a3), "l"(db), "r"(scale_d));
}

__host__ __device__ constexpr int unit_slot(int u) {
  constexpr int t[36] = {4, 5, 6, 7, 8, 4, 5, 6, 0, 7, 8, 4,  1, 5, 6, 0, 2, 7, 8, 4, 3, 1, 5, 6,
                         0, 2, 7, 8,  4, 3, 1, 5, 6, 0, 2, 7};
  return t[u];
}
__host__ __device__ constexpr int unit_wait(int u) {
  constexpr int t[36] = {-1, -1, -1, -1, -1, 0, 1, 2, 2, 3, 4, 5,  5, 6, 7, 8, 8, 9, 10, 11, 11, 12, 13, 14,
                         15, 16, 17, 18,  19, 20, 21, 22, 23, 24, 25, 26};
  return t[u];
}

struct Params {
  CUtensorMap x, w1, w2, wf, wg, wo, g, out64, out56;
};

__device__ __forceinline__ void init_bar(uint32_t bars, int i) {
  const uint32_t a = bars + i * 8;
  const bool is_e = (i >= kBarE && i < kBarE + 27);
  mbar_init(a, is_e ? 8 : (i == kBarFE ? 9 : 1));
  if (!is_e) {
    uint32_t bytes = 16384;
    if (i == kBarFX) bytes = 8192;
    if (i == kBarFE) bytes = 8192 + kGEBytes;
    mbar_expect(a, bytes);
  }
}

__global__ void __cluster_dims__(2, 1, 1) __launch_bounds__(kThreads, 1)
rnnt_joint_kernel(const __grid_constant__ Params P) {
  extern __shared__ uint8_t smem_raw[];
  const uint32_t sb = (smem_u32(smem_raw) + 1023u) & ~1023u;
  const uint32_t bars = sb + kOffBar;
  const int warp = threadIdx.x >> 5, lane = threadIdx.x & 31;
  uint32_t cta;
  asm volatile("mov.u32 %0, %%cluster_ctarank;" : "=r"(cta));
  const uint32_t peer = cta ^ 1u;
  const int cl = blockIdx.x >> 1;
  const bool ge_cta = cl < 2;
  const int b = ge_cta ? cl : ((cl - 2) >> 5);
  const int r0 = ge_cta ? 32 * kR : ((cl - 2) & 31) * kR;
  const int rvalid = ge_cta ? kT2 - 32 * kR : kR;

  if (warp >= 8) {
    asm volatile("setmaxnreg.dec.sync.aligned.u32 40;");
    if (warp > 8) {
      if (elect_one()) {
#pragma unroll
        for (int i = 0; i < 6; i++) if (9 + (warp - 1) * 6 + i < kBarG) init_bar(bars, 9 + (warp - 1) * 6 + i);
        asm volatile("fence.mbarrier_init.release.cluster;" ::: "memory");
      }
      __syncwarp();
      cluster_sync_relaxed();
      return;
    }
    TS(2, 0);
    unsigned int ticket = 0;
    const int par = cta == 0 ? 1 : 0;
    const int q0 = cta == 0 ? 2 * r0 - 2 : 2 * r0 - 1;
    if (elect_one()) {
#pragma unroll
      for (int p = 0; p < 4; p += 2)
        asm volatile("cp.async.bulk.prefetch.tensor.4d.L2.global.tile [%0, {%1, %2, %3, %4}];" ::"l"(&P.x), "r"(p * 64), "r"(par), "r"(q0), "r"(b) : "memory");
#pragma unroll
      for (int i = 0; i < 9; i++) { mbar_init(bars + i * 8, 1); mbar_expect(bars + i * 8, 16384); }
      if (ge_cta) { mbar_init(bars + kBarG * 8, 1); mbar_expect(bars + kBarG * 8, 4 * 16384 + 4096); mbar_init(bars + kBarP0 * 8, 8); }
      TS(2, 7);
      asm volatile("fence.mbarrier_init.release.cluster;" ::: "memory");
      fence_async_smem();
      TS(2, 8);
      if (ge_cta) {
        tma_load_3d(sb + kOffG, &P.g, bars + kBarG * 8, 0, b * 8, 0);
#pragma unroll
        for (int i = 0; i < 4; i++) tma_load_3d(sb + (9 + i) * kSlot, &P.wg, bars + kBarG * 8, 0, i * 64, 2 * cta);
      }
#pragma unroll
      for (int u = 0; u < 5; u++)
      {
        tma_load_3d(sb + unit_slot(u) * kSlot, &P.w1, bars + (kBarW + u) * 8, 0, (u % 3) * 256 + (u / 3) * 64, 2 * cta);
        if (u == 0) TS(2, 9);
      }
      TS(2, 10);
    }
    __syncwarp();
    TS(2, 6);
    cluster_sync_relaxed();
    TS(2, 1);
    if (elect_one()) {
#pragma unroll
      for (int p = 0; p < 2; p++)
        tma_load_4d_mc(sb + p * kSlot + cta * 8192, &P.x, bars + (kBarX + p) * 8, p * 64, par, q0, b, (uint16_t)3);
    }
    __syncwarp();
    if (lane == 0) ticket = atomicAdd(&g_cta_count, 1u);
    mbar_wait(bars + kBarX * 8);
    if (ge_cta) mbar_wait(bars + kBarP0 * 8);
    if (elect_one()) {
#pragma unroll
      for (int p = 2; p < 4; p++)
        tma_load_4d_mc(sb + p * kSlot + cta * 8192, &P.x, bars + (kBarX + p) * 8, p * 64, par, q0, b, (uint16_t)3);
    }
    __syncwarp();
#pragma unroll
    for (int u = 5; u < 36; u++) {
      if (unit_wait(u) != unit_wait(u - 1)) mbar_wait(bars + (kBarE + unit_wait(u)) * 8);
      if (u == 27) ticket = __shfl_sync(0xffffffffu, ticket, 0);
      if (elect_one()) {
        const uint32_t dst = sb + unit_slot(u) * kSlot, bar = bars + (kBarW + u) * 8;
        if (u < 12) tma_load_3d(dst, &P.w1, bar, 0, (u % 3) * 256 + (u / 3) * 64, 2 * cta);
        else if (u < 24) tma_load_3d(dst, &P.w2, bar, 0, ((u - 12) % 3) * 256 + ((2 * cta + (u - 12) / 3) & 3) * 64, 2 * cta);
        else if (u < 28) tma_load_3d(dst, &P.wf, bar, 0, ((2 * cta + (u - 24)) & 3) * 64, 2 * cta);
        else tma_load_3d(dst, &P.wo, bar, 0, ((u - 28) & 3) * 64, ((u - 28) >> 2) * 2);
        if (u == 27) {
          const unsigned int want = (ticket / kNumCtas + 1u) * 2u;
          const long long t0 = clock64();
          unsigned int v;
          do {
            asm volatile("ld.acquire.gpu.global.u32 %0, [%1];" : "=r"(v) : "l"(&g_ge_flag[b]) : "memory");
          } while ((int)(v - want) < 0 && clock64() - t0 < 4000000ll);
          asm volatile("fence.proxy.async;" ::: "memory");
          bulk_load(sb + kOffGE, reinterpret_cast<const char*>(g_ge) + b * kGEBytes, kGEBytes, bars + kBarFE * 8);
        }
      }
      __syncwarp();
      if (u == 11) TS(2, 2);
      if (u == 23) TS(2, 3);
      if (u == 27) TS(2, 4);
      if (u == 35) TS(2, 5);
    }
  } else {
    asm volatile("setmaxnreg.inc.sync.aligned.u32 232;");
    const int wg = warp >> 2, w = warp & 3;
    const int gq = lane >> 2, q = lane & 3;
    const uint32_t panel = 2 * cta + wg;
    const int ch = panel * 64 + w * 16 + gq;
    const uint32_t dA = desc_lo(sb + wg * 8192, 8192);
    const uint32_t dB = desc_lo(sb, 16);
    const uint32_t dBo = desc_lo(sb + cta * 2 * 8192, 16), dBp = desc_lo(sb + (cta ^ 1) * 2 * 8192, 16);
    const uint32_t dFo = desc_lo(sb + cta * 2 * 4096, 16), dFp = desc_lo(sb + (cta ^ 1) * 2 * 4096, 16);
    if (elect_one()) {
#pragma unroll
      for (int i = 0; i < 6; i++) init_bar(bars, 9 + warp * 6 + i);
      asm volatile("fence.mbarrier_init.release.cluster;" ::: "memory");
    }
    __syncwarp();
    cluster_sync_relaxed();
    if (w == 0) TS(wg, 0);

    if (ge_cta) {
      float ga[4];
      mbar_wait(bars + kBarG * 8);
      wg_fence();
#pragma unroll
      for (int i = 0; i < 4; i++) {
#pragma unroll
        for (int s = 0; s < 4; s++)
          wgmma_ss_n8(ga, desc_at(dA, (9 + i) * kSlot + s * 2048), desc_at(dB, kOffG + i * 1024 + s * 32), (i | s) != 0);
      }
      wg_commit();
      wg_wait<0>();
      if (lane == 0) mbar_arrive(bars + kBarP0 * 8);
      float* gp = g_ge + b * (kGEBytes / 4);
      gp[(2 * q) * (kGEPitch / 4) + ch] = ga[0];
      gp[(2 * q + 1) * (kGEPitch / 4) + ch] = ga[1];
      gp[(2 * q) * (kGEPitch / 4) + ch + 8] = ga[2];
      gp[(2 * q + 1) * (kGEPitch / 4) + ch + 8] = ga[3];
      __threadfence();
      bar_consumers();
      if (threadIdx.x == 0) asm volatile("red.release.gpu.global.add.u32 [%0], 1;" ::"l"(&g_ge_flag[b]) : "memory");
    }

    {
      float acc[32];
#pragma unroll
      for (int u = 0; u < 12; u++) {
        const int p = u / 3, tap = u % 3;
        if (tap == 0) mbar_wait(bars + (kBarX + p) * 8);
        mbar_wait(bars + (kBarW + u) * 8);
        if (u == 0 && w == 0) TS(wg, 1);
        wg_fence();
#pragma unroll
        for (int s = 0; s < 4; s++)
          wgmma_ss_n64(acc, desc_at(dA, unit_slot(u) * kSlot + s * 2048),
                       desc_at(dB, p * kSlot + (tap == 1 ? 8192 : (tap == 2 ? 128 : 0)) + s * 32), (u | s) != 0);
        wg_commit();
        if (u > 0) {
          wg_wait<1>();
          if (lane == 0) mbar_arrive(bars + (kBarE + u - 1) * 8);
        }
      }
      wg_wait<0>();
      if (lane == 0) mbar_arrive(bars + (kBarE + 11) * 8);
      if (w == 0) TS(wg, 2);
      const uint32_t hp = sb + kSlotH * kSlot + panel * 8192;
      const int mi = lane >> 3, l8 = lane & 7;
#pragma unroll
      for (int jb = 0; jb < 8; jb += 2) {
        uint32_t r[4];
#pragma unroll
        for (int t = 0; t < 2; t++) {
          r[2 * t + 0] = pack_bf16(gelu_tanh(acc[4 * (jb + t) + 0]), gelu_tanh(acc[4 * (jb + t) + 1]));
          r[2 * t + 1] = pack_bf16(gelu_tanh(acc[4 * (jb + t) + 2]), gelu_tanh(acc[4 * (jb + t) + 3]));
        }
        const int n = 8 * (jb + (mi >> 1)) + l8;
        const int row = n >> 1, chunk = 2 * w + (mi & 1);
        stsm_x4_trans(hp + (n & 1) * 4096 + row * 128 + ((chunk ^ (row & 7)) << 4), r[0], r[1], r[2], r[3]);
      }
      fence_async_smem();
      bar_consumers();
      if (warp == 0) {
        if (elect_one()) {
          const uint32_t src = sb + kSlotH * kSlot + cta * 16384;
          dsmem_copy(mapa(src, peer), src, 16384, mapa(bars + kBarHX * 8, peer));
        }
        __syncwarp();
      }
      if (w == 0) TS(wg, 3);
    }
    {
      float acc[16];
#pragma unroll
      for (int v = 0; v < 12; v++) {
        const int i = v / 3, tap = v % 3;
        if (v == 6) { mbar_wait_cluster(bars + kBarHX * 8); if (w == 0) TS(wg, 4); }
        mbar_wait(bars + (kBarW + 12 + v) * 8);
        wg_fence();
#pragma unroll
        for (int s = 0; s < 4; s++)
          wgmma_ss_n32(acc, desc_at(dA, unit_slot(12 + v) * kSlot + s * 2048),
                       desc_at(i < 2 ? dBo : dBp, kSlotH * kSlot + (i & 1) * 8192 + (tap == 1 ? 4096 : (tap == 2 ? 128 : 0)) + s * 32), (v | s) != 0);
        wg_commit();
        if (v > 0) {
          wg_wait<1>();
          if (lane == 0) mbar_arrive(bars + (kBarE + 12 + v - 1) * 8);
        }
      }
      wg_wait<0>();
      if (lane == 0) mbar_arrive(bars + (kBarE + 23) * 8);
      if (w == 0) TS(wg, 5);
      const uint32_t fp = sb + kSlotF * kSlot + panel * 4096;
      const int mi = lane >> 3, l8 = lane & 7;
#pragma unroll
      for (int jb = 0; jb < 4; jb += 2) {
        uint32_t r[4];
#pragma unroll
        for (int t = 0; t < 2; t++) {
          r[2 * t + 0] = pack_bf16(gelu_tanh(acc[4 * (jb + t) + 0]), gelu_tanh(acc[4 * (jb + t) + 1]));
          r[2 * t + 1] = pack_bf16(gelu_tanh(acc[4 * (jb + t) + 2]), gelu_tanh(acc[4 * (jb + t) + 3]));
        }
        const int n = 8 * (jb + (mi >> 1)) + l8;
        const int chunk = 2 * w + (mi & 1);
        stsm_x4_trans(fp + n * 128 + ((chunk ^ (n & 7)) << 4), r[0], r[1], r[2], r[3]);
      }
      fence_async_smem();
      bar_consumers();
      if (warp == 0) {
        if (elect_one()) {
          const uint32_t src = sb + kSlotF * kSlot + cta * 8192;
          dsmem_copy(mapa(src, peer), src, 8192, mapa(bars + kBarFX * 8, peer));
        }
        __syncwarp();
      }
      if (w == 0) TS(wg, 6);
    }
    {
      float acc[16];
#pragma unroll
      for (int i = 0; i < 4; i++) {
        if (i == 2) { mbar_wait_cluster(bars + kBarFX * 8); if (w == 0) TS(wg, 7); }
        mbar_wait(bars + (kBarW + 24 + i) * 8);
        wg_fence();
#pragma unroll
        for (int s = 0; s < 4; s++)
          wgmma_ss_n32(acc, desc_at(dA, unit_slot(24 + i) * kSlot + s * 2048),
                       desc_at(i < 2 ? dFo : dFp, kSlotF * kSlot + (i & 1) * 4096 + s * 32), (i | s) != 0);
        wg_commit();
        if (i > 0) {
          wg_wait<1>();
          if (lane == 0) mbar_arrive(bars + (kBarE + 24 + i - 1) * 8);
        }
      }
      wg_wait<0>();
      if (w == 0) TS(wg, 8);
      const uint32_t sw = ((ch >> 1) & 3) * 2;
      const uint32_t own = sb + kSlotFE * kSlot + ch * 64;
      const uint32_t stg = sb + kSlotH * kSlot + (ch - (int)cta * 128) * 64;
#pragma unroll
      for (int jb = 0; jb < 4; jb++) {
        const uint32_t base = ((uint32_t)(jb >> 1) == cta) ? own : stg;
        const uint32_t pr = (4 * (jb & 1) + q) ^ sw;
        sts64(base + pr * 8, acc[4 * jb + 0], acc[4 * jb + 1]);
        sts64(base + 512 + pr * 8, acc[4 * jb + 2], acc[4 * jb + 3]);
      }
      fence_async_smem();
      bar_wg(wg);
      if (w == 0) {
        if (elect_one())
          dsmem_copy(mapa(sb + kSlotFE * kSlot + panel * 4096, peer), sb + kSlotH * kSlot + wg * 4096, 4096, mapa(bars + kBarFE * 8, peer));
        __syncwarp();
      }
      if (lane == 0) mbar_arrive(bars + kBarFE * 8);
      if (w == 0) TS(wg, 9);
    }
    const int rl0 = cta * 16 + wg * 8;
    mbar_wait_cluster(bars + kBarFE * 8);
    asm volatile("barrier.cluster.arrive.relaxed.aligned;" ::: "memory");
    if (wg == 1) asm volatile("bar.sync 4, 256;" ::: "memory");
    if (rl0 < rvalid) {
      if (w == 0) TS(wg, 10);
      const uint32_t fe_t = sb + kSlotFE * kSlot + (2 * q) * 64 + (((4 * wg + w) ^ (2 * q)) << 3);
      const uint32_t ge_t = sb + kOffGE + gq * kGEPitch + (2 * q) * 4;
      const int mi = lane >> 3, l8 = lane & 7;
      const CUtensorMap* omap = (rl0 + 8 <= rvalid) ? &P.out64 : &P.out56;
      const int grow = (b * kT2 + r0 + rl0) * 8;
      const uint32_t st = sb + (wg ? 12 : 8) * kSlot + (16 * w + (mi & 1) * 8 + l8) * 128;
      uint32_t A[64];
      float acc[2][32];
#pragma unroll
      for (int g4 = 0; g4 < 4; g4++) {
#pragma unroll
        for (int k4 = 0; k4 < 4; k4++) {
          const int kk = g4 * 4 + k4;
          const float2 f0 = lds64(fe_t + kk * 1024), f1 = lds64(fe_t + kk * 1024 + 64);
          const float2 f2 = lds64(fe_t + kk * 1024 + 512), f3 = lds64(fe_t + kk * 1024 + 576);
          const float2 g0 = lds64(ge_t + kk * 64), g1 = lds64(ge_t + kk * 64 + 32);
          A[4 * kk + 0] = pack_bf16(tanh_fast(f0.x + g0.x), tanh_fast(f1.x + g0.y));
          A[4 * kk + 1] = pack_bf16(tanh_fast(f0.y + g0.x), tanh_fast(f1.y + g0.y));
          A[4 * kk + 2] = pack_bf16(tanh_fast(f2.x + g1.x), tanh_fast(f3.x + g1.y));
          A[4 * kk + 3] = pack_bf16(tanh_fast(f2.y + g1.x), tanh_fast(f3.y + g1.y));
        }
        if (g4 == 3 && wg == 0) asm volatile("bar.arrive 4, 256;" ::: "memory");
        mbar_wait(bars + (kBarW + 28 + g4) * 8);
        wg_fence();
#pragma unroll
        for (int k4 = 0; k4 < 4; k4++) {
          const int kk = g4 * 4 + k4;
          wgmma_rs_n64(acc[0], A[4 * kk], A[4 * kk + 1], A[4 * kk + 2], A[4 * kk + 3],
                       desc_at(dB, unit_slot(28 + g4) * kSlot + k4 * 2048), kk != 0);
        }
        wg_commit();
      }
      if (w == 0) TS(wg, 11);
#pragma unroll
      for (int j = 0; j < 4; j++) {
        if (j < 3) {
          const int jn = j + 1;
          wg_fence();
#pragma unroll
          for (int kk = 0; kk < 16; kk++) {
            if (jn == 2 && (kk & 3) == 0) { mbar_wait(bars + (kBarW + 32 + (kk >> 2)) * 8); wg_fence(); }
            wgmma_rs_n64(acc[jn & 1], A[4 * kk], A[4 * kk + 1], A[4 * kk + 2], A[4 * kk + 3],
                         desc_at(dB, unit_slot(28 + (jn >> 1) * 4 + (kk >> 2)) * kSlot + (jn & 1) * 8192 + (kk & 3) * 2048), kk != 0);
            if (kk == 1) { wg_commit(); wg_wait<1>(); }
            if (kk == 1) {
              if (j >= 2) {
              }
            }
            if (kk == 1) {
              if (j >= 2) {
                if (w == 0) { if (elect_one()) asm volatile("cp.async.bulk.wait_group.read 1;" ::: "memory"); __syncwarp(); }
                bar_wg(wg);
              }
#pragma unroll
              for (int jb = 0; jb < 8; jb += 2) {
                const uint32_t r0_ = pack_bf16(acc[j & 1][4 * jb + 0], acc[j & 1][4 * jb + 1]), r1_ = pack_bf16(acc[j & 1][4 * jb + 2], acc[j & 1][4 * jb + 3]);
                const uint32_t r2_ = pack_bf16(acc[j & 1][4 * jb + 4], acc[j & 1][4 * jb + 5]), r3_ = pack_bf16(acc[j & 1][4 * jb + 6], acc[j & 1][4 * jb + 7]);
                stsm_x4(st + (j & 1) * 8192 + (((jb + (mi >> 1)) ^ l8) << 4), r0_, r1_, r2_, r3_);
              }
              fence_async_smem();
              bar_wg(wg);
              if (w == 0) {
                if (elect_one()) {
                  tma_store_3d(omap, sb + (wg ? 12 : 8) * kSlot + (j & 1) * 8192, 0, grow, j);
                  asm volatile("cp.async.bulk.commit_group;" ::: "memory");
                }
                __syncwarp();
              }
              if (j == 0 && w == 0) TS(wg, 12);
              wg_fence();
            }
          }
          wg_commit();
        } else {
          wg_wait<0>();
          if (w == 0) TS(wg, 13);
          if (w == 0) { if (elect_one()) asm volatile("cp.async.bulk.wait_group.read 1;" ::: "memory"); __syncwarp(); }
          bar_wg(wg);
#pragma unroll
          for (int jb = 0; jb < 8; jb += 2) {
            const uint32_t r0_ = pack_bf16(acc[1][4 * jb + 0], acc[1][4 * jb + 1]), r1_ = pack_bf16(acc[1][4 * jb + 2], acc[1][4 * jb + 3]);
            const uint32_t r2_ = pack_bf16(acc[1][4 * jb + 4], acc[1][4 * jb + 5]), r3_ = pack_bf16(acc[1][4 * jb + 6], acc[1][4 * jb + 7]);
            stsm_x4(st + 8192 + (((jb + (mi >> 1)) ^ l8) << 4), r0_, r1_, r2_, r3_);
          }
          fence_async_smem();
          bar_wg(wg);
          if (w == 0) {
            if (elect_one()) {
              tma_store_3d(omap, sb + (wg ? 12 : 8) * kSlot + 8192, 0, grow, 3);
              asm volatile("cp.async.bulk.commit_group;" ::: "memory");
              asm volatile("cp.async.bulk.wait_group.read 0;" ::: "memory");
            }
            __syncwarp();
          }
        }
      }
      if (w == 0) TS(wg, 14);
    } else if (wg == 0) {
      asm volatile("bar.arrive 4, 256;" ::: "memory");
    }
    asm volatile("barrier.cluster.wait.aligned;" ::: "memory");
  }
}

typedef CUresult (*EncodeFn)(CUtensorMap*, CUtensorMapDataType, cuuint32_t, void*, const cuuint64_t*, const cuuint64_t*,
                             const cuuint32_t*, const cuuint32_t*, CUtensorMapInterleave, CUtensorMapSwizzle,
                             CUtensorMapL2promotion, CUtensorMapFloatOOBfill);

void make_map3(EncodeFn enc, CUtensorMap* tm, const void* ptr, uint64_t rows, uint32_t box_rows, uint32_t box_panels) {
  cuuint64_t gd[3] = {64, rows, 4};
  cuuint64_t gs[2] = {512, 128};
  cuuint32_t bd[3] = {64, box_rows, box_panels};
  cuuint32_t es[3] = {1, 1, 1};
  enc(tm, CU_TENSOR_MAP_DATA_TYPE_BFLOAT16, 3, const_cast<void*>(ptr), gd, gs, bd, es, CU_TENSOR_MAP_INTERLEAVE_NONE,
      CU_TENSOR_MAP_SWIZZLE_128B, CU_TENSOR_MAP_L2_PROMOTION_L2_256B, CU_TENSOR_MAP_FLOAT_OOB_FILL_NONE);
}

}

extern "C" void kernel_launch(void* const* d_in, const int* in_sizes, int n_in, void* d_out, int out_size) {
  static EncodeFn enc = nullptr;
  if (!enc) {
    cudaDriverEntryPointQueryResult qr;
    cudaGetDriverEntryPoint("cuTensorMapEncodeTiled", (void**)&enc, cudaEnableDefault, &qr);
    cudaFuncSetAttribute(rnnt_joint_kernel, cudaFuncAttributeMaxDynamicSharedMemorySize, kSmemBytes);
  }
  Params P;
  {
    cuuint64_t gd[4] = {256, 2, 2000, 2};
    cuuint64_t gs[3] = {512, 1024, 4000ull * 512};
    cuuint32_t bd[4] = {64, 1, 64, 1};
    cuuint32_t es[4] = {1, 1, 1, 1};
    enc(&P.x, CU_TENSOR_MAP_DATA_TYPE_BFLOAT16, 4, d_in[0], gd, gs, bd, es, CU_TENSOR_MAP_INTERLEAVE_NONE,
        CU_TENSOR_MAP_SWIZZLE_128B, CU_TENSOR_MAP_L2_PROMOTION_L2_256B, CU_TENSOR_MAP_FLOAT_OOB_FILL_NONE);
  }
  make_map3(enc, &P.w1, d_in[1], 768, 64, 2);
  make_map3(enc, &P.w2, d_in[2], 768, 64, 2);
  make_map3(enc, &P.g, d_in[3], 16, 8, 4);
  make_map3(enc, &P.wf, d_in[4], 256, 64, 2);
  make_map3(enc, &P.wg, d_in[5], 256, 64, 2);
  make_map3(enc, &P.wo, d_in[6], 256, 64, 2);
  make_map3(enc, &P.out64, d_out, 16000, 64, 1);
  make_map3(enc, &P.out56, d_out, 16000, 56, 1);
  rnnt_joint_kernel<<<kNumCtas, kThreads, kSmemBytes>>>(P);
}
```

```cpp
#include <cuda_runtime.h>
#include <cuda_bf16.h>
#include <cuda.h>
#include <stdint.h>

namespace {

constexpr int kT2 = 1000;
constexpr int kR = 31;
constexpr int kNumCtas = 132;
constexpr int kThreads = 384;
constexpr int kSlot = 16384;

constexpr int kSlotFE = 9, kSlotF = 10, kSlotH = 11;
constexpr int kOffG = 13 * kSlot;
constexpr int kOffGE = kOffG + 4096;
constexpr int kGEPitch = 1056;
constexpr int kGEBytes = 8 * kGEPitch;
constexpr int kOffBar = kOffGE + kGEBytes;
constexpr int kBarX = 0;
constexpr int kBarW = 4;
constexpr int kBarE = 40;
constexpr int kBarHX = 67, kBarFX = 68, kBarFE = 69, kBarG = 70, kBarP0 = 71;
constexpr int kNumBars = 72;
constexpr int kSmemBytes = kOffBar + kNumBars * 8 + 1024;

__device__ float g_ge[2 * kGEBytes / 4];
__device__ unsigned int g_ge_flag[2];
__device__ unsigned int g_cta_count;

#define TS(slot_, idx_) do {} while (0)

__device__ __forceinline__ uint32_t smem_u32(const void* p) { return (uint32_t)__cvta_generic_to_shared(p); }
__device__ __forceinline__ void mbar_init(uint32_t a, uint32_t c) { asm volatile("mbarrier.init.shared.b64 [%0], %1;" ::"r"(a), "r"(c) : "memory"); }
__device__ __forceinline__ void mbar_expect(uint32_t a, uint32_t b) { asm volatile("mbarrier.arrive.expect_tx.shared.b64 _, [%0], %1;" ::"r"(a), "r"(b) : "memory"); }
__device__ __forceinline__ void mbar_arrive(uint32_t a) { asm volatile("mbarrier.arrive.shared.b64 _, [%0];" ::"r"(a) : "memory"); }
__device__ __forceinline__ bool mbar_try(uint32_t a) {
  uint32_t ok;
  asm volatile("{\n.reg .pred p;\nmbarrier.try_wait.parity.shared.b64 p, [%1], 0;\nselp.u32 %0, 1, 0, p;\n}\n" : "=r"(ok) : "r"(a) : "memory");
  return ok != 0;
}
__device__ __forceinline__ bool mbar_try_cluster(uint32_t a) {
  uint32_t ok;
  asm volatile("{\n.reg .pred p;\nmbarrier.try_wait.parity.acquire.cluster.shared.b64 p, [%1], 0;\nselp.u32 %0, 1, 0, p;\n}\n" : "=r"(ok) : "r"(a) : "memory");
  return ok != 0;
}
__device__ __forceinline__ void mbar_wait_slow(uint32_t a) {
  const long long t0 = clock64();
  while (!mbar_try(a)) { if (clock64() - t0 > 4000000ll) break; }
}
__device__ __forceinline__ void mbar_wait_cluster_slow(uint32_t a) {
  const long long t0 = clock64();
  while (!mbar_try_cluster(a)) { if (clock64() - t0 > 4000000ll) break; }
}
__device__ __forceinline__ void mbar_wait(uint32_t a) { if (!mbar_try(a)) mbar_wait_slow(a); }
__device__ __forceinline__ void mbar_wait_cluster(uint32_t a) { if (!mbar_try_cluster(a)) mbar_wait_cluster_slow(a); }
__device__ __forceinline__ uint32_t mapa(uint32_t a, uint32_t r) { uint32_t d; asm volatile("mapa.shared::cluster.u32 %0, %1, %2;" : "=r"(d) : "r"(a), "r"(r)); return d; }
__device__ __forceinline__ bool elect_one() { uint32_t p; asm volatile("{\n.reg .pred P;\nelect.sync _|P, 0xffffffff;\nselp.u32 %0, 1, 0, P;\n}\n" : "=r"(p)); return p != 0; }
__device__ __forceinline__ void fence_async_smem() { asm volatile("fence.proxy.async.shared::cta;" ::: "memory"); }
__device__ __forceinline__ void bar_consumers() { asm volatile("bar.sync 1, 256;" ::: "memory"); }
__device__ __forceinline__ void bar_wg(int wg) { asm volatile("bar.sync %0, 128;" ::"r"(2 + wg) : "memory"); }
__device__ __forceinline__ void cluster_sync_relaxed() { asm volatile("barrier.cluster.arrive.relaxed.aligned;\nbarrier.cluster.wait.aligned;" ::: "memory"); }
__device__ __forceinline__ void wg_fence() { asm volatile("wgmma.fence.sync.aligned;" ::: "memory"); }
__device__ __forceinline__ void wg_commit() { asm volatile("wgmma.commit_group.sync.aligned;" ::: "memory"); }
template <int N> __device__ __forceinline__ void wg_wait() { asm volatile("wgmma.wait_group.sync.aligned %0;" ::"n"(N) : "memory"); }

__device__ __forceinline__ void tma_load_3d(uint32_t dst, const CUtensorMap* tm, uint32_t bar, int c0, int c1, int c2) {
  asm volatile("cp.async.bulk.tensor.3d.shared::cluster.global.mbarrier::complete_tx::bytes [%0], [%1, {%3, %4, %5}], [%2];"
               ::"r"(dst), "l"(tm), "r"(bar), "r"(c0), "r"(c1), "r"(c2) : "memory");
}
__device__ __forceinline__ void tma_load_4d_mc(uint32_t dst, const CUtensorMap* tm, uint32_t bar, int c0, int c1, int c2, int c3, uint16_t mask) {
  asm volatile("cp.async.bulk.tensor.4d.shared::cluster.global.mbarrier::complete_tx::bytes.multicast::cluster [%0], [%1, {%3, %4, %5, %6}], [%2], %7;"
               ::"r"(dst), "l"(tm), "r"(bar), "r"(c0), "r"(c1), "r"(c2), "r"(c3), "h"(mask) : "memory");
}
__device__ __forceinline__ void tma_store_3d(const CUtensorMap* tm, uint32_t src, int c0, int c1, int c2) {
  asm volatile("cp.async.bulk.tensor.3d.global.shared::cta.bulk_group [%0, {%2, %3, %4}], [%1];"
               ::"l"(tm), "r"(src), "r"(c0), "r"(c1), "r"(c2) : "memory");
}
__device__ __forceinline__ void bulk_load(uint32_t dst, const void* src, uint32_t bytes, uint32_t bar) {
  asm volatile("cp.async.bulk.shared::cluster.global.mbarrier::complete_tx::bytes [%0], [%1], %2, [%3];"
               ::"r"(dst), "l"(src), "r"(bytes), "r"(bar) : "memory");
}
__device__ __forceinline__ void dsmem_copy(uint32_t dst_remote, uint32_t src, uint32_t bytes, uint32_t bar_remote) {
  asm volatile("cp.async.bulk.shared::cluster.shared::cta.mbarrier::complete_tx::bytes [%0], [%1], %2, [%3];"
               ::"r"(dst_remote), "r"(src), "r"(bytes), "r"(bar_remote) : "memory");
}
__device__ __forceinline__ void stsm_x4_trans(uint32_t addr, uint32_t r0, uint32_t r1, uint32_t r2, uint32_t r3) {
  asm volatile("stmatrix.sync.aligned.m8n8.x4.trans.shared.b16 [%0], {%1, %2, %3, %4};" ::"r"(addr), "r"(r0), "r"(r1), "r"(r2), "r"(r3) : "memory");
}
__device__ __forceinline__ void stsm_x4(uint32_t addr, uint32_t r0, uint32_t r1, uint32_t r2, uint32_t r3) {
  asm volatile("stmatrix.sync.aligned.m8n8.x4.shared.b16 [%0], {%1, %2, %3, %4};" ::"r"(addr), "r"(r0), "r"(r1), "r"(r2), "r"(r3) : "memory");
}
__device__ __forceinline__ float2 lds64(uint32_t a) { float2 v; asm volatile("ld.shared.v2.f32 {%0, %1}, [%2];" : "=f"(v.x), "=f"(v.y) : "r"(a) : "memory"); return v; }
__device__ __forceinline__ void sts64(uint32_t a, float x, float y) { asm volatile("st.shared.v2.f32 [%0], {%1, %2};" ::"r"(a), "f"(x), "f"(y) : "memory"); }
__device__ __forceinline__ float tanh_fast(float x) { float y; asm("tanh.approx.f32 %0, %1;" : "=f"(y) : "f"(x)); return y; }
__device__ __forceinline__ uint32_t pack_bf16(float lo, float hi) { uint32_t r; asm("cvt.rn.bf16x2.f32 %0, %1, %2;" : "=r"(r) : "f"(hi), "f"(lo)); return r; }
__device__ __forceinline__ float gelu_tanh(float x) {
  const float k0 = 0.7978845608028654f, k1 = 0.7978845608028654f * 0.044715f;
  float u = x * fmaf(x * x, k1, k0);
  float hx = 0.5f * x;
  return fmaf(hx, tanh_fast(u), hx);
}
__device__ __forceinline__ uint64_t make_desc(uint32_t addr, uint32_t lbo, uint32_t sbo) {
  return (uint64_t)((addr & 0x3FFFF) >> 4) | ((uint64_t)(lbo >> 4) << 16) | ((uint64_t)(sbo >> 4) << 32) | ((uint64_t)1 << 62);
}

__device__ __forceinline__ uint32_t desc_lo(uint32_t addr, uint32_t lbo) { return ((addr & 0x3FFFF) >> 4) | ((lbo >> 4) << 16); }
__device__ __forceinline__ uint64_t desc_at(uint32_t lo, uint32_t off) { return ((uint64_t)0x40000040u << 32) | (uint64_t)(lo + (off >> 4)); }

__device__ __forceinline__ void wgmma_ss_n64(float (&d)[32], uint64_t da, uint64_t db, int scale_d) {
  asm volatile("{\n.reg .pred p;\nsetp.ne.b32 p, %34, 0;\n"
    "wgmma.mma_async.sync.aligned.m64n64k16.f32.bf16.bf16 {%0, %1, %2, %3, %4, %5, %6, %7, %8, %9, %10, %11, %12, %13, %14, %15, %16, %17, %18, %19, %20, %21, %22, %23, %24, %25, %26, %27, %28, %29, %30, %31}, %32, %33, p, 1, 1, 1, 0;\n}\n"
    : "+f"(d[0]), "+f"(d[1]), "+f"(d[2]), "+f"(d[3]), "+f"(d[4]), "+f"(d[5]), "+f"(d[6]), "+f"(d[7]), "+f"(d[8]), "+f"(d[9]), "+f"(d[10]), "+f"(d[11]), "+f"(d[12]), "+f"(d[13]), "+f"(d[14]), "+f"(d[15]), "+f"(d[16]), "+f"(d[17]), "+f"(d[18]), "+f"(d[19]), "+f"(d[20]), "+f"(d[21]), "+f"(d[22]), "+f"(d[23]), "+f"(d[24]), "+f"(d[25]), "+f"(d[26]), "+f"(d[27]), "+f"(d[28]), "+f"(d[29]), "+f"(d[30]), "+f"(d[31])
    : "l"(da), "l"(db), "r"(scale_d));
}

__device__ __forceinline__ void wgmma_ss_n32(float (&d)[16], uint64_t da, uint64_t db, int scale_d) {
  asm volatile("{\n.reg .pred p;\nsetp.ne.b32 p, %18, 0;\n"
    "wgmma.mma_async.sync.aligned.m64n32k16.f32.bf16.bf16 {%0, %1, %2, %3, %4, %5, %6, %7, %8, %9, %10, %11, %12, %13, %14, %15}, %16, %17, p, 1, 1, 1, 0;\n}\n"
    : "+f"(d[0]), "+f"(d[1]), "+f"(d[2]), "+f"(d[3]), "+f"(d[4]), "+f"(d[5]), "+f"(d[6]), "+f"(d[7]), "+f"(d[8]), "+f"(d[9]), "+f"(d[10]), "+f"(d[11]), "+f"(d[12]), "+f"(d[13]), "+f"(d[14]), "+f"(d[15])
    : "l"(da), "l"(db), "r"(scale_d));
}

__device__ __forceinline__ void wgmma_ss_n8(float (&d)[4], uint64_t da, uint64_t db, int scale_d) {
  asm volatile("{\n.reg .pred p;\nsetp.ne.b32 p, %6, 0;\n"
    "wgmma.mma_async.sync.aligned.m64n8k16.f32.bf16.bf16 {%0, %1, %2, %3}, %4, %5, p, 1, 1, 1, 0;\n}\n"
    : "+f"(d[0]), "+f"(d[1]), "+f"(d[2]), "+f"(d[3])
    : "l"(da), "l"(db), "r"(scale_d));
}

__device__ __forceinline__ void wgmma_rs_n64(float (&d)[32], uint32_t a0, uint32_t a1, uint32_t a2, uint32_t a3, uint64_t db, int scale_d) {
  asm volatile("{\n.reg .pred p;\nsetp.ne.b32 p, %37, 0;\n"
    "wgmma.mma_async.sync.aligned.m64n64k16.f32.bf16.bf16 {%0, %1, %2, %3, %4, %5, %6, %7, %8, %9, %10, %11, %12, %13, %14, %15, %16, %17, %18, %19, %20, %21, %22, %23, %24, %25, %26, %27, %28, %29, %30, %31}, {%32, %33, %34, %35}, %36, p, 1, 1, 1;\n}\n"
    : "+f"(d[0]), "+f"(d[1]), "+f"(d[2]), "+f"(d[3]), "+f"(d[4]), "+f"(d[5]), "+f"(d[6]), "+f"(d[7]), "+f"(d[8]), "+f"(d[9]), "+f"(d[10]), "+f"(d[11]), "+f"(d[12]), "+f"(d[13]), "+f"(d[14]), "+f"(d[15]), "+f"(d[16]), "+f"(d[17]), "+f"(d[18]), "+f"(d[19]), "+f"(d[20]), "+f"(d[21]), "+f"(d[22]), "+f"(d[23]), "+f"(d[24]), "+f"(d[25]), "+f"(d[26]), "+f"(d[27]), "+f"(d[28]), "+f"(d[29]), "+f"(d[30]), "+f"(d[31])
    : "r"(a0), "r"(a1), "r"(a2), "r"(a3), "l"(db), "r"(scale_d));
}

__host__ __device__ constexpr int unit_slot(int u) {
  constexpr int t[36] = {4, 5, 6, 7, 8, 4, 5, 6, 0, 7, 8, 4,  1, 5, 6, 0, 2, 7, 8, 4, 3, 1, 5, 6,
                         0, 2, 7, 8,  4, 3, 1, 5, 6, 0, 2, 7};
  return t[u];
}
__host__ __device__ constexpr int unit_wait(int u) {
  constexpr int t[36] = {-1, -1, -1, -1, -1, 0, 1, 2, 2, 3, 4, 5,  5, 6, 7, 8, 8, 9, 10, 11, 11, 12, 13, 14,
                         15, 16, 17, 18,  19, 20, 21, 22, 23, 24, 25, 26};
  return t[u];
}

struct Params {
  CUtensorMap x, w1, w2, wf, wg, wo, g, out64, out56;
};

__device__ __forceinline__ void init_bar(uint32_t bars, int i) {
  const uint32_t a = bars + i * 8;
  const bool is_e = (i >= kBarE && i < kBarE + 27);
  mbar_init(a, is_e ? 8 : (i == kBarFE ? 9 : 1));
  if (!is_e) {
    uint32_t bytes = 16384;
    if (i == kBarFX) bytes = 8192;
    if (i == kBarFE) bytes = 8192 + kGEBytes;
    mbar_expect(a, bytes);
  }
}

__global__ void __cluster_dims__(2, 1, 1) __launch_bounds__(kThreads, 1)
rnnt_joint_kernel(const __grid_constant__ Params P) {
  extern __shared__ uint8_t smem_raw[];
  const uint32_t sb = (smem_u32(smem_raw) + 1023u) & ~1023u;
  const uint32_t bars = sb + kOffBar;
  const int warp = threadIdx.x >> 5, lane = threadIdx.x & 31;
  uint32_t cta;
  asm volatile("mov.u32 %0, %%cluster_ctarank;" : "=r"(cta));
  const uint32_t peer = cta ^ 1u;
  const int cl = blockIdx.x >> 1;
  const bool ge_cta = cl < 2;
  const int b = ge_cta ? cl : ((cl - 2) >> 5);
  const int r0 = ge_cta ? 32 * kR : ((cl - 2) & 31) * kR;
  const int rvalid = ge_cta ? kT2 - 32 * kR : kR;

  if (warp >= 8) {
    asm volatile("setmaxnreg.dec.sync.aligned.u32 40;");
    if (warp > 8) {
      if (elect_one()) {
#pragma unroll
        for (int i = 0; i < 6; i++) if (9 + (warp - 1) * 6 + i < kBarG) init_bar(bars, 9 + (warp - 1) * 6 + i);
        asm volatile("fence.mbarrier_init.release.cluster;" ::: "memory");
      }
      __syncwarp();
      cluster_sync_relaxed();
      return;
    }
    TS(2, 0);
    unsigned int ticket = 0;
    const int par = cta == 0 ? 1 : 0;
    const int q0 = cta == 0 ? 2 * r0 - 2 : 2 * r0 - 1;
    if (elect_one()) {
#pragma unroll
      for (int p = 0; p < 2; p += 2)
        asm volatile("cp.async.bulk.prefetch.tensor.4d.L2.global.tile [%0, {%1, %2, %3, %4}];" ::"l"(&P.x), "r"(p * 64), "r"(par), "r"(q0), "r"(b) : "memory");
#pragma unroll
      for (int i = 0; i < 9; i++) { mbar_init(bars + i * 8, 1); mbar_expect(bars + i * 8, 16384); }
      if (ge_cta) { mbar_init(bars + kBarG * 8, 1); mbar_expect(bars + kBarG * 8, 4 * 16384 + 4096); mbar_init(bars + kBarP0 * 8, 8); }
      TS(2, 7);
      asm volatile("fence.mbarrier_init.release.cluster;" ::: "memory");
      fence_async_smem();
      TS(2, 8);
      if (ge_cta) {
        tma_load_3d(sb + kOffG, &P.g, bars + kBarG * 8, 0, b * 8, 0);
#pragma unroll
        for (int i = 0; i < 4; i++) tma_load_3d(sb + (9 + i) * kSlot, &P.wg, bars + kBarG * 8, 0, i * 64, 2 * cta);
      }
#pragma unroll
      for (int u = 0; u < 5; u++)
      {
        tma_load_3d(sb + unit_slot(u) * kSlot, &P.w1, bars + (kBarW + u) * 8, 0, (u % 3) * 256 + (u / 3) * 64, 2 * cta);
        if (u == 0) TS(2, 9);
      }
      TS(2, 10);
    }
    __syncwarp();
    TS(2, 6);
    cluster_sync_relaxed();
    TS(2, 1);
    if (elect_one()) {
#pragma unroll
      for (int p = 0; p < 2; p++)
        tma_load_4d_mc(sb + p * kSlot + cta * 8192, &P.x, bars + (kBarX + p) * 8, p * 64, par, q0, b, (uint16_t)3);
    }
    __syncwarp();
    if (lane == 0) ticket = atomicAdd(&g_cta_count, 1u);
    mbar_wait(bars + kBarX * 8);
    if (ge_cta) mbar_wait(bars + kBarP0 * 8);
    if (elect_one()) {
#pragma unroll
      for (int p = 2; p < 4; p++)
        tma_load_4d_mc(sb + p * kSlot + cta * 8192, &P.x, bars + (kBarX + p) * 8, p * 64, par, q0, b, (uint16_t)3);
    }
    __syncwarp();
#pragma unroll
    for (int u = 5; u < 36; u++) {
      if (unit_wait(u) != unit_wait(u - 1)) mbar_wait(bars + (kBarE + unit_wait(u)) * 8);
      if (u == 27) ticket = __shfl_sync(0xffffffffu, ticket, 0);
      if (elect_one()) {
        const uint32_t dst = sb + unit_slot(u) * kSlot, bar = bars + (kBarW + u) * 8;
        if (u < 12) tma_load_3d(dst, &P.w1, bar, 0, (u % 3) * 256 + (u / 3) * 64, 2 * cta);
        else if (u < 24) tma_load_3d(dst, &P.w2, bar, 0, ((u - 12) % 3) * 256 + ((2 * cta + (u - 12) / 3) & 3) * 64, 2 * cta);
        else if (u < 28) tma_load_3d(dst, &P.wf, bar, 0, ((2 * cta + (u - 24)) & 3) * 64, 2 * cta);
        else tma_load_3d(dst, &P.wo, bar, 0, ((u - 28) & 3) * 64, ((u - 28) >> 2) * 2);
        if (u == 27) {
          const unsigned int want = (ticket / kNumCtas + 1u) * 2u;
          const long long t0 = clock64();
          unsigned int v;
          do {
            asm volatile("ld.acquire.gpu.global.u32 %0, [%1];" : "=r"(v) : "l"(&g_ge_flag[b]) : "memory");
          } while ((int)(v - want) < 0 && clock64() - t0 < 4000000ll);
          asm volatile("fence.proxy.async;" ::: "memory");
          bulk_load(sb + kOffGE, reinterpret_cast<const char*>(g_ge) + b * kGEBytes, kGEBytes, bars + kBarFE * 8);
        }
      }
      __syncwarp();
      if (u == 11) TS(2, 2);
      if (u == 23) TS(2, 3);
      if (u == 27) TS(2, 4);
      if (u == 35) TS(2, 5);
    }
  } else {
    asm volatile("setmaxnreg.inc.sync.aligned.u32 232;");
    const int wg = warp >> 2, w = warp & 3;
    const int gq = lane >> 2, q = lane & 3;
    const uint32_t panel = 2 * cta + wg;
    const int ch = panel * 64 + w * 16 + gq;
    const uint32_t dA = desc_lo(sb + wg * 8192, 8192);
    const uint32_t dB = desc_lo(sb, 16);
    const uint32_t dBo = desc_lo(sb + cta * 2 * 8192, 16), dBp = desc_lo(sb + (cta ^ 1) * 2 * 8192, 16);
    const uint32_t dFo = desc_lo(sb + cta * 2 * 4096, 16), dFp = desc_lo(sb + (cta ^ 1) * 2 * 4096, 16);
    if (elect_one()) {
#pragma unroll
      for (int i = 0; i < 6; i++) init_bar(bars, 9 + warp * 6 + i);
      asm volatile("fence.mbarrier_init.release.cluster;" ::: "memory");
    }
    __syncwarp();
    cluster_sync_relaxed();
    if (w == 0) TS(wg, 0);

    if (ge_cta) {
      float ga[4];
      mbar_wait(bars + kBarG * 8);
      wg_fence();
#pragma unroll
      for (int i = 0; i < 4; i++) {
#pragma unroll
        for (int s = 0; s < 4; s++)
          wgmma_ss_n8(ga, desc_at(dA, (9 + i) * kSlot + s * 2048), desc_at(dB, kOffG + i * 1024 + s * 32), (i | s) != 0);
      }
      wg_commit();
      wg_wait<0>();
      if (lane == 0) mbar_arrive(bars + kBarP0 * 8);
      float* gp = g_ge + b * (kGEBytes / 4);
      gp[(2 * q) * (kGEPitch / 4) + ch] = ga[0];
      gp[(2 * q + 1) * (kGEPitch / 4) + ch] = ga[1];
      gp[(2 * q) * (kGEPitch / 4) + ch + 8] = ga[2];
      gp[(2 * q + 1) * (kGEPitch / 4) + ch + 8] = ga[3];
      __threadfence();
      bar_consumers();
      if (threadIdx.x == 0) asm volatile("red.release.gpu.global.add.u32 [%0], 1;" ::"l"(&g_ge_flag[b]) : "memory");
    }

    {
      float acc[32];
#pragma unroll
      for (int u = 0; u < 12; u++) {
        const int p = u / 3, tap = u % 3;
        if (tap == 0) mbar_wait(bars + (kBarX + p) * 8);
        mbar_wait(bars + (kBarW + u) * 8);
        if (u == 0 && w == 0) TS(wg, 1);
        wg_fence();
#pragma unroll
        for (int s = 0; s < 4; s++)
          wgmma_ss_n64(acc, desc_at(dA, unit_slot(u) * kSlot + s * 2048),
                       desc_at(dB, p * kSlot + (tap == 1 ? 8192 : (tap == 2 ? 128 : 0)) + s * 32), (u | s) != 0);
        wg_commit();
        if (u > 0) {
          wg_wait<1>();
          if (lane == 0) mbar_arrive(bars + (kBarE + u - 1) * 8);
        }
      }
      wg_wait<0>();
      if (lane == 0) mbar_arrive(bars + (kBarE + 11) * 8);
      if (w == 0) TS(wg, 2);
      const uint32_t hp = sb + kSlotH * kSlot + panel * 8192;
      const int mi = lane >> 3, l8 = lane & 7;
#pragma unroll
      for (int jb = 0; jb < 8; jb += 2) {
        uint32_t r[4];
#pragma unroll
        for (int t = 0; t < 2; t++) {
          r[2 * t + 0] = pack_bf16(gelu_tanh(acc[4 * (jb + t) + 0]), gelu_tanh(acc[4 * (jb + t) + 1]));
          r[2 * t + 1] = pack_bf16(gelu_tanh(acc[4 * (jb + t) + 2]), gelu_tanh(acc[4 * (jb + t) + 3]));
        }
        const int n = 8 * (jb + (mi >> 1)) + l8;
        const int row = n >> 1, chunk = 2 * w + (mi & 1);
        stsm_x4_trans(hp + (n & 1) * 4096 + row * 128 + ((chunk ^ (row & 7)) << 4), r[0], r[1], r[2], r[3]);
      }
      fence_async_smem();
      bar_consumers();
      if (warp == 0) {
        if (elect_one()) {
          const uint32_t src = sb + kSlotH * kSlot + cta * 16384;
          dsmem_copy(mapa(src, peer), src, 16384, mapa(bars + kBarHX * 8, peer));
        }
        __syncwarp();
      }
      if (w == 0) TS(wg, 3);
    }
    {
      float acc[16];
#pragma unroll
      for (int v = 0; v < 12; v++) {
        const int i = v / 3, tap = v % 3;
        if (v == 6) { mbar_wait_cluster(bars + kBarHX * 8); if (w == 0) TS(wg, 4); }
        mbar_wait(bars + (kBarW + 12 + v) * 8);
        wg_fence();
#pragma unroll
        for (int s = 0; s < 4; s++)
          wgmma_ss_n32(acc, desc_at(dA, unit_slot(12 + v) * kSlot + s * 2048),
                       desc_at(i < 2 ? dBo : dBp, kSlotH * kSlot + (i & 1) * 8192 + (tap == 1 ? 4096 : (tap == 2 ? 128 : 0)) + s * 32), (v | s) != 0);
        wg_commit();
        if (v > 0) {
          wg_wait<1>();
          if (lane == 0) mbar_arrive(bars + (kBarE + 12 + v - 1) * 8);
        }
      }
      wg_wait<0>();
      if (lane == 0) mbar_arrive(bars + (kBarE + 23) * 8);
      if (w == 0) TS(wg, 5);
      const uint32_t fp = sb + kSlotF * kSlot + panel * 4096;
      const int mi = lane >> 3, l8 = lane & 7;
#pragma unroll
      for (int jb = 0; jb < 4; jb += 2) {
        uint32_t r[4];
#pragma unroll
        for (int t = 0; t < 2; t++) {
          r[2 * t + 0] = pack_bf16(gelu_tanh(acc[4 * (jb + t) + 0]), gelu_tanh(acc[4 * (jb + t) + 1]));
          r[2 * t + 1] = pack_bf16(gelu_tanh(acc[4 * (jb + t) + 2]), gelu_tanh(acc[4 * (jb + t) + 3]));
        }
        const int n = 8 * (jb + (mi >> 1)) + l8;
        const int chunk = 2 * w + (mi & 1);
        stsm_x4_trans(fp + n * 128 + ((chunk ^ (n & 7)) << 4), r[0], r[1], r[2], r[3]);
      }
      fence_async_smem();
      bar_consumers();
      if (warp == 0) {
        if (elect_one()) {
          const uint32_t src = sb + kSlotF * kSlot + cta * 8192;
          dsmem_copy(mapa(src, peer), src, 8192, mapa(bars + kBarFX * 8, peer));
        }
        __syncwarp();
      }
      if (w == 0) TS(wg, 6);
    }
    {
      float acc[16];
#pragma unroll
      for (int i = 0; i < 4; i++) {
        if (i == 2) { mbar_wait_cluster(bars + kBarFX * 8); if (w == 0) TS(wg, 7); }
        mbar_wait(bars + (kBarW + 24 + i) * 8);
        wg_fence();
#pragma unroll
        for (int s = 0; s < 4; s++)
          wgmma_ss_n32(acc, desc_at(dA, unit_slot(24 + i) * kSlot + s * 2048),
                       desc_at(i < 2 ? dFo : dFp, kSlotF * kSlot + (i & 1) * 4096 + s * 32), (i | s) != 0);
        wg_commit();
        if (i > 0) {
          wg_wait<1>();
          if (lane == 0) mbar_arrive(bars + (kBarE + 24 + i - 1) * 8);
        }
      }
      wg_wait<0>();
      if (w == 0) TS(wg, 8);
      const uint32_t sw = ((ch >> 1) & 3) * 2;
      const uint32_t own = sb + kSlotFE * kSlot + ch * 64;
      const uint32_t stg = sb + kSlotH * kSlot + (ch - (int)cta * 128) * 64;
#pragma unroll
      for (int jb = 0; jb < 4; jb++) {
        const uint32_t base = ((uint32_t)(jb >> 1) == cta) ? own : stg;
        const uint32_t pr = (4 * (jb & 1) + q) ^ sw;
        sts64(base + pr * 8, acc[4 * jb + 0], acc[4 * jb + 1]);
        sts64(base + 512 + pr * 8, acc[4 * jb + 2], acc[4 * jb + 3]);
      }
      fence_async_smem();
      bar_wg(wg);
      if (w == 0) {
        if (elect_one())
          dsmem_copy(mapa(sb + kSlotFE * kSlot + panel * 4096, peer), sb + kSlotH * kSlot + wg * 4096, 4096, mapa(bars + kBarFE * 8, peer));
        __syncwarp();
      }
      if (lane == 0) mbar_arrive(bars + kBarFE * 8);
      if (w == 0) TS(wg, 9);
    }
    const int rl0 = cta * 16 + wg * 8;
    mbar_wait_cluster(bars + kBarFE * 8);
    asm volatile("barrier.cluster.arrive.relaxed.aligned;" ::: "memory");
    if (wg == 1) asm volatile("bar.sync 4, 256;" ::: "memory");
    if (rl0 < rvalid) {
      if (w == 0) TS(wg, 10);
      const uint32_t fe_t = sb + kSlotFE * kSlot + (2 * q) * 64 + (((4 * wg + w) ^ (2 * q)) << 3);
      const uint32_t ge_t = sb + kOffGE + gq * kGEPitch + (2 * q) * 4;
      const int mi = lane >> 3, l8 = lane & 7;
      const CUtensorMap* omap = (rl0 + 8 <= rvalid) ? &P.out64 : &P.out56;
      const int grow = (b * kT2 + r0 + rl0) * 8;
      const uint32_t st = sb + (wg ? 12 : 8) * kSlot + (16 * w + (mi & 1) * 8 + l8) * 128;
      uint32_t A[64];
      float acc[2][32];
#pragma unroll
      for (int kk = 0; kk < 16; kk++) {
        const float2 f0 = lds64(fe_t + kk * 1024), f1 = lds64(fe_t + kk * 1024 + 64);
        const float2 f2 = lds64(fe_t + kk * 1024 + 512), f3 = lds64(fe_t + kk * 1024 + 576);
        const float2 g0 = lds64(ge_t + kk * 64), g1 = lds64(ge_t + kk * 64 + 32);
        A[4 * kk + 0] = pack_bf16(tanh_fast(f0.x + g0.x), tanh_fast(f1.x + g0.y));
        A[4 * kk + 1] = pack_bf16(tanh_fast(f0.y + g0.x), tanh_fast(f1.y + g0.y));
        A[4 * kk + 2] = pack_bf16(tanh_fast(f2.x + g1.x), tanh_fast(f3.x + g1.y));
        A[4 * kk + 3] = pack_bf16(tanh_fast(f2.y + g1.x), tanh_fast(f3.y + g1.y));
      }
      if (wg == 0) asm volatile("bar.arrive 4, 256;" ::: "memory");
      if (w == 0) TS(wg, 15);
#pragma unroll
      for (int kk = 0; kk < 16; kk++) {
        if ((kk & 3) == 0) { mbar_wait(bars + (kBarW + 28 + (kk >> 2)) * 8); wg_fence(); }
        wgmma_rs_n64(acc[0], A[4 * kk], A[4 * kk + 1], A[4 * kk + 2], A[4 * kk + 3],
                     desc_at(dB, unit_slot(28 + (kk >> 2)) * kSlot + (kk & 3) * 2048), kk != 0);
      }
      wg_commit();
      if (w == 0) TS(wg, 11);
#pragma unroll
      for (int j = 0; j < 4; j++) {
        if (j < 3) {
          const int jn = j + 1;
          wg_fence();
#pragma unroll
          for (int kk = 0; kk < 16; kk++) {
            if (jn == 2 && (kk & 3) == 0) { mbar_wait(bars + (kBarW + 32 + (kk >> 2)) * 8); wg_fence(); }
            wgmma_rs_n64(acc[jn & 1], A[4 * kk], A[4 * kk + 1], A[4 * kk + 2], A[4 * kk + 3],
                         desc_at(dB, unit_slot(28 + (jn >> 1) * 4 + (kk >> 2)) * kSlot + (jn & 1) * 8192 + (kk & 3) * 2048), kk != 0);
            if (kk == 1) { wg_commit(); wg_wait<1>(); }
            if (kk == 1) {
              if (j >= 2) {
              }
            }
            if (kk == 1) {
              if (j >= 2) {
                if (w == 0) { if (elect_one()) asm volatile("cp.async.bulk.wait_group.read 1;" ::: "memory"); __syncwarp(); }
                bar_wg(wg);
              }
#pragma unroll
              for (int jb = 0; jb < 8; jb += 2) {
                const uint32_t r0_ = pack_bf16(acc[j & 1][4 * jb + 0], acc[j & 1][4 * jb + 1]), r1_ = pack_bf16(acc[j & 1][4 * jb + 2], acc[j & 1][4 * jb + 3]);
                const uint32_t r2_ = pack_bf16(acc[j & 1][4 * jb + 4], acc[j & 1][4 * jb + 5]), r3_ = pack_bf16(acc[j & 1][4 * jb + 6], acc[j & 1][4 * jb + 7]);
                stsm_x4(st + (j & 1) * 8192 + (((jb + (mi >> 1)) ^ l8) << 4), r0_, r1_, r2_, r3_);
              }
              fence_async_smem();
              bar_wg(wg);
              if (w == 0) {
                if (elect_one()) {
                  tma_store_3d(omap, sb + (wg ? 12 : 8) * kSlot + (j & 1) * 8192, 0, grow, j);
                  asm volatile("cp.async.bulk.commit_group;" ::: "memory");
                }
                __syncwarp();
              }
              if (j == 0 && w == 0) TS(wg, 12);
              wg_fence();
            }
          }
          wg_commit();
        } else {
          wg_wait<0>();
          if (w == 0) TS(wg, 13);
          if (w == 0) { if (elect_one()) asm volatile("cp.async.bulk.wait_group.read 1;" ::: "memory"); __syncwarp(); }
          bar_wg(wg);
#pragma unroll
          for (int jb = 0; jb < 8; jb += 2) {
            const uint32_t r0_ = pack_bf16(acc[1][4 * jb + 0], acc[1][4 * jb + 1]), r1_ = pack_bf16(acc[1][4 * jb + 2], acc[1][4 * jb + 3]);
            const uint32_t r2_ = pack_bf16(acc[1][4 * jb + 4], acc[1][4 * jb + 5]), r3_ = pack_bf16(acc[1][4 * jb + 6], acc[1][4 * jb + 7]);
            stsm_x4(st + 8192 + (((jb + (mi >> 1)) ^ l8) << 4), r0_, r1_, r2_, r3_);
          }
          fence_async_smem();
          bar_wg(wg);
          if (w == 0) {
            if (elect_one()) {
              tma_store_3d(omap, sb + (wg ? 12 : 8) * kSlot + 8192, 0, grow, 3);
              asm volatile("cp.async.bulk.commit_group;" ::: "memory");
              asm volatile("cp.async.bulk.wait_group.read 0;" ::: "memory");
            }
            __syncwarp();
          }
        }
      }
      if (w == 0) TS(wg, 14);
    } else if (wg == 0) {
      asm volatile("bar.arrive 4, 256;" ::: "memory");
    }
    asm volatile("barrier.cluster.wait.aligned;" ::: "memory");
  }
}

typedef CUresult (*EncodeFn)(CUtensorMap*, CUtensorMapDataType, cuuint32_t, void*, const cuuint64_t*, const cuuint64_t*,
                             const cuuint32_t*, const cuuint32_t*, CUtensorMapInterleave, CUtensorMapSwizzle,
                             CUtensorMapL2promotion, CUtensorMapFloatOOBfill);

void make_map3(EncodeFn enc, CUtensorMap* tm, const void* ptr, uint64_t rows, uint32_t box_rows, uint32_t box_panels) {
  cuuint64_t gd[3] = {64, rows, 4};
  cuuint64_t gs[2] = {512, 128};
  cuuint32_t bd[3] = {64, box_rows, box_panels};
  cuuint32_t es[3] = {1, 1, 1};
  enc(tm, CU_TENSOR_MAP_DATA_TYPE_BFLOAT16, 3, const_cast<void*>(ptr), gd, gs, bd, es, CU_TENSOR_MAP_INTERLEAVE_NONE,
      CU_TENSOR_MAP_SWIZZLE_128B, CU_TENSOR_MAP_L2_PROMOTION_L2_256B, CU_TENSOR_MAP_FLOAT_OOB_FILL_NONE);
}

}

extern "C" void kernel_launch(void* const* d_in, const int* in_sizes, int n_in, void* d_out, int out_size) {
  static EncodeFn enc = nullptr;
  if (!enc) {
    cudaDriverEntryPointQueryResult qr;
    cudaGetDriverEntryPoint("cuTensorMapEncodeTiled", (void**)&enc, cudaEnableDefault, &qr);
    cudaFuncSetAttribute(rnnt_joint_kernel, cudaFuncAttributeMaxDynamicSharedMemorySize, kSmemBytes);
  }
  Params P;
  {
    cuuint64_t gd[4] = {256, 2, 2000, 2};
    cuuint64_t gs[3] = {512, 1024, 4000ull * 512};
    cuuint32_t bd[4] = {64, 1, 64, 1};
    cuuint32_t es[4] = {1, 1, 1, 1};
    enc(&P.x, CU_TENSOR_MAP_DATA_TYPE_BFLOAT16, 4, d_in[0], gd, gs, bd, es, CU_TENSOR_MAP_INTERLEAVE_NONE,
        CU_TENSOR_MAP_SWIZZLE_128B, CU_TENSOR_MAP_L2_PROMOTION_L2_256B, CU_TENSOR_MAP_FLOAT_OOB_FILL_NONE);
  }
  make_map3(enc, &P.w1, d_in[1], 768, 64, 2);
  make_map3(enc, &P.w2, d_in[2], 768, 64, 2);
  make_map3(enc, &P.g, d_in[3], 16, 8, 4);
  make_map3(enc, &P.wf, d_in[4], 256, 64, 2);
  make_map3(enc, &P.wg, d_in[5], 256, 64, 2);
  make_map3(enc, &P.wo, d_in[6], 256, 64, 2);
  make_map3(enc, &P.out64, d_out, 16000, 64, 1);
  make_map3(enc, &P.out56, d_out, 16000, 56, 1);
  rnnt_joint_kernel<<<kNumCtas, kThreads, kSmemBytes>>>(P);
}
```

```cpp
#include <cuda_runtime.h>
#include <cuda_bf16.h>
#include <cuda.h>
#include <stdint.h>

#define XPREF 1
#define XFIRST 2
#define XSTEP 2
#define XPROMO CU_TENSOR_MAP_L2_PROMOTION_L2_256B
namespace {

constexpr int kT2 = 1000;
constexpr int kR = 31;
constexpr int kNumCtas = 132;
constexpr int kThreads = 384;
constexpr int kSlot = 16384;

constexpr int kSlotFE = 9, kSlotF = 10, kSlotH = 11;
constexpr int kOffG = 13 * kSlot;
constexpr int kOffGE = kOffG + 4096;
constexpr int kGEPitch = 1056;
constexpr int kGEBytes = 8 * kGEPitch;
constexpr int kOffBar = kOffGE + kGEBytes;
constexpr int kBarX = 0;
constexpr int kBarW = 4;
constexpr int kBarE = 40;
constexpr int kBarHX = 67, kBarFX = 68, kBarFE = 69, kBarG = 70, kBarP0 = 71;
constexpr int kNumBars = 72;
constexpr int kSmemBytes = kOffBar + kNumBars * 8 + 1024;

__device__ float g_ge[2 * kGEBytes / 4];
__device__ unsigned int g_ge_flag[2];
__device__ unsigned int g_cta_count;

#define TS(slot_, idx_) do {} while (0)

__device__ __forceinline__ uint32_t smem_u32(const void* p) { return (uint32_t)__cvta_generic_to_shared(p); }
__device__ __forceinline__ void mbar_init(uint32_t a, uint32_t c) { asm volatile("mbarrier.init.shared.b64 [%0], %1;" ::"r"(a), "r"(c) : "memory"); }
__device__ __forceinline__ void mbar_expect(uint32_t a, uint32_t b) { asm volatile("mbarrier.arrive.expect_tx.shared.b64 _, [%0], %1;" ::"r"(a), "r"(b) : "memory"); }
__device__ __forceinline__ void mbar_arrive(uint32_t a) { asm volatile("mbarrier.arrive.shared.b64 _, [%0];" ::"r"(a) : "memory"); }
__device__ __forceinline__ bool mbar_try(uint32_t a) {
  uint32_t ok;
  asm volatile("{\n.reg .pred p;\nmbarrier.try_wait.parity.shared.b64 p, [%1], 0;\nselp.u32 %0, 1, 0, p;\n}\n" : "=r"(ok) : "r"(a) : "memory");
  return ok != 0;
}
__device__ __forceinline__ bool mbar_try_cluster(uint32_t a) {
  uint32_t ok;
  asm volatile("{\n.reg .pred p;\nmbarrier.try_wait.parity.acquire.cluster.shared.b64 p, [%1], 0;\nselp.u32 %0, 1, 0, p;\n}\n" : "=r"(ok) : "r"(a) : "memory");
  return ok != 0;
}
__device__ __forceinline__ void mbar_wait_slow(uint32_t a) {
  const long long t0 = clock64();
  while (!mbar_try(a)) { if (clock64() - t0 > 4000000ll) break; }
}
__device__ __forceinline__ void mbar_wait_cluster_slow(uint32_t a) {
  const long long t0 = clock64();
  while (!mbar_try_cluster(a)) { if (clock64() - t0 > 4000000ll) break; }
}
__device__ __forceinline__ void mbar_wait(uint32_t a) { if (!mbar_try(a)) mbar_wait_slow(a); }
__device__ __forceinline__ void mbar_wait_cluster(uint32_t a) { if (!mbar_try_cluster(a)) mbar_wait_cluster_slow(a); }
__device__ __forceinline__ uint32_t mapa(uint32_t a, uint32_t r) { uint32_t d; asm volatile("mapa.shared::cluster.u32 %0, %1, %2;" : "=r"(d) : "r"(a), "r"(r)); return d; }
__device__ __forceinline__ bool elect_one() { uint32_t p; asm volatile("{\n.reg .pred P;\nelect.sync _|P, 0xffffffff;\nselp.u32 %0, 1, 0, P;\n}\n" : "=r"(p)); return p != 0; }
__device__ __forceinline__ void fence_async_smem() { asm volatile("fence.proxy.async.shared::cta;" ::: "memory"); }
__device__ __forceinline__ void bar_consumers() { asm volatile("bar.sync 1, 256;" ::: "memory"); }
__device__ __forceinline__ void bar_wg(int wg) { asm volatile("bar.sync %0, 128;" ::"r"(2 + wg) : "memory"); }
__device__ __forceinline__ void cluster_sync_relaxed() { asm volatile("barrier.cluster.arrive.relaxed.aligned;\nbarrier.cluster.wait.aligned;" ::: "memory"); }
__device__ __forceinline__ void wg_fence() { asm volatile("wgmma.fence.sync.aligned;" ::: "memory"); }
__device__ __forceinline__ void wg_commit() { asm volatile("wgmma.commit_group.sync.aligned;" ::: "memory"); }
template <int N> __device__ __forceinline__ void wg_wait() { asm volatile("wgmma.wait_group.sync.aligned %0;" ::"n"(N) : "memory"); }

__device__ __forceinline__ void tma_load_3d(uint32_t dst, const CUtensorMap* tm, uint32_t bar, int c0, int c1, int c2) {
  asm volatile("cp.async.bulk.tensor.3d.shared::cluster.global.mbarrier::complete_tx::bytes [%0], [%1, {%3, %4, %5}], [%2];"
               ::"r"(dst), "l"(tm), "r"(bar), "r"(c0), "r"(c1), "r"(c2) : "memory");
}
__device__ __forceinline__ void tma_load_4d_mc(uint32_t dst, const CUtensorMap* tm, uint32_t bar, int c0, int c1, int c2, int c3, uint16_t mask) {
  asm volatile("cp.async.bulk.tensor.4d.shared::cluster.global.mbarrier::complete_tx::bytes.multicast::cluster [%0], [%1, {%3, %4, %5, %6}], [%2], %7;"
               ::"r"(dst), "l"(tm), "r"(bar), "r"(c0), "r"(c1), "r"(c2), "r"(c3), "h"(mask) : "memory");
}
__device__ __forceinline__ void tma_store_3d(const CUtensorMap* tm, uint32_t src, int c0, int c1, int c2) {
  asm volatile("cp.async.bulk.tensor.3d.global.shared::cta.bulk_group [%0, {%2, %3, %4}], [%1];"
               ::"l"(tm), "r"(src), "r"(c0), "r"(c1), "r"(c2) : "memory");
}
__device__ __forceinline__ void bulk_load(uint32_t dst, const void* src, uint32_t bytes, uint32_t bar) {
  asm volatile("cp.async.bulk.shared::cluster.global.mbarrier::complete_tx::bytes [%0], [%1], %2, [%3];"
               ::"r"(dst), "l"(src), "r"(bytes), "r"(bar) : "memory");
}
__device__ __forceinline__ void dsmem_copy(uint32_t dst_remote, uint32_t src, uint32_t bytes, uint32_t bar_remote) {
  asm volatile("cp.async.bulk.shared::cluster.shared::cta.mbarrier::complete_tx::bytes [%0], [%1], %2, [%3];"
               ::"r"(dst_remote), "r"(src), "r"(bytes), "r"(bar_remote) : "memory");
}
__device__ __forceinline__ void stsm_x4_trans(uint32_t addr, uint32_t r0, uint32_t r1, uint32_t r2, uint32_t r3) {
  asm volatile("stmatrix.sync.aligned.m8n8.x4.trans.shared.b16 [%0], {%1, %2, %3, %4};" ::"r"(addr), "r"(r0), "r"(r1), "r"(r2), "r"(r3) : "memory");
}
__device__ __forceinline__ void stsm_x4(uint32_t addr, uint32_t r0, uint32_t r1, uint32_t r2, uint32_t r3) {
  asm volatile("stmatrix.sync.aligned.m8n8.x4.shared.b16 [%0], {%1, %2, %3, %4};" ::"r"(addr), "r"(r0), "r"(r1), "r"(r2), "r"(r3) : "memory");
}
__device__ __forceinline__ float2 lds64(uint32_t a) { float2 v; asm volatile("ld.shared.v2.f32 {%0, %1}, [%2];" : "=f"(v.x), "=f"(v.y) : "r"(a) : "memory"); return v; }
__device__ __forceinline__ void sts64(uint32_t a, float x, float y) { asm volatile("st.shared.v2.f32 [%0], {%1, %2};" ::"r"(a), "f"(x), "f"(y) : "memory"); }
__device__ __forceinline__ float tanh_fast(float x) { float y; asm("tanh.approx.f32 %0, %1;" : "=f"(y) : "f"(x)); return y; }
__device__ __forceinline__ uint32_t pack_bf16(float lo, float hi) { uint32_t r; asm("cvt.rn.bf16x2.f32 %0, %1, %2;" : "=r"(r) : "f"(hi), "f"(lo)); return r; }
__device__ __forceinline__ float gelu_tanh(float x) {
  const float k0 = 0.7978845608028654f, k1 = 0.7978845608028654f * 0.044715f;
  float u = x * fmaf(x * x, k1, k0);
  float hx = 0.5f * x;
  return fmaf(hx, tanh_fast(u), hx);
}
__device__ __forceinline__ uint64_t make_desc(uint32_t addr, uint32_t lbo, uint32_t sbo) {
  return (uint64_t)((addr & 0x3FFFF) >> 4) | ((uint64_t)(lbo >> 4) << 16) | ((uint64_t)(sbo >> 4) << 32) | ((uint64_t)1 << 62);
}

__device__ __forceinline__ uint32_t desc_lo(uint32_t addr, uint32_t lbo) { return ((addr & 0x3FFFF) >> 4) | ((lbo >> 4) << 16); }
__device__ __forceinline__ uint64_t desc_at(uint32_t lo, uint32_t off) { return ((uint64_t)0x40000040u << 32) | (uint64_t)(lo + (off >> 4)); }

__device__ __forceinline__ void wgmma_ss_n64(float (&d)[32], uint64_t da, uint64_t db, int scale_d) {
  asm volatile("{\n.reg .pred p;\nsetp.ne.b32 p, %34, 0;\n"
    "wgmma.mma_async.sync.aligned.m64n64k16.f32.bf16.bf16 {%0, %1, %2, %3, %4, %5, %6, %7, %8, %9, %10, %11, %12, %13, %14, %15, %16, %17, %18, %19, %20, %21, %22, %23, %24, %25, %26, %27, %28, %29, %30, %31}, %32, %33, p, 1, 1, 1, 0;\n}\n"
    : "+f"(d[0]), "+f"(d[1]), "+f"(d[2]), "+f"(d[3]), "+f"(d[4]), "+f"(d[5]), "+f"(d[6]), "+f"(d[7]), "+f"(d[8]), "+f"(d[9]), "+f"(d[10]), "+f"(d[11]), "+f"(d[12]), "+f"(d[13]), "+f"(d[14]), "+f"(d[15]), "+f"(d[16]), "+f"(d[17]), "+f"(d[18]), "+f"(d[19]), "+f"(d[20]), "+f"(d[21]), "+f"(d[22]), "+f"(d[23]), "+f"(d[24]), "+f"(d[25]), "+f"(d[26]), "+f"(d[27]), "+f"(d[28]), "+f"(d[29]), "+f"(d[30]), "+f"(d[31])
    : "l"(da), "l"(db), "r"(scale_d));
}

__device__ __forceinline__ void wgmma_ss_n32(float (&d)[16], uint64_t da, uint64_t db, int scale_d) {
  asm volatile("{\n.reg .pred p;\nsetp.ne.b32 p, %18, 0;\n"
    "wgmma.mma_async.sync.aligned.m64n32k16.f32.bf16.bf16 {%0, %1, %2, %3, %4, %5, %6, %7, %8, %9, %10, %11, %12, %13, %14, %15}, %16, %17, p, 1, 1, 1, 0;\n}\n"
    : "+f"(d[0]), "+f"(d[1]), "+f"(d[2]), "+f"(d[3]), "+f"(d[4]), "+f"(d[5]), "+f"(d[6]), "+f"(d[7]), "+f"(d[8]), "+f"(d[9]), "+f"(d[10]), "+f"(d[11]), "+f"(d[12]), "+f"(d[13]), "+f"(d[14]), "+f"(d[15])
    : "l"(da), "l"(db), "r"(scale_d));
}

__device__ __forceinline__ void wgmma_ss_n8(float (&d)[4], uint64_t da, uint64_t db, int scale_d) {
  asm volatile("{\n.reg .pred p;\nsetp.ne.b32 p, %6, 0;\n"
    "wgmma.mma_async.sync.aligned.m64n8k16.f32.bf16.bf16 {%0, %1, %2, %3}, %4, %5, p, 1, 1, 1, 0;\n}\n"
    : "+f"(d[0]), "+f"(d[1]), "+f"(d[2]), "+f"(d[3])
    : "l"(da), "l"(db), "r"(scale_d));
}

__device__ __forceinline__ void wgmma_rs_n64(float (&d)[32], uint32_t a0, uint32_t a1, uint32_t a2, uint32_t a3, uint64_t db, int scale_d) {
  asm volatile("{\n.reg .pred p;\nsetp.ne.b32 p, %37, 0;\n"
    "wgmma.mma_async.sync.aligned.m64n64k16.f32.bf16.bf16 {%0, %1, %2, %3, %4, %5, %6, %7, %8, %9, %10, %11, %12, %13, %14, %15, %16, %17, %18, %19, %20, %21, %22, %23, %24, %25, %26, %27, %28, %29, %30, %31}, {%32, %33, %34, %35}, %36, p, 1, 1, 1;\n}\n"
    : "+f"(d[0]), "+f"(d[1]), "+f"(d[2]), "+f"(d[3]), "+f"(d[4]), "+f"(d[5]), "+f"(d[6]), "+f"(d[7]), "+f"(d[8]), "+f"(d[9]), "+f"(d[10]), "+f"(d[11]), "+f"(d[12]), "+f"(d[13]), "+f"(d[14]), "+f"(d[15]), "+f"(d[16]), "+f"(d[17]), "+f"(d[18]), "+f"(d[19]), "+f"(d[20]), "+f"(d[21]), "+f"(d[22]), "+f"(d[23]), "+f"(d[24]), "+f"(d[25]), "+f"(d[26]), "+f"(d[27]), "+f"(d[28]), "+f"(d[29]), "+f"(d[30]), "+f"(d[31])
    : "r"(a0), "r"(a1), "r"(a2), "r"(a3), "l"(db), "r"(scale_d));
}

__host__ __device__ constexpr int unit_slot(int u) {
  constexpr int t[36] = {4, 5, 6, 7, 8, 4, 5, 6, 0, 7, 8, 4,  1, 5, 6, 0, 2, 7, 8, 4, 3, 1, 5, 6,
                         0, 2, 7, 8,  4, 3, 1, 5, 6, 0, 2, 7};
  return t[u];
}
__host__ __device__ constexpr int unit_wait(int u) {
  constexpr int t[36] = {-1, -1, -1, -1, -1, 0, 1, 2, 2, 3, 4, 5,  5, 6, 7, 8, 8, 9, 10, 11, 11, 12, 13, 14,
                         15, 16, 17, 18,  19, 20, 21, 22, 23, 24, 25, 26};
  return t[u];
}

struct Params {
  CUtensorMap x, w1, w2, wf, wg, wo, g, out64, out56;
};

__device__ __forceinline__ void init_bar(uint32_t bars, int i) {
  const uint32_t a = bars + i * 8;
  const bool is_e = (i >= kBarE && i < kBarE + 27);
  mbar_init(a, is_e ? 8 : (i == kBarFE ? 9 : 1));
  if (!is_e) {
    uint32_t bytes = 16384;
    if (i == kBarFX) bytes = 8192;
    if (i == kBarFE) bytes = 8192 + kGEBytes;
    mbar_expect(a, bytes);
  }
}

__global__ void __cluster_dims__(2, 1, 1) __launch_bounds__(kThreads, 1)
rnnt_joint_kernel(const __grid_constant__ Params P) {
  extern __shared__ uint8_t smem_raw[];
  const uint32_t sb = (smem_u32(smem_raw) + 1023u) & ~1023u;
  const uint32_t bars = sb + kOffBar;
  const int warp = threadIdx.x >> 5, lane = threadIdx.x & 31;
  uint32_t cta;
  asm volatile("mov.u32 %0, %%cluster_ctarank;" : "=r"(cta));
  const uint32_t peer = cta ^ 1u;
  const int cl = blockIdx.x >> 1;
  const bool ge_cta = cl < 2;
  const int b = ge_cta ? cl : ((cl - 2) >> 5);
  const int r0 = ge_cta ? 32 * kR : ((cl - 2) & 31) * kR;
  const int rvalid = ge_cta ? kT2 - 32 * kR : kR;

  if (warp >= 8) {
    asm volatile("setmaxnreg.dec.sync.aligned.u32 40;");
    if (warp > 8) {
      if (elect_one()) {
#pragma unroll
        for (int i = 0; i < 6; i++) if (9 + (warp - 1) * 6 + i < kBarG) init_bar(bars, 9 + (warp - 1) * 6 + i);
        asm volatile("fence.mbarrier_init.release.cluster;" ::: "memory");
      }
      __syncwarp();
      cluster_sync_relaxed();
      return;
    }
    TS(2, 0);
    unsigned int ticket = 0;
    const int par = cta == 0 ? 1 : 0;
    const int q0 = cta == 0 ? 2 * r0 - 2 : 2 * r0 - 1;
    if (elect_one()) {
      asm volatile("cp.async.bulk.prefetch.tensor.4d.L2.global.tile [%0, {%1, %2, %3, %4}];" ::"l"(&P.x), "r"(0), "r"(par), "r"(q0), "r"(b) : "memory");
#pragma unroll
      for (int i = 0; i < 9; i++) { mbar_init(bars + i * 8, 1); mbar_expect(bars + i * 8, 16384); }
      if (ge_cta) { mbar_init(bars + kBarG * 8, 1); mbar_expect(bars + kBarG * 8, 4 * 16384 + 4096); mbar_init(bars + kBarP0 * 8, 8); }
      TS(2, 7);
      asm volatile("fence.mbarrier_init.release.cluster;" ::: "memory");
      fence_async_smem();
      TS(2, 8);
      if (ge_cta) {
        tma_load_3d(sb + kOffG, &P.g, bars + kBarG * 8, 0, b * 8, 0);
#pragma unroll
        for (int i = 0; i < 4; i++) tma_load_3d(sb + (9 + i) * kSlot, &P.wg, bars + kBarG * 8, 0, i * 64, 2 * cta);
      }
#pragma unroll
      for (int u = 0; u < 5; u++)
      {
        tma_load_3d(sb + unit_slot(u) * kSlot, &P.w1, bars + (kBarW + u) * 8, 0, (u % 3) * 256 + (u / 3) * 64, 2 * cta);
        if (u == 0) TS(2, 9);
      }
      TS(2, 10);
    }
    __syncwarp();
    TS(2, 6);
    cluster_sync_relaxed();
    TS(2, 1);
    if (elect_one()) {
#pragma unroll
      for (int p = 0; p < XFIRST; p++)
        tma_load_4d_mc(sb + p * kSlot + cta * 8192, &P.x, bars + (kBarX + p) * 8, p * 64, par, q0, b, (uint16_t)3);
    }
    __syncwarp();
    if (lane == 0) ticket = atomicAdd(&g_cta_count, 1u);
#pragma unroll
    for (int p = XFIRST; p < 4; p++) {
      if (XSTEP == 1 || ((p - XFIRST) & 1) == 0) mbar_wait(bars + (kBarX + p - XFIRST) * 8);
      if (ge_cta && p == 3) mbar_wait(bars + kBarP0 * 8);
      if (elect_one())
        tma_load_4d_mc(sb + p * kSlot + cta * 8192, &P.x, bars + (kBarX + p) * 8, p * 64, par, q0, b, (uint16_t)3);
      __syncwarp();
    }
#pragma unroll
    for (int u = 5; u < 36; u++) {
      if (unit_wait(u) != unit_wait(u - 1)) mbar_wait(bars + (kBarE + unit_wait(u)) * 8);
      if (u == 27) ticket = __shfl_sync(0xffffffffu, ticket, 0);
      if (elect_one()) {
        const uint32_t dst = sb + unit_slot(u) * kSlot, bar = bars + (kBarW + u) * 8;
        if (u < 12) tma_load_3d(dst, &P.w1, bar, 0, (u % 3) * 256 + (u / 3) * 64, 2 * cta);
        else if (u < 24) tma_load_3d(dst, &P.w2, bar, 0, ((u - 12) % 3) * 256 + ((2 * cta + (u - 12) / 3) & 3) * 64, 2 * cta);
        else if (u < 28) tma_load_3d(dst, &P.wf, bar, 0, ((2 * cta + (u - 24)) & 3) * 64, 2 * cta);
        else tma_load_3d(dst, &P.wo, bar, 0, ((u - 28) & 3) * 64, ((u - 28) >> 2) * 2);
        if (u == 27) {
          const unsigned int want = (ticket / kNumCtas + 1u) * 2u;
          const long long t0 = clock64();
          unsigned int v;
          do {
            asm volatile("ld.acquire.gpu.global.u32 %0, [%1];" : "=r"(v) : "l"(&g_ge_flag[b]) : "memory");
          } while ((int)(v - want) < 0 && clock64() - t0 < 4000000ll);
          asm volatile("fence.proxy.async;" ::: "memory");
          bulk_load(sb + kOffGE, reinterpret_cast<const char*>(g_ge) + b * kGEBytes, kGEBytes, bars + kBarFE * 8);
        }
      }
      __syncwarp();
      if (u == 11) TS(2, 2);
      if (u == 23) TS(2, 3);
      if (u == 27) TS(2, 4);
      if (u == 35) TS(2, 5);
    }
  } else {
    asm volatile("setmaxnreg.inc.sync.aligned.u32 232;");
    const int wg = warp >> 2, w = warp & 3;
    const int gq = lane >> 2, q = lane & 3;
    const uint32_t panel = 2 * cta + wg;
    const int ch = panel * 64 + w * 16 + gq;
    const uint32_t dA = desc_lo(sb + wg * 8192, 8192);
    const uint32_t dB = desc_lo(sb, 16);
    const uint32_t dBo = desc_lo(sb + cta * 2 * 8192, 16), dBp = desc_lo(sb + (cta ^ 1) * 2 * 8192, 16);
    const uint32_t dFo = desc_lo(sb + cta * 2 * 4096, 16), dFp = desc_lo(sb + (cta ^ 1) * 2 * 4096, 16);
    if (elect_one()) {
#pragma unroll
      for (int i = 0; i < 6; i++) init_bar(bars, 9 + warp * 6 + i);
      asm volatile("fence.mbarrier_init.release.cluster;" ::: "memory");
    }
    __syncwarp();
    cluster_sync_relaxed();
    if (w == 0) TS(wg, 0);

    if (ge_cta) {
      float ga[4];
      mbar_wait(bars + kBarG * 8);
      wg_fence();
#pragma unroll
      for (int i = 0; i < 4; i++) {
#pragma unroll
        for (int s = 0; s < 4; s++)
          wgmma_ss_n8(ga, desc_at(dA, (9 + i) * kSlot + s * 2048), desc_at(dB, kOffG + i * 1024 + s * 32), (i | s) != 0);
      }
      wg_commit();
      wg_wait<0>();
      if (lane == 0) mbar_arrive(bars + kBarP0 * 8);
      float* gp = g_ge + b * (kGEBytes / 4);
      gp[(2 * q) * (kGEPitch / 4) + ch] = ga[0];
      gp[(2 * q + 1) * (kGEPitch / 4) + ch] = ga[1];
      gp[(2 * q) * (kGEPitch / 4) + ch + 8] = ga[2];
      gp[(2 * q + 1) * (kGEPitch / 4) + ch + 8] = ga[3];
      __threadfence();
      bar_consumers();
      if (threadIdx.x == 0) asm volatile("red.release.gpu.global.add.u32 [%0], 1;" ::"l"(&g_ge_flag[b]) : "memory");
    }

    {
      float acc[32];
#pragma unroll
      for (int u = 0; u < 12; u++) {
        const int p = u / 3, tap = u % 3;
        if (tap == 0) mbar_wait(bars + (kBarX + p) * 8);
        mbar_wait(bars + (kBarW + u) * 8);
        if (u == 0 && w == 0) TS(wg, 1);
        wg_fence();
#pragma unroll
        for (int s = 0; s < 4; s++)
          wgmma_ss_n64(acc, desc_at(dA, unit_slot(u) * kSlot + s * 2048),
                       desc_at(dB, p * kSlot + (tap == 1 ? 8192 : (tap == 2 ? 128 : 0)) + s * 32), (u | s) != 0);
        wg_commit();
        if (u > 0) {
          wg_wait<1>();
          if (lane == 0) mbar_arrive(bars + (kBarE + u - 1) * 8);
        }
      }
      wg_wait<0>();
      if (lane == 0) mbar_arrive(bars + (kBarE + 11) * 8);
      if (w == 0) TS(wg, 2);
      const uint32_t hp = sb + kSlotH * kSlot + panel * 8192;
      const int mi = lane >> 3, l8 = lane & 7;
#pragma unroll
      for (int jb = 0; jb < 8; jb += 2) {
        uint32_t r[4];
#pragma unroll
        for (int t = 0; t < 2; t++) {
          r[2 * t + 0] = pack_bf16(gelu_tanh(acc[4 * (jb + t) + 0]), gelu_tanh(acc[4 * (jb + t) + 1]));
          r[2 * t + 1] = pack_bf16(gelu_tanh(acc[4 * (jb + t) + 2]), gelu_tanh(acc[4 * (jb + t) + 3]));
        }
        const int n = 8 * (jb + (mi >> 1)) + l8;
        const int row = n >> 1, chunk = 2 * w + (mi & 1);
        stsm_x4_trans(hp + (n & 1) * 4096 + row * 128 + ((chunk ^ (row & 7)) << 4), r[0], r[1], r[2], r[3]);
      }
      fence_async_smem();
      bar_consumers();
      if (warp == 0) {
        if (elect_one()) {
          const uint32_t src = sb + kSlotH * kSlot + cta * 16384;
          dsmem_copy(mapa(src, peer), src, 16384, mapa(bars + kBarHX * 8, peer));
        }
        __syncwarp();
      }
      if (w == 0) TS(wg, 3);
    }
    {
      float acc[16];
#pragma unroll
      for (int v = 0; v < 12; v++) {
        const int i = v / 3, tap = v % 3;
        if (v == 6) { mbar_wait_cluster(bars + kBarHX * 8); if (w == 0) TS(wg, 4); }
        mbar_wait(bars + (kBarW + 12 + v) * 8);
        wg_fence();
#pragma unroll
        for (int s = 0; s < 4; s++)
          wgmma_ss_n32(acc, desc_at(dA, unit_slot(12 + v) * kSlot + s * 2048),
                       desc_at(i < 2 ? dBo : dBp, kSlotH * kSlot + (i & 1) * 8192 + (tap == 1 ? 4096 : (tap == 2 ? 128 : 0)) + s * 32), (v | s) != 0);
        wg_commit();
        if (v > 0) {
          wg_wait<1>();
          if (lane == 0) mbar_arrive(bars + (kBarE + 12 + v - 1) * 8);
        }
      }
      wg_wait<0>();
      if (lane == 0) mbar_arrive(bars + (kBarE + 23) * 8);
      if (w == 0) TS(wg, 5);
      const uint32_t fp = sb + kSlotF * kSlot + panel * 4096;
      const int mi = lane >> 3, l8 = lane & 7;
#pragma unroll
      for (int jb = 0; jb < 4; jb += 2) {
        uint32_t r[4];
#pragma unroll
        for (int t = 0; t < 2; t++) {
          r[2 * t + 0] = pack_bf16(gelu_tanh(acc[4 * (jb + t) + 0]), gelu_tanh(acc[4 * (jb + t) + 1]));
          r[2 * t + 1] = pack_bf16(gelu_tanh(acc[4 * (jb + t) + 2]), gelu_tanh(acc[4 * (jb + t) + 3]));
        }
        const int n = 8 * (jb + (mi >> 1)) + l8;
        const int chunk = 2 * w + (mi & 1);
        stsm_x4_trans(fp + n * 128 + ((chunk ^ (n & 7)) << 4), r[0], r[1], r[2], r[3]);
      }
      fence_async_smem();
      bar_consumers();
      if (warp == 0) {
        if (elect_one()) {
          const uint32_t src = sb + kSlotF * kSlot + cta * 8192;
          dsmem_copy(mapa(src, peer), src, 8192, mapa(bars + kBarFX * 8, peer));
        }
        __syncwarp();
      }
      if (w == 0) TS(wg, 6);
    }
    {
      float acc[16];
#pragma unroll
      for (int i = 0; i < 4; i++) {
        if (i == 2) { mbar_wait_cluster(bars + kBarFX * 8); if (w == 0) TS(wg, 7); }
        mbar_wait(bars + (kBarW + 24 + i) * 8);
        wg_fence();
#pragma unroll
        for (int s = 0; s < 4; s++)
          wgmma_ss_n32(acc, desc_at(dA, unit_slot(24 + i) * kSlot + s * 2048),
                       desc_at(i < 2 ? dFo : dFp, kSlotF * kSlot + (i & 1) * 4096 + s * 32), (i | s) != 0);
        wg_commit();
        if (i > 0) {
          wg_wait<1>();
          if (lane == 0) mbar_arrive(bars + (kBarE + 24 + i - 1) * 8);
        }
      }
      wg_wait<0>();
      if (w == 0) TS(wg, 8);
      const uint32_t sw = ((ch >> 1) & 3) * 2;
      const uint32_t own = sb + kSlotFE * kSlot + ch * 64;
      const uint32_t stg = sb + kSlotH * kSlot + (ch - (int)cta * 128) * 64;
#pragma unroll
      for (int jb = 0; jb < 4; jb++) {
        const uint32_t base = ((uint32_t)(jb >> 1) == cta) ? own : stg;
        const uint32_t pr = (4 * (jb & 1) + q) ^ sw;
        sts64(base + pr * 8, acc[4 * jb + 0], acc[4 * jb + 1]);
        sts64(base + 512 + pr * 8, acc[4 * jb + 2], acc[4 * jb + 3]);
      }
      fence_async_smem();
      bar_wg(wg);
      if (w == 0) {
        if (elect_one())
          dsmem_copy(mapa(sb + kSlotFE * kSlot + panel * 4096, peer), sb + kSlotH * kSlot + wg * 4096, 4096, mapa(bars + kBarFE * 8, peer));
        __syncwarp();
      }
      if (lane == 0) mbar_arrive(bars + kBarFE * 8);
      if (w == 0) TS(wg, 9);
    }
    const int rl0 = cta * 16 + wg * 8;
    mbar_wait_cluster(bars + kBarFE * 8);
    asm volatile("barrier.cluster.arrive.relaxed.aligned;" ::: "memory");
    if (wg == 1) asm volatile("bar.sync 4, 256;" ::: "memory");
    if (rl0 < rvalid) {
      if (w == 0) TS(wg, 10);
      const uint32_t fe_t = sb + kSlotFE * kSlot + (2 * q) * 64 + (((4 * wg + w) ^ (2 * q)) << 3);
      const uint32_t ge_t = sb + kOffGE + gq * kGEPitch + (2 * q) * 4;
      const int mi = lane >> 3, l8 = lane & 7;
      const CUtensorMap* omap = (rl0 + 8 <= rvalid) ? &P.out64 : &P.out56;
      const int grow = (b * kT2 + r0 + rl0) * 8;
      const uint32_t st = sb + (wg ? 12 : 8) * kSlot + (16 * w + (mi & 1) * 8 + l8) * 128;
      uint32_t A[64];
      float acc[2][32];
#pragma unroll
      for (int kk = 0; kk < 16; kk++) {
        const float2 f0 = lds64(fe_t + kk * 1024), f1 = lds64(fe_t + kk * 1024 + 64);
        const float2 f2 = lds64(fe_t + kk * 1024 + 512), f3 = lds64(fe_t + kk * 1024 + 576);
        const float2 g0 = lds64(ge_t + kk * 64), g1 = lds64(ge_t + kk * 64 + 32);
        A[4 * kk + 0] = pack_bf16(tanh_fast(f0.x + g0.x), tanh_fast(f1.x + g0.y));
        A[4 * kk + 1] = pack_bf16(tanh_fast(f0.y + g0.x), tanh_fast(f1.y + g0.y));
        A[4 * kk + 2] = pack_bf16(tanh_fast(f2.x + g1.x), tanh_fast(f3.x + g1.y));
        A[4 * kk + 3] = pack_bf16(tanh_fast(f2.y + g1.x), tanh_fast(f3.y + g1.y));
      }
      if (wg == 0) asm volatile("bar.arrive 4, 256;" ::: "memory");
      if (w == 0) TS(wg, 15);
#pragma unroll
      for (int kk = 0; kk < 16; kk++) {
        if ((kk & 3) == 0) { mbar_wait(bars + (kBarW + 28 + (kk >> 2)) * 8); wg_fence(); }
        wgmma_rs_n64(acc[0], A[4 * kk], A[4 * kk + 1], A[4 * kk + 2], A[4 * kk + 3],
                     desc_at(dB, unit_slot(28 + (kk >> 2)) * kSlot + (kk & 3) * 2048), kk != 0);
      }
      wg_commit();
      if (w == 0) TS(wg, 11);
#pragma unroll
      for (int j = 0; j < 4; j++) {
        const int jn = j + 1;
        if (jn == 2) {
#pragma unroll
          for (int i = 0; i < 4; i++) mbar_wait(bars + (kBarW + 32 + i) * 8);
        }
        if (j < 3) wg_fence();
#pragma unroll
        for (int kk = 0; kk < 16; kk++) {
          if (j < 3) {
            wgmma_rs_n64(acc[jn & 1], A[4 * kk], A[4 * kk + 1], A[4 * kk + 2], A[4 * kk + 3],
                         desc_at(dB, unit_slot(28 + (jn >> 1) * 4 + (kk >> 2)) * kSlot + (jn & 1) * 8192 + (kk & 3) * 2048), kk != 0);
          }
          if (kk == 1) {
            if (j < 3) { wg_commit(); wg_wait<1>(); } else { wg_wait<0>(); if (w == 0) TS(wg, 13); }
            if (j >= 2) {
              if (w == 0) { if (elect_one()) asm volatile("cp.async.bulk.wait_group.read 1;" ::: "memory"); __syncwarp(); }
              bar_wg(wg);
            }
          }
          if (kk >= 2 && kk < 10 && (kk & 1) == 0) {
            const int jb = kk - 2;
            const uint32_t r0_ = pack_bf16(acc[j & 1][4 * jb + 0], acc[j & 1][4 * jb + 1]), r1_ = pack_bf16(acc[j & 1][4 * jb + 2], acc[j & 1][4 * jb + 3]);
            const uint32_t r2_ = pack_bf16(acc[j & 1][4 * jb + 4], acc[j & 1][4 * jb + 5]), r3_ = pack_bf16(acc[j & 1][4 * jb + 6], acc[j & 1][4 * jb + 7]);
            stsm_x4(st + (j & 1) * 8192 + (((jb + (mi >> 1)) ^ l8) << 4), r0_, r1_, r2_, r3_);
          }
          if (kk == 9) {
            fence_async_smem();
            bar_wg(wg);
            if (w == 0) {
              if (elect_one()) {
                tma_store_3d(omap, sb + (wg ? 12 : 8) * kSlot + (j & 1) * 8192, 0, grow, j);
                asm volatile("cp.async.bulk.commit_group;" ::: "memory");
                if (j == 3) asm volatile("cp.async.bulk.wait_group.read 0;" ::: "memory");
              }
              __syncwarp();
            }
            if (j == 0 && w == 0) TS(wg, 12);
          }
        }
        if (j < 3) wg_commit();
      }
      if (w == 0) TS(wg, 14);
    } else if (wg == 0) {
      asm volatile("bar.arrive 4, 256;" ::: "memory");
    }
    asm volatile("barrier.cluster.wait.aligned;" ::: "memory");
  }
}

typedef CUresult (*EncodeFn)(CUtensorMap*, CUtensorMapDataType, cuuint32_t, void*, const cuuint64_t*, const cuuint64_t*,
                             const cuuint32_t*, const cuuint32_t*, CUtensorMapInterleave, CUtensorMapSwizzle,
                             CUtensorMapL2promotion, CUtensorMapFloatOOBfill);

void make_map3(EncodeFn enc, CUtensorMap* tm, const void* ptr, uint64_t rows, uint32_t box_rows, uint32_t box_panels) {
  cuuint64_t gd[3] = {64, rows, 4};
  cuuint64_t gs[2] = {512, 128};
  cuuint32_t bd[3] = {64, box_rows, box_panels};
  cuuint32_t es[3] = {1, 1, 1};
  enc(tm, CU_TENSOR_MAP_DATA_TYPE_BFLOAT16, 3, const_cast<void*>(ptr), gd, gs, bd, es, CU_TENSOR_MAP_INTERLEAVE_NONE,
      CU_TENSOR_MAP_SWIZZLE_128B, CU_TENSOR_MAP_L2_PROMOTION_L2_256B, CU_TENSOR_MAP_FLOAT_OOB_FILL_NONE);
}

}

extern "C" void kernel_launch(void* const* d_in, const int* in_sizes, int n_in, void* d_out, int out_size) {
  static EncodeFn enc = nullptr;
  if (!enc) {
    cudaDriverEntryPointQueryResult qr;
    cudaGetDriverEntryPoint("cuTensorMapEncodeTiled", (void**)&enc, cudaEnableDefault, &qr);
    cudaFuncSetAttribute(rnnt_joint_kernel, cudaFuncAttributeMaxDynamicSharedMemorySize, kSmemBytes);
  }
  Params P;
  {
    cuuint64_t gd[4] = {256, 2, 2000, 2};
    cuuint64_t gs[3] = {512, 1024, 4000ull * 512};
    cuuint32_t bd[4] = {64, 1, 64, 1};
    cuuint32_t es[4] = {1, 1, 1, 1};
    enc(&P.x, CU_TENSOR_MAP_DATA_TYPE_BFLOAT16, 4, d_in[0], gd, gs, bd, es, CU_TENSOR_MAP_INTERLEAVE_NONE,
        CU_TENSOR_MAP_SWIZZLE_128B, XPROMO, CU_TENSOR_MAP_FLOAT_OOB_FILL_NONE);
  }
  make_map3(enc, &P.w1, d_in[1], 768, 64, 2);
  make_map3(enc, &P.w2, d_in[2], 768, 64, 2);
  make_map3(enc, &P.g, d_in[3], 16, 8, 4);
  make_map3(enc, &P.wf, d_in[4], 256, 64, 2);
  make_map3(enc, &P.wg, d_in[5], 256, 64, 2);
  make_map3(enc, &P.wo, d_in[6], 256, 64, 2);
  make_map3(enc, &P.out64, d_out, 16000, 64, 1);
  make_map3(enc, &P.out56, d_out, 16000, 56, 1);
  rnnt_joint_kernel<<<kNumCtas, kThreads, kSmemBytes>>>(P);
}
```

```cpp
#include <cuda_runtime.h>
#include <cuda_bf16.h>
#include <cuda.h>
#include <stdint.h>

#define XPREF 1
#define XFIRST 2
#define XSTEP 2
#define XPROMO CU_TENSOR_MAP_L2_PROMOTION_L2_256B
namespace {

constexpr int kT2 = 1000;
constexpr int kR = 31;
constexpr int kNumCtas = 132;
constexpr int kThreads = 384;
constexpr int kSlot = 16384;

constexpr int kSlotFE = 9, kSlotF = 10, kSlotH = 11;
constexpr int kOffG = 13 * kSlot;
constexpr int kOffGE = kOffG + 4096;
constexpr int kGEPitch = 1056;
constexpr int kGEBytes = 8 * kGEPitch;
constexpr int kOffBar = kOffGE + kGEBytes;
constexpr int kBarX = 0;
constexpr int kBarW = 4;
constexpr int kBarE = 40;
constexpr int kBarHX = 67, kBarFX = 68, kBarFE = 69, kBarG = 70, kBarP0 = 71;
constexpr int kBarRH = 72, kBarRF = 74, kBarRE = 76;
constexpr int kBarPR = 78;
constexpr int kNumBars = 86;
constexpr int kSmemBytes = kOffBar + kNumBars * 8 + 1024;

__device__ float g_ge[2 * kGEBytes / 4];
__device__ unsigned int g_ge_flag[2];
__device__ unsigned int g_cta_count;

#define TS(slot_, idx_) do {} while (0)

__device__ __forceinline__ uint32_t smem_u32(const void* p) { return (uint32_t)__cvta_generic_to_shared(p); }
__device__ __forceinline__ void mbar_init(uint32_t a, uint32_t c) { asm volatile("mbarrier.init.shared.b64 [%0], %1;" ::"r"(a), "r"(c) : "memory"); }
__device__ __forceinline__ void mbar_expect(uint32_t a, uint32_t b) { asm volatile("mbarrier.arrive.expect_tx.shared.b64 _, [%0], %1;" ::"r"(a), "r"(b) : "memory"); }
__device__ __forceinline__ void mbar_arrive(uint32_t a) { asm volatile("mbarrier.arrive.shared.b64 _, [%0];" ::"r"(a) : "memory"); }
__device__ __forceinline__ void mbar_arrive_pred(uint32_t a, bool p) {
  asm volatile("{\n.reg .pred q;\nsetp.ne.u32 q, %1, 0;\n@q mbarrier.arrive.shared.b64 _, [%0];\n}\n" ::"r"(a), "r"((uint32_t)p) : "memory");
}
__device__ __forceinline__ bool mbar_try(uint32_t a) {
  uint32_t ok;
  asm volatile("{\n.reg .pred p;\nmbarrier.try_wait.parity.shared.b64 p, [%1], 0;\nselp.u32 %0, 1, 0, p;\n}\n" : "=r"(ok) : "r"(a) : "memory");
  return ok != 0;
}
__device__ __forceinline__ bool mbar_test(uint32_t a) {
  uint32_t ok;
  asm volatile("{\n.reg .pred p;\nmbarrier.test_wait.parity.shared.b64 p, [%1], 0;\nselp.u32 %0, 1, 0, p;\n}\n" : "=r"(ok) : "r"(a) : "memory");
  return ok != 0;
}
__device__ __forceinline__ bool mbar_try_cluster(uint32_t a) {
  uint32_t ok;
  asm volatile("{\n.reg .pred p;\nmbarrier.try_wait.parity.acquire.cluster.shared.b64 p, [%1], 0;\nselp.u32 %0, 1, 0, p;\n}\n" : "=r"(ok) : "r"(a) : "memory");
  return ok != 0;
}
__device__ __forceinline__ void mbar_wait_slow(uint32_t a) {
  const long long t0 = clock64();
  while (!mbar_try(a)) { if (clock64() - t0 > 4000000ll) break; }
}
__device__ __forceinline__ void mbar_wait_cluster_slow(uint32_t a) {
  const long long t0 = clock64();
  while (!mbar_try_cluster(a)) { if (clock64() - t0 > 4000000ll) break; }
}
__device__ __forceinline__ void mbar_wait(uint32_t a) { if (!mbar_try(a)) mbar_wait_slow(a); }
__device__ __forceinline__ void mbar_wait_cluster(uint32_t a) { if (!mbar_try_cluster(a)) mbar_wait_cluster_slow(a); }
__device__ __forceinline__ uint32_t mapa(uint32_t a, uint32_t r) { uint32_t d; asm volatile("mapa.shared::cluster.u32 %0, %1, %2;" : "=r"(d) : "r"(a), "r"(r)); return d; }
__device__ __forceinline__ bool elect_one() { uint32_t p; asm volatile("{\n.reg .pred P;\nelect.sync _|P, 0xffffffff;\nselp.u32 %0, 1, 0, P;\n}\n" : "=r"(p)); return p != 0; }
__device__ __forceinline__ void fence_async_smem() { asm volatile("fence.proxy.async.shared::cta;" ::: "memory"); }
__device__ __forceinline__ void bar_consumers() { asm volatile("bar.sync 1, 256;" ::: "memory"); }
__device__ __forceinline__ void bar_wg(int wg) { asm volatile("bar.sync %0, 128;" ::"r"(2 + wg) : "memory"); }
__device__ __forceinline__ void cluster_sync_relaxed() { asm volatile("barrier.cluster.arrive.relaxed.aligned;\nbarrier.cluster.wait.aligned;" ::: "memory"); }
__device__ __forceinline__ void wg_fence() { asm volatile("wgmma.fence.sync.aligned;" ::: "memory"); }
__device__ __forceinline__ void wg_commit() { asm volatile("wgmma.commit_group.sync.aligned;" ::: "memory"); }
template <int N> __device__ __forceinline__ void wg_wait() { asm volatile("wgmma.wait_group.sync.aligned %0;" ::"n"(N) : "memory"); }

__device__ __forceinline__ void tma_load_3d(uint32_t dst, const CUtensorMap* tm, uint32_t bar, int c0, int c1, int c2) {
  asm volatile("cp.async.bulk.tensor.3d.shared::cluster.global.mbarrier::complete_tx::bytes [%0], [%1, {%3, %4, %5}], [%2];"
               ::"r"(dst), "l"(tm), "r"(bar), "r"(c0), "r"(c1), "r"(c2) : "memory");
}
__device__ __forceinline__ void tma_load_4d_mc(uint32_t dst, const CUtensorMap* tm, uint32_t bar, int c0, int c1, int c2, int c3, uint16_t mask) {
  asm volatile("cp.async.bulk.tensor.4d.shared::cluster.global.mbarrier::complete_tx::bytes.multicast::cluster [%0], [%1, {%3, %4, %5, %6}], [%2], %7;"
               ::"r"(dst), "l"(tm), "r"(bar), "r"(c0), "r"(c1), "r"(c2), "r"(c3), "h"(mask) : "memory");
}
__device__ __forceinline__ void tma_store_3d(const CUtensorMap* tm, uint32_t src, int c0, int c1, int c2) {
  asm volatile("cp.async.bulk.tensor.3d.global.shared::cta.bulk_group [%0, {%2, %3, %4}], [%1];"
               ::"l"(tm), "r"(src), "r"(c0), "r"(c1), "r"(c2) : "memory");
}
__device__ __forceinline__ void bulk_load(uint32_t dst, const void* src, uint32_t bytes, uint32_t bar) {
  asm volatile("cp.async.bulk.shared::cluster.global.mbarrier::complete_tx::bytes [%0], [%1], %2, [%3];"
               ::"r"(dst), "l"(src), "r"(bytes), "r"(bar) : "memory");
}
__device__ __forceinline__ void dsmem_copy(uint32_t dst_remote, uint32_t src, uint32_t bytes, uint32_t bar_remote) {
  asm volatile("cp.async.bulk.shared::cluster.shared::cta.mbarrier::complete_tx::bytes [%0], [%1], %2, [%3];"
               ::"r"(dst_remote), "r"(src), "r"(bytes), "r"(bar_remote) : "memory");
}
__device__ __forceinline__ void stsm_x4_trans(uint32_t addr, uint32_t r0, uint32_t r1, uint32_t r2, uint32_t r3) {
  asm volatile("stmatrix.sync.aligned.m8n8.x4.trans.shared.b16 [%0], {%1, %2, %3, %4};" ::"r"(addr), "r"(r0), "r"(r1), "r"(r2), "r"(r3) : "memory");
}
__device__ __forceinline__ void stsm_x4(uint32_t addr, uint32_t r0, uint32_t r1, uint32_t r2, uint32_t r3) {
  asm volatile("stmatrix.sync.aligned.m8n8.x4.shared.b16 [%0], {%1, %2, %3, %4};" ::"r"(addr), "r"(r0), "r"(r1), "r"(r2), "r"(r3) : "memory");
}
__device__ __forceinline__ float2 lds64(uint32_t a) { float2 v; asm volatile("ld.shared.v2.f32 {%0, %1}, [%2];" : "=f"(v.x), "=f"(v.y) : "r"(a) : "memory"); return v; }
__device__ __forceinline__ void sts64(uint32_t a, float x, float y) { asm volatile("st.shared.v2.f32 [%0], {%1, %2};" ::"r"(a), "f"(x), "f"(y) : "memory"); }
__device__ __forceinline__ float tanh_fast(float x) { float y; asm("tanh.approx.f32 %0, %1;" : "=f"(y) : "f"(x)); return y; }
__device__ __forceinline__ uint32_t pack_bf16(float lo, float hi) { uint32_t r; asm("cvt.rn.bf16x2.f32 %0, %1, %2;" : "=r"(r) : "f"(hi), "f"(lo)); return r; }
__device__ __forceinline__ float gelu_tanh(float x) {
  const float k0 = 0.7978845608028654f, k1 = 0.7978845608028654f * 0.044715f;
  float u = x * fmaf(x * x, k1, k0);
  float hx = 0.5f * x;
  return fmaf(hx, tanh_fast(u), hx);
}
__device__ __forceinline__ uint64_t make_desc(uint32_t addr, uint32_t lbo, uint32_t sbo) {
  return (uint64_t)((addr & 0x3FFFF) >> 4) | ((uint64_t)(lbo >> 4) << 16) | ((uint64_t)(sbo >> 4) << 32) | ((uint64_t)1 << 62);
}

__device__ __forceinline__ uint32_t desc_lo(uint32_t addr, uint32_t lbo) { return ((addr & 0x3FFFF) >> 4) | ((lbo >> 4) << 16); }
__device__ __forceinline__ uint64_t desc_at(uint32_t lo, uint32_t off) { return ((uint64_t)0x40000040u << 32) | (uint64_t)(lo + (off >> 4)); }

__device__ __forceinline__ void wgmma_ss_n64(float (&d)[32], uint64_t da, uint64_t db, int scale_d) {
  asm volatile("{\n.reg .pred p;\nsetp.ne.b32 p, %34, 0;\n"
    "wgmma.mma_async.sync.aligned.m64n64k16.f32.bf16.bf16 {%0, %1, %2, %3, %4, %5, %6, %7, %8, %9, %10, %11, %12, %13, %14, %15, %16, %17, %18, %19, %20, %21, %22, %23, %24, %25, %26, %27, %28, %29, %30, %31}, %32, %33, p, 1, 1, 1, 0;\n}\n"
    : "+f"(d[0]), "+f"(d[1]), "+f"(d[2]), "+f"(d[3]), "+f"(d[4]), "+f"(d[5]), "+f"(d[6]), "+f"(d[7]), "+f"(d[8]), "+f"(d[9]), "+f"(d[10]), "+f"(d[11]), "+f"(d[12]), "+f"(d[13]), "+f"(d[14]), "+f"(d[15]), "+f"(d[16]), "+f"(d[17]), "+f"(d[18]), "+f"(d[19]), "+f"(d[20]), "+f"(d[21]), "+f"(d[22]), "+f"(d[23]), "+f"(d[24]), "+f"(d[25]), "+f"(d[26]), "+f"(d[27]), "+f"(d[28]), "+f"(d[29]), "+f"(d[30]), "+f"(d[31])
    : "l"(da), "l"(db), "r"(scale_d));
}

__device__ __forceinline__ void wgmma_ss_n32(float (&d)[16], uint64_t da, uint64_t db, int scale_d) {
  asm volatile("{\n.reg .pred p;\nsetp.ne.b32 p, %18, 0;\n"
    "wgmma.mma_async.sync.aligned.m64n32k16.f32.bf16.bf16 {%0, %1, %2, %3, %4, %5, %6, %7, %8, %9, %10, %11, %12, %13, %14, %15}, %16, %17, p, 1, 1, 1, 0;\n}\n"
    : "+f"(d[0]), "+f"(d[1]), "+f"(d[2]), "+f"(d[3]), "+f"(d[4]), "+f"(d[5]), "+f"(d[6]), "+f"(d[7]), "+f"(d[8]), "+f"(d[9]), "+f"(d[10]), "+f"(d[11]), "+f"(d[12]), "+f"(d[13]), "+f"(d[14]), "+f"(d[15])
    : "l"(da), "l"(db), "r"(scale_d));
}

__device__ __forceinline__ void wgmma_ss_n8(float (&d)[4], uint64_t da, uint64_t db, int scale_d) {
  asm volatile("{\n.reg .pred p;\nsetp.ne.b32 p, %6, 0;\n"
    "wgmma.mma_async.sync.aligned.m64n8k16.f32.bf16.bf16 {%0, %1, %2, %3}, %4, %5, p, 1, 1, 1, 0;\n}\n"
    : "+f"(d[0]), "+f"(d[1]), "+f"(d[2]), "+f"(d[3])
    : "l"(da), "l"(db), "r"(scale_d));
}

__device__ __forceinline__ void wgmma_rs_n64(float (&d)[32], uint32_t a0, uint32_t a1, uint32_t a2, uint32_t a3, uint64_t db, int scale_d) {
  asm volatile("{\n.reg .pred p;\nsetp.ne.b32 p, %37, 0;\n"
    "wgmma.mma_async.sync.aligned.m64n64k16.f32.bf16.bf16 {%0, %1, %2, %3, %4, %5, %6, %7, %8, %9, %10, %11, %12, %13, %14, %15, %16, %17, %18, %19, %20, %21, %22, %23, %24, %25, %26, %27, %28, %29, %30, %31}, {%32, %33, %34, %35}, %36, p, 1, 1, 1;\n}\n"
    : "+f"(d[0]), "+f"(d[1]), "+f"(d[2]), "+f"(d[3]), "+f"(d[4]), "+f"(d[5]), "+f"(d[6]), "+f"(d[7]), "+f"(d[8]), "+f"(d[9]), "+f"(d[10]), "+f"(d[11]), "+f"(d[12]), "+f"(d[13]), "+f"(d[14]), "+f"(d[15]), "+f"(d[16]), "+f"(d[17]), "+f"(d[18]), "+f"(d[19]), "+f"(d[20]), "+f"(d[21]), "+f"(d[22]), "+f"(d[23]), "+f"(d[24]), "+f"(d[25]), "+f"(d[26]), "+f"(d[27]), "+f"(d[28]), "+f"(d[29]), "+f"(d[30]), "+f"(d[31])
    : "r"(a0), "r"(a1), "r"(a2), "r"(a3), "l"(db), "r"(scale_d));
}

__host__ __device__ constexpr int unit_slot(int u) {
  constexpr int t[36] = {4, 5, 6, 7, 8, 4, 5, 6, 0, 7, 8, 4,  1, 5, 6, 0, 2, 7, 8, 4, 3, 1, 5, 6,
                         0, 2, 7, 8,  4, 3, 1, 5, 6, 0, 2, 7};
  return t[u];
}
__host__ __device__ constexpr int unit_wait(int u) {
  constexpr int t[36] = {-1, -1, -1, -1, -1, 0, 1, 2, 2, 3, 4, 5,  5, 6, 7, 8, 8, 9, 10, 11, 11, 12, 13, 14,
                         15, 16, 17, 18,  19, 20, 21, 22, 23, 24, 25, 26};
  return t[u];
}

__device__ __forceinline__ uint32_t stage_off(int g, int j) {
  return g == 0 ? (j < 2 ? 8 * kSlot + j * 8192 : 10 * kSlot + (j - 2) * 8192)
                : (j < 2 ? 12 * kSlot + j * 8192 : (j == 2 ? 11 * kSlot + 8192 : 9 * kSlot));
}

struct Params {
  CUtensorMap x, w1, w2, wf, wg, wo, g, out64, out56;
};

__device__ __forceinline__ void init_bar(uint32_t bars, int i) {
  const uint32_t a = bars + i * 8;
  const bool is_e = (i >= kBarE && i < kBarE + 27);
  mbar_init(a, is_e ? 8 : (i == kBarFE ? 9 : 1));
  if (!is_e) {
    uint32_t bytes = 16384;
    if (i == kBarFX) bytes = 8192;
    if (i == kBarFE) bytes = 8192 + kGEBytes;
    mbar_expect(a, bytes);
  }
}

__global__ void __cluster_dims__(2, 1, 1) __launch_bounds__(kThreads, 1)
rnnt_joint_kernel(const __grid_constant__ Params P) {
  extern __shared__ uint8_t smem_raw[];
  const uint32_t sb = (smem_u32(smem_raw) + 1023u) & ~1023u;
  const uint32_t bars = sb + kOffBar;
  const int warp = threadIdx.x >> 5, lane = threadIdx.x & 31;
  uint32_t cta;
  asm volatile("mov.u32 %0, %%cluster_ctarank;" : "=r"(cta));
  const uint32_t peer = cta ^ 1u;
  const int cl = blockIdx.x >> 1;
  const bool ge_cta = cl < 2;
  const int b = ge_cta ? cl : ((cl - 2) >> 5);
  const int r0 = ge_cta ? 32 * kR : ((cl - 2) & 31) * kR;
  const int rvalid = ge_cta ? kT2 - 32 * kR : kR;

  if (warp >= 8) {
    asm volatile("setmaxnreg.dec.sync.aligned.u32 40;");
    if (warp > 8) {
      if (elect_one()) {
#pragma unroll
        for (int i = 0; i < 6; i++) if (9 + (warp - 1) * 6 + i < kBarG) init_bar(bars, 9 + (warp - 1) * 6 + i);
        if (warp == 11) {
#pragma unroll
          for (int i = kBarRH; i < kNumBars; i++) mbar_init(bars + i * 8, 4);
        }
        asm volatile("fence.mbarrier_init.release.cluster;" ::: "memory");
      }
      __syncwarp();
      cluster_sync_relaxed();
      if (warp > 9) return;
#pragma unroll
      for (int g = 0; g < 2; g++) {
        mbar_wait(bars + (kBarRH + g) * 8);
        if (elect_one()) {
          const uint32_t src = sb + kSlotH * kSlot + (2 * cta + g) * 8192;
          dsmem_copy(mapa(src, peer), src, 8192, mapa(bars + kBarHX * 8, peer));
        }
        __syncwarp();
      }
#pragma unroll
      for (int g = 0; g < 2; g++) {
        mbar_wait(bars + (kBarRF + g) * 8);
        if (elect_one()) {
          const uint32_t src = sb + kSlotF * kSlot + (2 * cta + g) * 4096;
          dsmem_copy(mapa(src, peer), src, 4096, mapa(bars + kBarFX * 8, peer));
        }
        __syncwarp();
      }
#pragma unroll
      for (int g = 0; g < 2; g++) {
        mbar_wait(bars + (kBarRE + g) * 8);
        if (elect_one())
          dsmem_copy(mapa(sb + kSlotFE * kSlot + (2 * cta + g) * 4096, peer), sb + kSlotH * kSlot + g * 4096, 4096, mapa(bars + kBarFE * 8, peer));
        __syncwarp();
      }
      {
        int nxt0 = ((int)cta * 16 < rvalid) ? 0 : 4, nxt1 = ((int)cta * 16 + 8 < rvalid) ? 0 : 4;
        const long long t0 = clock64();
        while ((nxt0 < 4 || nxt1 < 4) && clock64() - t0 < 8000000ll) {
#pragma unroll
          for (int g = 0; g < 2; g++) {
            const int j = g ? nxt1 : nxt0;
            if (j < 4 && mbar_test(bars + (kBarPR + g * 4 + j) * 8)) {
              if (elect_one()) {
                const int rl0 = cta * 16 + g * 8;
                tma_store_3d((rl0 + 8 <= rvalid) ? &P.out64 : &P.out56, sb + stage_off(g, j), 0, (b * kT2 + r0 + rl0) * 8, j);
                asm volatile("cp.async.bulk.commit_group;" ::: "memory");
              }
              __syncwarp();
              if (g) nxt1++; else nxt0++;
            }
          }
        }
        if (elect_one()) asm volatile("cp.async.bulk.wait_group.read 0;" ::: "memory");
        __syncwarp();
        TS(2, 11);
      }
      return;
    }
    TS(2, 0);
    unsigned int ticket = 0;
    const int par = cta == 0 ? 1 : 0;
    const int q0 = cta == 0 ? 2 * r0 - 2 : 2 * r0 - 1;
    if (elect_one()) {
      asm volatile("cp.async.bulk.prefetch.tensor.4d.L2.global.tile [%0, {%1, %2, %3, %4}];" ::"l"(&P.x), "r"(0), "r"(par), "r"(q0), "r"(b) : "memory");
#pragma unroll
      for (int i = 0; i < 9; i++) { mbar_init(bars + i * 8, 1); mbar_expect(bars + i * 8, 16384); }
      if (ge_cta) { mbar_init(bars + kBarG * 8, 1); mbar_expect(bars + kBarG * 8, 4 * 16384 + 4096); mbar_init(bars + kBarP0 * 8, 8); }
      TS(2, 7);
      asm volatile("fence.mbarrier_init.release.cluster;" ::: "memory");
      fence_async_smem();
      TS(2, 8);
      if (ge_cta) {
        tma_load_3d(sb + kOffG, &P.g, bars + kBarG * 8, 0, b * 8, 0);
#pragma unroll
        for (int i = 0; i < 4; i++) tma_load_3d(sb + (9 + i) * kSlot, &P.wg, bars + kBarG * 8, 0, i * 64, 2 * cta);
      }
#pragma unroll
      for (int u = 0; u < 5; u++)
      {
        tma_load_3d(sb + unit_slot(u) * kSlot, &P.w1, bars + (kBarW + u) * 8, 0, (u % 3) * 256 + (u / 3) * 64, 2 * cta);
        if (u == 0) TS(2, 9);
      }
      TS(2, 10);
    }
    __syncwarp();
    TS(2, 6);
    cluster_sync_relaxed();
    TS(2, 1);
    if (elect_one()) {
#pragma unroll
      for (int p = 0; p < XFIRST; p++)
        tma_load_4d_mc(sb + p * kSlot + cta * 8192, &P.x, bars + (kBarX + p) * 8, p * 64, par, q0, b, (uint16_t)3);
    }
    __syncwarp();
    if (lane == 0) ticket = atomicAdd(&g_cta_count, 1u);
#pragma unroll
    for (int p = XFIRST; p < 4; p++) {
      if (XSTEP == 1 || ((p - XFIRST) & 1) == 0) mbar_wait(bars + (kBarX + p - XFIRST) * 8);
      if (ge_cta && p == 3) mbar_wait(bars + kBarP0 * 8);
      if (elect_one())
        tma_load_4d_mc(sb + p * kSlot + cta * 8192, &P.x, bars + (kBarX + p) * 8, p * 64, par, q0, b, (uint16_t)3);
      __syncwarp();
    }
#pragma unroll
    for (int u = 5; u < 36; u++) {
      if (unit_wait(u) != unit_wait(u - 1)) mbar_wait(bars + (kBarE + unit_wait(u)) * 8);
      if (u == 27) ticket = __shfl_sync(0xffffffffu, ticket, 0);
      if (elect_one()) {
        const uint32_t dst = sb + unit_slot(u) * kSlot, bar = bars + (kBarW + u) * 8;
        if (u < 12) tma_load_3d(dst, &P.w1, bar, 0, (u % 3) * 256 + (u / 3) * 64, 2 * cta);
        else if (u < 24) tma_load_3d(dst, &P.w2, bar, 0, ((u - 12) % 3) * 256 + ((2 * cta + (u - 12) / 3) & 3) * 64, 2 * cta);
        else if (u < 28) tma_load_3d(dst, &P.wf, bar, 0, ((2 * cta + (u - 24)) & 3) * 64, 2 * cta);
        else tma_load_3d(dst, &P.wo, bar, 0, ((u - 28) & 3) * 64, ((u - 28) >> 2) * 2);
        if (u == 27) {
          const unsigned int want = (ticket / kNumCtas + 1u) * 2u;
          const long long t0 = clock64();
          unsigned int v;
          do {
            asm volatile("ld.acquire.gpu.global.u32 %0, [%1];" : "=r"(v) : "l"(&g_ge_flag[b]) : "memory");
          } while ((int)(v - want) < 0 && clock64() - t0 < 4000000ll);
          asm volatile("fence.proxy.async;" ::: "memory");
          bulk_load(sb + kOffGE, reinterpret_cast<const char*>(g_ge) + b * kGEBytes, kGEBytes, bars + kBarFE * 8);
        }
      }
      __syncwarp();
      if (u == 11) TS(2, 2);
      if (u == 23) TS(2, 3);
      if (u == 27) TS(2, 4);
      if (u == 35) TS(2, 5);
    }
  } else {
    asm volatile("setmaxnreg.inc.sync.aligned.u32 232;");
    const int wg = warp >> 2, w = warp & 3;
    const int gq = lane >> 2, q = lane & 3;
    const uint32_t panel = 2 * cta + wg;
    const int ch = panel * 64 + w * 16 + gq;
    const uint32_t dA = desc_lo(sb + wg * 8192, 8192);
    const uint32_t dB = desc_lo(sb, 16);
    const uint32_t dBo = desc_lo(sb + cta * 2 * 8192, 16), dBp = desc_lo(sb + (cta ^ 1) * 2 * 8192, 16);
    const uint32_t dFo = desc_lo(sb + cta * 2 * 4096, 16), dFp = desc_lo(sb + (cta ^ 1) * 2 * 4096, 16);
    if (elect_one()) {
#pragma unroll
      for (int i = 0; i < 6; i++) init_bar(bars, 9 + warp * 6 + i);
      asm volatile("fence.mbarrier_init.release.cluster;" ::: "memory");
    }
    __syncwarp();
    cluster_sync_relaxed();
    if (w == 0) TS(wg, 0);

    if (ge_cta) {
      float ga[4];
      mbar_wait(bars + kBarG * 8);
      wg_fence();
#pragma unroll
      for (int i = 0; i < 4; i++) {
#pragma unroll
        for (int s = 0; s < 4; s++)
          wgmma_ss_n8(ga, desc_at(dA, (9 + i) * kSlot + s * 2048), desc_at(dB, kOffG + i * 1024 + s * 32), (i | s) != 0);
      }
      wg_commit();
      wg_wait<0>();
      if (lane == 0) mbar_arrive(bars + kBarP0 * 8);
      float* gp = g_ge + b * (kGEBytes / 4);
      gp[(2 * q) * (kGEPitch / 4) + ch] = ga[0];
      gp[(2 * q + 1) * (kGEPitch / 4) + ch] = ga[1];
      gp[(2 * q) * (kGEPitch / 4) + ch + 8] = ga[2];
      gp[(2 * q + 1) * (kGEPitch / 4) + ch + 8] = ga[3];
      __threadfence();
      bar_consumers();
      if (threadIdx.x == 0) asm volatile("red.release.gpu.global.add.u32 [%0], 1;" ::"l"(&g_ge_flag[b]) : "memory");
    }

    {
      float acc[32];
#pragma unroll
      for (int u = 0; u < 12; u++) {
        const int p = u / 3, tap = u % 3;
        if (tap == 0) mbar_wait(bars + (kBarX + p) * 8);
        mbar_wait(bars + (kBarW + u) * 8);
        if (u == 0 && w == 0) TS(wg, 1);
        wg_fence();
#pragma unroll
        for (int s = 0; s < 4; s++)
          wgmma_ss_n64(acc, desc_at(dA, unit_slot(u) * kSlot + s * 2048),
                       desc_at(dB, p * kSlot + (tap == 1 ? 8192 : (tap == 2 ? 128 : 0)) + s * 32), (u | s) != 0);
        wg_commit();
        if (u > 0) {
          wg_wait<1>();
          if (lane == 0) mbar_arrive(bars + (kBarE + u - 1) * 8);
        }
      }
      wg_wait<0>();
      if (lane == 0) mbar_arrive(bars + (kBarE + 11) * 8);
      if (w == 0) TS(wg, 2);
      const uint32_t hp = sb + kSlotH * kSlot + panel * 8192;
      const int mi = lane >> 3, l8 = lane & 7;
#pragma unroll
      for (int jb = 0; jb < 8; jb += 2) {
        uint32_t r[4];
#pragma unroll
        for (int t = 0; t < 2; t++) {
          r[2 * t + 0] = pack_bf16(gelu_tanh(acc[4 * (jb + t) + 0]), gelu_tanh(acc[4 * (jb + t) + 1]));
          r[2 * t + 1] = pack_bf16(gelu_tanh(acc[4 * (jb + t) + 2]), gelu_tanh(acc[4 * (jb + t) + 3]));
        }
        const int n = 8 * (jb + (mi >> 1)) + l8;
        const int row = n >> 1, chunk = 2 * w + (mi & 1);
        stsm_x4_trans(hp + (n & 1) * 4096 + row * 128 + ((chunk ^ (row & 7)) << 4), r[0], r[1], r[2], r[3]);
      }
      fence_async_smem();
      __syncwarp();
      if (lane == 0) mbar_arrive(bars + (kBarRH + wg) * 8);
      mbar_wait(bars + kBarRH * 8);
      mbar_wait(bars + (kBarRH + 1) * 8);
      if (w == 0) TS(wg, 3);
    }
    {
      float acc[16];
#pragma unroll
      for (int v = 0; v < 12; v++) {
        const int i = v / 3, tap = v % 3;
        if (v == 6) { mbar_wait_cluster(bars + kBarHX * 8); if (w == 0) TS(wg, 4); }
        mbar_wait(bars + (kBarW + 12 + v) * 8);
        wg_fence();
#pragma unroll
        for (int s = 0; s < 4; s++)
          wgmma_ss_n32(acc, desc_at(dA, unit_slot(12 + v) * kSlot + s * 2048),
                       desc_at(i < 2 ? dBo : dBp, kSlotH * kSlot + (i & 1) * 8192 + (tap == 1 ? 4096 : (tap == 2 ? 128 : 0)) + s * 32), (v | s) != 0);
        wg_commit();
        if (v > 0) {
          wg_wait<1>();
          if (lane == 0) mbar_arrive(bars + (kBarE + 12 + v - 1) * 8);
        }
      }
      wg_wait<0>();
      if (lane == 0) mbar_arrive(bars + (kBarE + 23) * 8);
      if (w == 0) TS(wg, 5);
      const uint32_t fp = sb + kSlotF * kSlot + panel * 4096;
      const int mi = lane >> 3, l8 = lane & 7;
#pragma unroll
      for (int jb = 0; jb < 4; jb += 2) {
        uint32_t r[4];
#pragma unroll
        for (int t = 0; t < 2; t++) {
          r[2 * t + 0] = pack_bf16(gelu_tanh(acc[4 * (jb + t) + 0]), gelu_tanh(acc[4 * (jb + t) + 1]));
          r[2 * t + 1] = pack_bf16(gelu_tanh(acc[4 * (jb + t) + 2]), gelu_tanh(acc[4 * (jb + t) + 3]));
        }
        const int n = 8 * (jb + (mi >> 1)) + l8;
        const int chunk = 2 * w + (mi & 1);
        stsm_x4_trans(fp + n * 128 + ((chunk ^ (n & 7)) << 4), r[0], r[1], r[2], r[3]);
      }
      fence_async_smem();
      __syncwarp();
      if (lane == 0) mbar_arrive(bars + (kBarRF + wg) * 8);
      mbar_wait(bars + kBarRF * 8);
      mbar_wait(bars + (kBarRF + 1) * 8);
      if (w == 0) TS(wg, 6);
    }
    {
      float acc[16];
#pragma unroll
      for (int i = 0; i < 4; i++) {
        if (i == 2) { mbar_wait_cluster(bars + kBarFX * 8); if (w == 0) TS(wg, 7); }
        mbar_wait(bars + (kBarW + 24 + i) * 8);
        wg_fence();
#pragma unroll
        for (int s = 0; s < 4; s++)
          wgmma_ss_n32(acc, desc_at(dA, unit_slot(24 + i) * kSlot + s * 2048),
                       desc_at(i < 2 ? dFo : dFp, kSlotF * kSlot + (i & 1) * 4096 + s * 32), (i | s) != 0);
        wg_commit();
        if (i > 0) {
          wg_wait<1>();
          if (lane == 0) mbar_arrive(bars + (kBarE + 24 + i - 1) * 8);
        }
      }
      wg_wait<0>();
      if (w == 0) TS(wg, 8);
      const uint32_t sw = ((ch >> 1) & 3) * 2;
      const uint32_t own = sb + kSlotFE * kSlot + ch * 64;
      const uint32_t stg = sb + kSlotH * kSlot + (ch - (int)cta * 128) * 64;
#pragma unroll
      for (int jb = 0; jb < 4; jb++) {
        const uint32_t base = ((uint32_t)(jb >> 1) == cta) ? own : stg;
        const uint32_t pr = (4 * (jb & 1) + q) ^ sw;
        sts64(base + pr * 8, acc[4 * jb + 0], acc[4 * jb + 1]);
        sts64(base + 512 + pr * 8, acc[4 * jb + 2], acc[4 * jb + 3]);
      }
      fence_async_smem();
      __syncwarp();
      if (lane == 0) { mbar_arrive(bars + (kBarRE + wg) * 8); mbar_arrive(bars + kBarFE * 8); }
      if (w == 0) TS(wg, 9);
    }
    const int rl0 = cta * 16 + wg * 8;
    mbar_wait_cluster(bars + kBarFE * 8);
    asm volatile("barrier.cluster.arrive.relaxed.aligned;" ::: "memory");
    if (wg == 1) asm volatile("bar.sync 4, 256;" ::: "memory");
    if (rl0 < rvalid) {
      if (w == 0) TS(wg, 10);
      const uint32_t fe_t = sb + kSlotFE * kSlot + (2 * q) * 64 + (((4 * wg + w) ^ (2 * q)) << 3);
      const uint32_t ge_t = sb + kOffGE + gq * kGEPitch + (2 * q) * 4;
      const int mi = lane >> 3, l8 = lane & 7;
      const uint32_t st = sb + (16 * w + (mi & 1) * 8 + l8) * 128;
      uint32_t A[64];
      float acc[2][32];
#pragma unroll
      for (int kk = 0; kk < 16; kk++) {
        const float2 f0 = lds64(fe_t + kk * 1024), f1 = lds64(fe_t + kk * 1024 + 64);
        const float2 f2 = lds64(fe_t + kk * 1024 + 512), f3 = lds64(fe_t + kk * 1024 + 576);
        const float2 g0 = lds64(ge_t + kk * 64), g1 = lds64(ge_t + kk * 64 + 32);
        A[4 * kk + 0] = pack_bf16(tanh_fast(f0.x + g0.x), tanh_fast(f1.x + g0.y));
        A[4 * kk + 1] = pack_bf16(tanh_fast(f0.y + g0.x), tanh_fast(f1.y + g0.y));
        A[4 * kk + 2] = pack_bf16(tanh_fast(f2.x + g1.x), tanh_fast(f3.x + g1.y));
        A[4 * kk + 3] = pack_bf16(tanh_fast(f2.y + g1.x), tanh_fast(f3.y + g1.y));
      }
      if (wg == 0) asm volatile("bar.arrive 4, 256;" ::: "memory");
      if (w == 0) TS(wg, 15);
#pragma unroll
      for (int kk = 0; kk < 16; kk++) {
        if ((kk & 3) == 0) { mbar_wait(bars + (kBarW + 28 + (kk >> 2)) * 8); wg_fence(); }
        wgmma_rs_n64(acc[0], A[4 * kk], A[4 * kk + 1], A[4 * kk + 2], A[4 * kk + 3],
                     desc_at(dB, unit_slot(28 + (kk >> 2)) * kSlot + (kk & 3) * 2048), kk != 0);
      }
      wg_commit();
      if (w == 0) TS(wg, 11);
#pragma unroll
      for (int j = 0; j < 4; j++) {
        const int jn = j + 1;
        if (jn == 2) {
#pragma unroll
          for (int i = 0; i < 4; i++) mbar_wait(bars + (kBarW + 32 + i) * 8);
        }
        if (j < 3) wg_fence();
        const uint32_t stj = st + (wg ? stage_off(1, j) : stage_off(0, j));
#pragma unroll
        for (int kk = 0; kk < 16; kk++) {
          if (j < 3)
            wgmma_rs_n64(acc[jn & 1], A[4 * kk], A[4 * kk + 1], A[4 * kk + 2], A[4 * kk + 3],
                         desc_at(dB, unit_slot(28 + (jn >> 1) * 4 + (kk >> 2)) * kSlot + (jn & 1) * 8192 + (kk & 3) * 2048), kk != 0);
          if (kk == 1) {
            if (j < 3) { wg_commit(); wg_wait<1>(); } else { wg_wait<0>(); }
          }
          if (kk >= 2 && kk < 10 && (kk & 1) == 0) {
            const int jb = kk - 2;
            const uint32_t r0_ = pack_bf16(acc[j & 1][4 * jb + 0], acc[j & 1][4 * jb + 1]), r1_ = pack_bf16(acc[j & 1][4 * jb + 2], acc[j & 1][4 * jb + 3]);
            const uint32_t r2_ = pack_bf16(acc[j & 1][4 * jb + 4], acc[j & 1][4 * jb + 5]), r3_ = pack_bf16(acc[j & 1][4 * jb + 6], acc[j & 1][4 * jb + 7]);
            stsm_x4(stj + (((jb + (mi >> 1)) ^ l8) << 4), r0_, r1_, r2_, r3_);
          }
          if (kk == 9) {
            fence_async_smem();
            __syncwarp();
            mbar_arrive_pred(bars + (kBarPR + wg * 4 + j) * 8, lane == 0);
          }
        }
        if (j < 3) wg_commit();
        if (j == 0 && w == 0) TS(wg, 12);
        if (j == 2 && w == 0) TS(wg, 13);
      }
      if (w == 0) TS(wg, 14);
    } else if (wg == 0) {
      asm volatile("bar.arrive 4, 256;" ::: "memory");
    }
    asm volatile("barrier.cluster.wait.aligned;" ::: "memory");
  }
}

typedef CUresult (*EncodeFn)(CUtensorMap*, CUtensorMapDataType, cuuint32_t, void*, const cuuint64_t*, const cuuint64_t*,
                             const cuuint32_t*, const cuuint32_t*, CUtensorMapInterleave, CUtensorMapSwizzle,
                             CUtensorMapL2promotion, CUtensorMapFloatOOBfill);

void make_map3(EncodeFn enc, CUtensorMap* tm, const void* ptr, uint64_t rows, uint32_t box_rows, uint32_t box_panels) {
  cuuint64_t gd[3] = {64, rows, 4};
  cuuint64_t gs[2] = {512, 128};
  cuuint32_t bd[3] = {64, box_rows, box_panels};
  cuuint32_t es[3] = {1, 1, 1};
  enc(tm, CU_TENSOR_MAP_DATA_TYPE_BFLOAT16, 3, const_cast<void*>(ptr), gd, gs, bd, es, CU_TENSOR_MAP_INTERLEAVE_NONE,
      CU_TENSOR_MAP_SWIZZLE_128B, CU_TENSOR_MAP_L2_PROMOTION_L2_256B, CU_TENSOR_MAP_FLOAT_OOB_FILL_NONE);
}

}

extern "C" void kernel_launch(void* const* d_in, const int* in_sizes, int n_in, void* d_out, int out_size) {
  static EncodeFn enc = nullptr;
  if (!enc) {
    cudaDriverEntryPointQueryResult qr;
    cudaGetDriverEntryPoint("cuTensorMapEncodeTiled", (void**)&enc, cudaEnableDefault, &qr);
    cudaFuncSetAttribute(rnnt_joint_kernel, cudaFuncAttributeMaxDynamicSharedMemorySize, kSmemBytes);
  }
  Params P;
  {
    cuuint64_t gd[4] = {256, 2, 2000, 2};
    cuuint64_t gs[3] = {512, 1024, 4000ull * 512};
    cuuint32_t bd[4] = {64, 1, 64, 1};
    cuuint32_t es[4] = {1, 1, 1, 1};
    enc(&P.x, CU_TENSOR_MAP_DATA_TYPE_BFLOAT16, 4, d_in[0], gd, gs, bd, es, CU_TENSOR_MAP_INTERLEAVE_NONE,
        CU_TENSOR_MAP_SWIZZLE_128B, XPROMO, CU_TENSOR_MAP_FLOAT_OOB_FILL_NONE);
  }
  make_map3(enc, &P.w1, d_in[1], 768, 64, 2);
  make_map3(enc, &P.w2, d_in[2], 768, 64, 2);
  make_map3(enc, &P.g, d_in[3], 16, 8, 4);
  make_map3(enc, &P.wf, d_in[4], 256, 64, 2);
  make_map3(enc, &P.wg, d_in[5], 256, 64, 2);
  make_map3(enc, &P.wo, d_in[6], 256, 64, 2);
  make_map3(enc, &P.out64, d_out, 16000, 64, 1);
  make_map3(enc, &P.out56, d_out, 16000, 56, 1);
  rnnt_joint_kernel<<<kNumCtas, kThreads, kSmemBytes>>>(P);
}
```

```cpp
#include <cuda_runtime.h>
#include <cuda_bf16.h>
#include <cuda.h>
#include <stdint.h>

#define XPREF 1
#define XFIRST 3
#define XSTEP 1
#define XPROMO CU_TENSOR_MAP_L2_PROMOTION_L2_128B
namespace {

constexpr int kT2 = 1000;
constexpr int kR = 31;
constexpr int kNumCtas = 132;
constexpr int kThreads = 384;
constexpr int kSlot = 16384;

constexpr int kSlotFE = 9, kSlotF = 10, kSlotH = 11;
constexpr int kOffG = 13 * kSlot;
constexpr int kOffGE = kOffG + 4096;
constexpr int kGEPitch = 272;
constexpr int kGEBytes = 32 * kGEPitch;
constexpr int kOffBar = kOffGE + kGEBytes;
constexpr int kBarX = 0;
constexpr int kBarW = 4;
constexpr int kBarE = 40;
constexpr int kBarHX = 67, kBarFX = 68, kBarFE = 69, kBarG = 70, kBarP0 = 71;
constexpr int kBarRH = 72, kBarRF = 74, kBarRE = 76;
constexpr int kBarPR = 78;
constexpr int kNumBars = 86;
constexpr int kSmemBytes = kOffBar + kNumBars * 8 + 1024;

__device__ __align__(128) float g_ge[2 * kGEBytes / 4];
__device__ unsigned int g_ge_flag[2];
__device__ unsigned int g_cta_count;

#define TS(slot_, idx_) do {} while (0)

__device__ __forceinline__ uint32_t smem_u32(const void* p) { return (uint32_t)__cvta_generic_to_shared(p); }
__device__ __forceinline__ void mbar_init(uint32_t a, uint32_t c) { asm volatile("mbarrier.init.shared.b64 [%0], %1;" ::"r"(a), "r"(c) : "memory"); }
__device__ __forceinline__ void mbar_expect(uint32_t a, uint32_t b) { asm volatile("mbarrier.arrive.expect_tx.shared.b64 _, [%0], %1;" ::"r"(a), "r"(b) : "memory"); }
__device__ __forceinline__ void mbar_arrive(uint32_t a) { asm volatile("mbarrier.arrive.shared.b64 _, [%0];" ::"r"(a) : "memory"); }
__device__ __forceinline__ void mbar_arrive_pred(uint32_t a, bool p) {
  asm volatile("{\n.reg .pred q;\nsetp.ne.u32 q, %1, 0;\n@q mbarrier.arrive.shared.b64 _, [%0];\n}\n" ::"r"(a), "r"((uint32_t)p) : "memory");
}
__device__ __forceinline__ bool mbar_try(uint32_t a) {
  uint32_t ok;
  asm volatile("{\n.reg .pred p;\nmbarrier.try_wait.parity.shared.b64 p, [%1], 0;\nselp.u32 %0, 1, 0, p;\n}\n" : "=r"(ok) : "r"(a) : "memory");
  return ok != 0;
}
__device__ __forceinline__ bool mbar_test(uint32_t a) {
  uint32_t ok;
  asm volatile("{\n.reg .pred p;\nmbarrier.test_wait.parity.shared.b64 p, [%1], 0;\nselp.u32 %0, 1, 0, p;\n}\n" : "=r"(ok) : "r"(a) : "memory");
  return ok != 0;
}
__device__ __forceinline__ bool mbar_try_cluster(uint32_t a) {
  uint32_t ok;
  asm volatile("{\n.reg .pred p;\nmbarrier.try_wait.parity.acquire.cluster.shared.b64 p, [%1], 0;\nselp.u32 %0, 1, 0, p;\n}\n" : "=r"(ok) : "r"(a) : "memory");
  return ok != 0;
}
__device__ __forceinline__ void mbar_wait_slow(uint32_t a) {
  const long long t0 = clock64();
  while (!mbar_try(a)) { if (clock64() - t0 > 4000000ll) break; }
}
__device__ __forceinline__ void mbar_wait_cluster_slow(uint32_t a) {
  const long long t0 = clock64();
  while (!mbar_try_cluster(a)) { if (clock64() - t0 > 4000000ll) break; }
}
__device__ __forceinline__ void mbar_wait(uint32_t a) { if (!mbar_try(a)) mbar_wait_slow(a); }
__device__ __forceinline__ void mbar_wait_cluster(uint32_t a) { if (!mbar_try_cluster(a)) mbar_wait_cluster_slow(a); }
__device__ __forceinline__ uint32_t mapa(uint32_t a, uint32_t r) { uint32_t d; asm volatile("mapa.shared::cluster.u32 %0, %1, %2;" : "=r"(d) : "r"(a), "r"(r)); return d; }
__device__ __forceinline__ bool elect_one() { uint32_t p; asm volatile("{\n.reg .pred P;\nelect.sync _|P, 0xffffffff;\nselp.u32 %0, 1, 0, P;\n}\n" : "=r"(p)); return p != 0; }
__device__ __forceinline__ void fence_async_smem() { asm volatile("fence.proxy.async.shared::cta;" ::: "memory"); }
__device__ __forceinline__ void bar_consumers() { asm volatile("bar.sync 1, 256;" ::: "memory"); }
__device__ __forceinline__ void bar_wg(int wg) { asm volatile("bar.sync %0, 128;" ::"r"(2 + wg) : "memory"); }
__device__ __forceinline__ void cluster_sync_relaxed() { asm volatile("barrier.cluster.arrive.relaxed.aligned;\nbarrier.cluster.wait.aligned;" ::: "memory"); }
__device__ __forceinline__ void wg_fence() { asm volatile("wgmma.fence.sync.aligned;" ::: "memory"); }
__device__ __forceinline__ void wg_commit() { asm volatile("wgmma.commit_group.sync.aligned;" ::: "memory"); }
template <int N> __device__ __forceinline__ void wg_wait() { asm volatile("wgmma.wait_group.sync.aligned %0;" ::"n"(N) : "memory"); }

__device__ __forceinline__ void tma_load_3d(uint32_t dst, const CUtensorMap* tm, uint32_t bar, int c0, int c1, int c2) {
  asm volatile("cp.async.bulk.tensor.3d.shared::cluster.global.mbarrier::complete_tx::bytes [%0], [%1, {%3, %4, %5}], [%2];"
               ::"r"(dst), "l"(tm), "r"(bar), "r"(c0), "r"(c1), "r"(c2) : "memory");
}
__device__ __forceinline__ void tma_load_4d_mc(uint32_t dst, const CUtensorMap* tm, uint32_t bar, int c0, int c1, int c2, int c3, uint16_t mask) {
  asm volatile("cp.async.bulk.tensor.4d.shared::cluster.global.mbarrier::complete_tx::bytes.multicast::cluster [%0], [%1, {%3, %4, %5, %6}], [%2], %7;"
               ::"r"(dst), "l"(tm), "r"(bar), "r"(c0), "r"(c1), "r"(c2), "r"(c3), "h"(mask) : "memory");
}
__device__ __forceinline__ void tma_store_3d(const CUtensorMap* tm, uint32_t src, int c0, int c1, int c2) {
  asm volatile("cp.async.bulk.tensor.3d.global.shared::cta.bulk_group [%0, {%2, %3, %4}], [%1];"
               ::"l"(tm), "r"(src), "r"(c0), "r"(c1), "r"(c2) : "memory");
}
__device__ __forceinline__ void bulk_load(uint32_t dst, const void* src, uint32_t bytes, uint32_t bar) {
  asm volatile("cp.async.bulk.shared::cluster.global.mbarrier::complete_tx::bytes [%0], [%1], %2, [%3];"
               ::"r"(dst), "l"(src), "r"(bytes), "r"(bar) : "memory");
}
__device__ __forceinline__ void dsmem_copy(uint32_t dst_remote, uint32_t src, uint32_t bytes, uint32_t bar_remote) {
  asm volatile("cp.async.bulk.shared::cluster.shared::cta.mbarrier::complete_tx::bytes [%0], [%1], %2, [%3];"
               ::"r"(dst_remote), "r"(src), "r"(bytes), "r"(bar_remote) : "memory");
}
__device__ __forceinline__ void stsm_x4_trans(uint32_t addr, uint32_t r0, uint32_t r1, uint32_t r2, uint32_t r3) {
  asm volatile("stmatrix.sync.aligned.m8n8.x4.trans.shared.b16 [%0], {%1, %2, %3, %4};" ::"r"(addr), "r"(r0), "r"(r1), "r"(r2), "r"(r3) : "memory");
}
__device__ __forceinline__ void stsm_x4(uint32_t addr, uint32_t r0, uint32_t r1, uint32_t r2, uint32_t r3) {
  asm volatile("stmatrix.sync.aligned.m8n8.x4.shared.b16 [%0], {%1, %2, %3, %4};" ::"r"(addr), "r"(r0), "r"(r1), "r"(r2), "r"(r3) : "memory");
}
__device__ __forceinline__ float2 lds64(uint32_t a) { float2 v; asm volatile("ld.shared.v2.f32 {%0, %1}, [%2];" : "=f"(v.x), "=f"(v.y) : "r"(a) : "memory"); return v; }
__device__ __forceinline__ float4 lds128(uint32_t a) { float4 v; asm volatile("ld.shared.v4.f32 {%0, %1, %2, %3}, [%4];" : "=f"(v.x), "=f"(v.y), "=f"(v.z), "=f"(v.w) : "r"(a) : "memory"); return v; }
__device__ __forceinline__ void sts64(uint32_t a, float x, float y) { asm volatile("st.shared.v2.f32 [%0], {%1, %2};" ::"r"(a), "f"(x), "f"(y) : "memory"); }
__device__ __forceinline__ float tanh_fast(float x) { float y; asm("tanh.approx.f32 %0, %1;" : "=f"(y) : "f"(x)); return y; }
__device__ __forceinline__ uint32_t pack_bf16(float lo, float hi) { uint32_t r; asm("cvt.rn.bf16x2.f32 %0, %1, %2;" : "=r"(r) : "f"(hi), "f"(lo)); return r; }
__device__ __forceinline__ float gelu_tanh(float x) {
  const float k0 = 0.7978845608028654f, k1 = 0.7978845608028654f * 0.044715f;
  float u = x * fmaf(x * x, k1, k0);
  float hx = 0.5f * x;
  return fmaf(hx, tanh_fast(u), hx);
}
__device__ __forceinline__ uint64_t make_desc(uint32_t addr, uint32_t lbo, uint32_t sbo) {
  return (uint64_t)((addr & 0x3FFFF) >> 4) | ((uint64_t)(lbo >> 4) << 16) | ((uint64_t)(sbo >> 4) << 32) | ((uint64_t)1 << 62);
}

__device__ __forceinline__ uint32_t desc_lo(uint32_t addr, uint32_t lbo) { return ((addr & 0x3FFFF) >> 4) | ((lbo >> 4) << 16); }
__device__ __forceinline__ uint64_t desc_at(uint32_t lo, uint32_t off) { return ((uint64_t)0x40000040u << 32) | (uint64_t)(lo + (off >> 4)); }

__device__ __forceinline__ void wgmma_ss_n64(float (&d)[32], uint64_t da, uint64_t db, int scale_d) {
  asm volatile("{\n.reg .pred p;\nsetp.ne.b32 p, %34, 0;\n"
    "wgmma.mma_async.sync.aligned.m64n64k16.f32.bf16.bf16 {%0, %1, %2, %3, %4, %5, %6, %7, %8, %9, %10, %11, %12, %13, %14, %15, %16, %17, %18, %19, %20, %21, %22, %23, %24, %25, %26, %27, %28, %29, %30, %31}, %32, %33, p, 1, 1, 1, 0;\n}\n"
    : "+f"(d[0]), "+f"(d[1]), "+f"(d[2]), "+f"(d[3]), "+f"(d[4]), "+f"(d[5]), "+f"(d[6]), "+f"(d[7]), "+f"(d[8]), "+f"(d[9]), "+f"(d[10]), "+f"(d[11]), "+f"(d[12]), "+f"(d[13]), "+f"(d[14]), "+f"(d[15]), "+f"(d[16]), "+f"(d[17]), "+f"(d[18]), "+f"(d[19]), "+f"(d[20]), "+f"(d[21]), "+f"(d[22]), "+f"(d[23]), "+f"(d[24]), "+f"(d[25]), "+f"(d[26]), "+f"(d[27]), "+f"(d[28]), "+f"(d[29]), "+f"(d[30]), "+f"(d[31])
    : "l"(da), "l"(db), "r"(scale_d));
}

__device__ __forceinline__ void wgmma_ss_n32(float (&d)[16], uint64_t da, uint64_t db, int scale_d) {
  asm volatile("{\n.reg .pred p;\nsetp.ne.b32 p, %18, 0;\n"
    "wgmma.mma_async.sync.aligned.m64n32k16.f32.bf16.bf16 {%0, %1, %2, %3, %4, %5, %6, %7, %8, %9, %10, %11, %12, %13, %14, %15}, %16, %17, p, 1, 1, 1, 0;\n}\n"
    : "+f"(d[0]), "+f"(d[1]), "+f"(d[2]), "+f"(d[3]), "+f"(d[4]), "+f"(d[5]), "+f"(d[6]), "+f"(d[7]), "+f"(d[8]), "+f"(d[9]), "+f"(d[10]), "+f"(d[11]), "+f"(d[12]), "+f"(d[13]), "+f"(d[14]), "+f"(d[15])
    : "l"(da), "l"(db), "r"(scale_d));
}

__device__ __forceinline__ void wgmma_ss_n8(float (&d)[4], uint64_t da, uint64_t db, int scale_d) {
  asm volatile("{\n.reg .pred p;\nsetp.ne.b32 p, %6, 0;\n"
    "wgmma.mma_async.sync.aligned.m64n8k16.f32.bf16.bf16 {%0, %1, %2, %3}, %4, %5, p, 1, 1, 1, 0;\n}\n"
    : "+f"(d[0]), "+f"(d[1]), "+f"(d[2]), "+f"(d[3])
    : "l"(da), "l"(db), "r"(scale_d));
}

__device__ __forceinline__ void wgmma_rs_n64(float (&d)[32], uint32_t a0, uint32_t a1, uint32_t a2, uint32_t a3, uint64_t db, int scale_d) {
  asm volatile("{\n.reg .pred p;\nsetp.ne.b32 p, %37, 0;\n"
    "wgmma.mma_async.sync.aligned.m64n64k16.f32.bf16.bf16 {%0, %1, %2, %3, %4, %5, %6, %7, %8, %9, %10, %11, %12, %13, %14, %15, %16, %17, %18, %19, %20, %21, %22, %23, %24, %25, %26, %27, %28, %29, %30, %31}, {%32, %33, %34, %35}, %36, p, 1, 1, 1;\n}\n"
    : "+f"(d[0]), "+f"(d[1]), "+f"(d[2]), "+f"(d[3]), "+f"(d[4]), "+f"(d[5]), "+f"(d[6]), "+f"(d[7]), "+f"(d[8]), "+f"(d[9]), "+f"(d[10]), "+f"(d[11]), "+f"(d[12]), "+f"(d[13]), "+f"(d[14]), "+f"(d[15]), "+f"(d[16]), "+f"(d[17]), "+f"(d[18]), "+f"(d[19]), "+f"(d[20]), "+f"(d[21]), "+f"(d[22]), "+f"(d[23]), "+f"(d[24]), "+f"(d[25]), "+f"(d[26]), "+f"(d[27]), "+f"(d[28]), "+f"(d[29]), "+f"(d[30]), "+f"(d[31])
    : "r"(a0), "r"(a1), "r"(a2), "r"(a3), "l"(db), "r"(scale_d));
}

__host__ __device__ constexpr int unit_slot(int u) {
  constexpr int t[36] = {4, 5, 6, 7, 8, 4, 5, 6, 0, 7, 8, 4,  1, 5, 6, 0, 2, 7, 8, 4, 3, 1, 5, 6,
                         0, 2, 7, 8,  4, 3, 1, 5, 6, 0, 2, 7};
  return t[u];
}
__host__ __device__ constexpr int unit_wait(int u) {
  constexpr int t[36] = {-1, -1, -1, -1, -1, 0, 1, 2, 2, 3, 4, 5,  5, 6, 7, 8, 8, 9, 10, 11, 11, 12, 13, 14,
                         15, 16, 17, 18,  19, 20, 21, 22, 23, 24, 25, 26};
  return t[u];
}

__device__ __forceinline__ uint32_t stage_off(int g, int j) {
  return g == 0 ? (j < 2 ? 8 * kSlot + j * 8192 : 10 * kSlot + (j - 2) * 8192)
                : (j < 2 ? 12 * kSlot + j * 8192 : (j == 2 ? 11 * kSlot + 8192 : 9 * kSlot));
}

struct Params {
  CUtensorMap x, w1, w2, wf, wg, wo, g, out64, out56;
};

__device__ __forceinline__ void init_bar(uint32_t bars, int i) {
  const uint32_t a = bars + i * 8;
  const bool is_e = (i >= kBarE && i < kBarE + 27);
  mbar_init(a, is_e ? 8 : (i == kBarFE ? 9 : 1));
  if (!is_e) {
    uint32_t bytes = 16384;
    if (i == kBarFX) bytes = 8192;
    if (i == kBarFE) bytes = 8192 + kGEBytes;
    mbar_expect(a, bytes);
  }
}

__global__ void __cluster_dims__(2, 1, 1) __launch_bounds__(kThreads, 1)
rnnt_joint_kernel(const __grid_constant__ Params P) {
  extern __shared__ uint8_t smem_raw[];
  const uint32_t sb = (smem_u32(smem_raw) + 1023u) & ~1023u;
  const uint32_t bars = sb + kOffBar;
  const int warp = threadIdx.x >> 5, lane = threadIdx.x & 31;
  uint32_t cta;
  asm volatile("mov.u32 %0, %%cluster_ctarank;" : "=r"(cta));
  const uint32_t peer = cta ^ 1u;
  const int cl = blockIdx.x >> 1;
  const bool ge_cta = cl < 2;
  const int b = ge_cta ? cl : ((cl - 2) >> 5);
  const int r0 = ge_cta ? 32 * kR : ((cl - 2) & 31) * kR;
  const int rvalid = ge_cta ? kT2 - 32 * kR : kR;

  if (warp >= 8) {
    asm volatile("setmaxnreg.dec.sync.aligned.u32 40;");
    if (warp > 8) {
      if (elect_one()) {
#pragma unroll
        for (int i = 0; i < 5; i++) if (57 + (warp - 9) * 5 + i < kBarG) init_bar(bars, 57 + (warp - 9) * 5 + i);
#pragma unroll
        for (int i = 0; i < 5; i++) if (kBarRH + (warp - 9) * 5 + i < kNumBars) mbar_init(bars + (kBarRH + (warp - 9) * 5 + i) * 8, 4);
        asm volatile("fence.mbarrier_init.release.cluster;" ::: "memory");
      }
      __syncwarp();
      cluster_sync_relaxed();
      if (warp > 9) return;
#pragma unroll
      for (int g = 0; g < 2; g++) {
        mbar_wait(bars + (kBarRH + g) * 8);
        if (elect_one()) {
          const uint32_t src = sb + kSlotH * kSlot + (2 * cta + g) * 8192;
          dsmem_copy(mapa(src, peer), src, 8192, mapa(bars + kBarHX * 8, peer));
        }
        __syncwarp();
      }
#pragma unroll
      for (int g = 0; g < 2; g++) {
        mbar_wait(bars + (kBarRF + g) * 8);
        if (elect_one()) {
          const uint32_t src = sb + kSlotF * kSlot + (2 * cta + g) * 4096;
          dsmem_copy(mapa(src, peer), src, 4096, mapa(bars + kBarFX * 8, peer));
        }
        __syncwarp();
      }
#pragma unroll
      for (int g = 0; g < 2; g++) {
        mbar_wait(bars + (kBarRE + g) * 8);
        if (elect_one())
          dsmem_copy(mapa(sb + kSlotFE * kSlot + (2 * cta + g) * 4096, peer), sb + kSlotH * kSlot + g * 4096, 4096, mapa(bars + kBarFE * 8, peer));
        __syncwarp();
      }
      {
        int nxt0 = ((int)cta * 16 < rvalid) ? 0 : 4, nxt1 = ((int)cta * 16 + 8 < rvalid) ? 0 : 4;
        const long long t0 = clock64();
        while ((nxt0 < 4 || nxt1 < 4) && clock64() - t0 < 8000000ll) {
#pragma unroll
          for (int g = 0; g < 2; g++) {
            const int j = g ? nxt1 : nxt0;
            if (j < 4 && mbar_test(bars + (kBarPR + g * 4 + j) * 8)) {
              if (elect_one()) {
                const int rl0 = cta * 16 + g * 8;
                tma_store_3d((rl0 + 8 <= rvalid) ? &P.out64 : &P.out56, sb + stage_off(g, j), 0, (b * kT2 + r0 + rl0) * 8, j);
                asm volatile("cp.async.bulk.commit_group;" ::: "memory");
              }
              __syncwarp();
              if (g) nxt1++; else nxt0++;
            }
          }
        }
        if (elect_one()) asm volatile("cp.async.bulk.wait_group.read 0;" ::: "memory");
        __syncwarp();
        TS(2, 11);
      }
      return;
    }
    TS(2, 0);
    unsigned int ticket = 0;
    const int par = cta == 0 ? 1 : 0;
    const int q0 = cta == 0 ? 2 * r0 - 2 : 2 * r0 - 1;
    if (elect_one()) {
      asm volatile("cp.async.bulk.prefetch.tensor.4d.L2.global.tile [%0, {%1, %2, %3, %4}];" ::"l"(&P.x), "r"(0), "r"(par), "r"(q0), "r"(b) : "memory");
#pragma unroll
      for (int i = 0; i < 9; i++) { mbar_init(bars + i * 8, 1); mbar_expect(bars + i * 8, 16384); }
      if (ge_cta) { mbar_init(bars + kBarG * 8, 1); mbar_expect(bars + kBarG * 8, 4 * 16384 + 4096); mbar_init(bars + kBarP0 * 8, 8); }
      TS(2, 7);
      asm volatile("fence.mbarrier_init.release.cluster;" ::: "memory");
      fence_async_smem();
      TS(2, 8);
      if (ge_cta) {
        tma_load_3d(sb + kOffG, &P.g, bars + kBarG * 8, 0, b * 8, 0);
#pragma unroll
        for (int i = 0; i < 4; i++) tma_load_3d(sb + (9 + i) * kSlot, &P.wg, bars + kBarG * 8, 0, i * 64, 2 * cta);
      }
#pragma unroll
      for (int u = 0; u < 5; u++)
      {
        tma_load_3d(sb + unit_slot(u) * kSlot, &P.w1, bars + (kBarW + u) * 8, 0, (u % 3) * 256 + (u / 3) * 64, 2 * cta);
        if (u == 0) TS(2, 9);
      }
      TS(2, 10);
    }
    __syncwarp();
    TS(2, 6);
    cluster_sync_relaxed();
    TS(2, 1);
    if (elect_one()) {
#pragma unroll
      for (int p = 0; p < XFIRST; p++)
        tma_load_4d_mc(sb + p * kSlot + cta * 8192, &P.x, bars + (kBarX + p) * 8, p * 64, par, q0, b, (uint16_t)3);
    }
    __syncwarp();
    if (lane == 0) ticket = atomicAdd(&g_cta_count, 1u);
#pragma unroll
    for (int p = XFIRST; p < 4; p++) {
      if (XSTEP == 1 || ((p - XFIRST) & 1) == 0) mbar_wait(bars + (kBarX + p - XFIRST) * 8);
      if (ge_cta && p == 3) mbar_wait(bars + kBarP0 * 8);
      if (elect_one())
        tma_load_4d_mc(sb + p * kSlot + cta * 8192, &P.x, bars + (kBarX + p) * 8, p * 64, par, q0, b, (uint16_t)3);
      __syncwarp();
    }
#pragma unroll
    for (int u = 5; u < 36; u++) {
      if (unit_wait(u) != unit_wait(u - 1)) mbar_wait(bars + (kBarE + unit_wait(u)) * 8);
      if (u == 27) ticket = __shfl_sync(0xffffffffu, ticket, 0);
      if (elect_one()) {
        const uint32_t dst = sb + unit_slot(u) * kSlot, bar = bars + (kBarW + u) * 8;
        if (u < 12) tma_load_3d(dst, &P.w1, bar, 0, (u % 3) * 256 + (u / 3) * 64, 2 * cta);
        else if (u < 24) tma_load_3d(dst, &P.w2, bar, 0, ((u - 12) % 3) * 256 + ((2 * cta + (u - 12) / 3) & 3) * 64, 2 * cta);
        else if (u < 28) tma_load_3d(dst, &P.wf, bar, 0, ((2 * cta + (u - 24)) & 3) * 64, 2 * cta);
        else tma_load_3d(dst, &P.wo, bar, 0, ((u - 28) & 3) * 64, ((u - 28) >> 2) * 2);
        if (u == 27) {
          const unsigned int want = (ticket / kNumCtas + 1u) * 2u;
          const long long t0 = clock64();
          unsigned int v;
          do {
            asm volatile("ld.acquire.gpu.global.u32 %0, [%1];" : "=r"(v) : "l"(&g_ge_flag[b]) : "memory");
          } while ((int)(v - want) < 0 && clock64() - t0 < 4000000ll);
          asm volatile("fence.proxy.async;" ::: "memory");
          bulk_load(sb + kOffGE, reinterpret_cast<const char*>(g_ge) + b * kGEBytes, kGEBytes, bars + kBarFE * 8);
        }
      }
      __syncwarp();
      if (u == 11) TS(2, 2);
      if (u == 23) TS(2, 3);
      if (u == 27) TS(2, 4);
      if (u == 35) TS(2, 5);
    }
  } else {
    asm volatile("setmaxnreg.inc.sync.aligned.u32 232;");
    const int wg = warp >> 2, w = warp & 3;
    const int gq = lane >> 2, q = lane & 3;
    const uint32_t panel = 2 * cta + wg;
    const int ch = panel * 64 + w * 16 + gq;
    const uint32_t dA = desc_lo(sb + wg * 8192, 8192);
    const uint32_t dB = desc_lo(sb, 16);
    const uint32_t dBo = desc_lo(sb + cta * 2 * 8192, 16), dBp = desc_lo(sb + (cta ^ 1) * 2 * 8192, 16);
    const uint32_t dFo = desc_lo(sb + cta * 2 * 4096, 16), dFp = desc_lo(sb + (cta ^ 1) * 2 * 4096, 16);
    if (elect_one()) {
#pragma unroll
      for (int i = 0; i < 6; i++) init_bar(bars, 9 + warp * 6 + i);
      asm volatile("fence.mbarrier_init.release.cluster;" ::: "memory");
    }
    __syncwarp();
    cluster_sync_relaxed();
    if (w == 0) TS(wg, 0);

    if (ge_cta) {
      float ga[4];
      mbar_wait(bars + kBarG * 8);
      wg_fence();
#pragma unroll
      for (int i = 0; i < 4; i++) {
#pragma unroll
        for (int s = 0; s < 4; s++)
          wgmma_ss_n8(ga, desc_at(dA, (9 + i) * kSlot + s * 2048), desc_at(dB, kOffG + i * 1024 + s * 32), (i | s) != 0);
      }
      wg_commit();
      wg_wait<0>();
      if (lane == 0) mbar_arrive(bars + kBarP0 * 8);
      float* gp = g_ge + b * (kGEBytes / 4) + ((ch & 7) >> 1) * (kGEPitch / 4) + (ch >> 4) * 4 + (ch & 1);
      gp[(2 * q) * 4 * (kGEPitch / 4)] = ga[0];
      gp[(2 * q + 1) * 4 * (kGEPitch / 4)] = ga[1];
      gp[(2 * q) * 4 * (kGEPitch / 4) + 2] = ga[2];
      gp[(2 * q + 1) * 4 * (kGEPitch / 4) + 2] = ga[3];
      __threadfence();
      bar_consumers();
      if (threadIdx.x == 0) asm volatile("red.release.gpu.global.add.u32 [%0], 1;" ::"l"(&g_ge_flag[b]) : "memory");
    }

    {
      float acc[32];
#pragma unroll
      for (int u = 0; u < 12; u++) {
        const int p = u / 3, tap = u % 3;
        if (tap == 0) mbar_wait(bars + (kBarX + p) * 8);
        mbar_wait(bars + (kBarW + u) * 8);
        if (u == 0 && w == 0) TS(wg, 1);
        wg_fence();
#pragma unroll
        for (int s = 0; s < 4; s++)
          wgmma_ss_n64(acc, desc_at(dA, unit_slot(u) * kSlot + s * 2048),
                       desc_at(dB, p * kSlot + (tap == 1 ? 8192 : (tap == 2 ? 128 : 0)) + s * 32), (u | s) != 0);
        wg_commit();
        if (u > 0) {
          wg_wait<1>();
          if (lane == 0) mbar_arrive(bars + (kBarE + u - 1) * 8);
        }
      }
      wg_wait<0>();
      if (lane == 0) mbar_arrive(bars + (kBarE + 11) * 8);
      if (w == 0) TS(wg, 2);
      const uint32_t hp = sb + kSlotH * kSlot + panel * 8192;
      const int mi = lane >> 3, l8 = lane & 7;
#pragma unroll
      for (int jb = 0; jb < 8; jb += 2) {
        uint32_t r[4];
#pragma unroll
        for (int t = 0; t < 2; t++) {
          r[2 * t + 0] = pack_bf16(gelu_tanh(acc[4 * (jb + t) + 0]), gelu_tanh(acc[4 * (jb + t) + 1]));
          r[2 * t + 1] = pack_bf16(gelu_tanh(acc[4 * (jb + t) + 2]), gelu_tanh(acc[4 * (jb + t) + 3]));
        }
        const int n = 8 * (jb + (mi >> 1)) + l8;
        const int row = n >> 1, chunk = 2 * w + (mi & 1);
        stsm_x4_trans(hp + (n & 1) * 4096 + row * 128 + ((chunk ^ (row & 7)) << 4), r[0], r[1], r[2], r[3]);
      }
      fence_async_smem();
      __syncwarp();
      if (lane == 0) mbar_arrive(bars + (kBarRH + wg) * 8);
      mbar_wait(bars + kBarRH * 8);
      mbar_wait(bars + (kBarRH + 1) * 8);
      if (w == 0) TS(wg, 3);
    }
    {
      float acc[16];
#pragma unroll
      for (int v = 0; v < 12; v++) {
        const int i = v / 3, tap = v % 3;
        if (v == 6) { mbar_wait_cluster(bars + kBarHX * 8); if (w == 0) TS(wg, 4); }
        mbar_wait(bars + (kBarW + 12 + v) * 8);
        wg_fence();
#pragma unroll
        for (int s = 0; s < 4; s++)
          wgmma_ss_n32(acc, desc_at(dA, unit_slot(12 + v) * kSlot + s * 2048),
                       desc_at(i < 2 ? dBo : dBp, kSlotH * kSlot + (i & 1) * 8192 + (tap == 1 ? 4096 : (tap == 2 ? 128 : 0)) + s * 32), (v | s) != 0);
        wg_commit();
        if (v > 0) {
          wg_wait<1>();
          if (lane == 0) mbar_arrive(bars + (kBarE + 12 + v - 1) * 8);
        }
      }
      wg_wait<0>();
      if (lane == 0) mbar_arrive(bars + (kBarE + 23) * 8);
      if (w == 0) TS(wg, 5);
      const uint32_t fp = sb + kSlotF * kSlot + panel * 4096;
      const int mi = lane >> 3, l8 = lane & 7;
#pragma unroll
      for (int jb = 0; jb < 4; jb += 2) {
        uint32_t r[4];
#pragma unroll
        for (int t = 0; t < 2; t++) {
          r[2 * t + 0] = pack_bf16(gelu_tanh(acc[4 * (jb + t) + 0]), gelu_tanh(acc[4 * (jb + t) + 1]));
          r[2 * t + 1] = pack_bf16(gelu_tanh(acc[4 * (jb + t) + 2]), gelu_tanh(acc[4 * (jb + t) + 3]));
        }
        const int n = 8 * (jb + (mi >> 1)) + l8;
        const int chunk = 2 * w + (mi & 1);
        stsm_x4_trans(fp + n * 128 + ((chunk ^ (n & 7)) << 4), r[0], r[1], r[2], r[3]);
      }
      fence_async_smem();
      __syncwarp();
      if (lane == 0) mbar_arrive(bars + (kBarRF + wg) * 8);
      mbar_wait(bars + kBarRF * 8);
      mbar_wait(bars + (kBarRF + 1) * 8);
      if (w == 0) TS(wg, 6);
    }
    {
      float acc[16];
#pragma unroll
      for (int i = 0; i < 4; i++) {
        if (i == 2) { mbar_wait_cluster(bars + kBarFX * 8); if (w == 0) TS(wg, 7); }
        mbar_wait(bars + (kBarW + 24 + i) * 8);
        wg_fence();
#pragma unroll
        for (int s = 0; s < 4; s++)
          wgmma_ss_n32(acc, desc_at(dA, unit_slot(24 + i) * kSlot + s * 2048),
                       desc_at(i < 2 ? dFo : dFp, kSlotF * kSlot + (i & 1) * 4096 + s * 32), (i | s) != 0);
        wg_commit();
        if (i > 0) {
          wg_wait<1>();
          if (lane == 0) mbar_arrive(bars + (kBarE + 24 + i - 1) * 8);
        }
      }
      wg_wait<0>();
      if (w == 0) TS(wg, 8);
      const uint32_t qk = gq >> 1;
      const uint32_t off0 = qk * 128 + (((2 * w) ^ (2 * qk)) << 4) + (gq & 1) * 8;
      const uint32_t off1 = qk * 128 + (((2 * w + 1) ^ (2 * qk)) << 4) + (gq & 1) * 8;
      const uint32_t own = sb + kSlotFE * kSlot + panel * 4096;
      const uint32_t stg = sb + kSlotH * kSlot + wg * 4096;
#pragma unroll
      for (int jb = 0; jb < 4; jb++) {
        const uint32_t base = (((uint32_t)(jb >> 1) == cta) ? own : stg) + (4 * (jb & 1) + q) * 512;
        sts64(base + off0, acc[4 * jb + 0], acc[4 * jb + 1]);
        sts64(base + off1, acc[4 * jb + 2], acc[4 * jb + 3]);
      }
      fence_async_smem();
      __syncwarp();
      if (lane == 0) { mbar_arrive(bars + (kBarRE + wg) * 8); mbar_arrive(bars + kBarFE * 8); }
      if (w == 0) TS(wg, 9);
    }
    const int rl0 = cta * 16 + wg * 8;
    mbar_wait_cluster(bars + kBarFE * 8);
    asm volatile("barrier.cluster.arrive.relaxed.aligned;" ::: "memory");
    if (wg == 1) asm volatile("bar.sync 4, 256;" ::: "memory");
    if (rl0 < rvalid) {
      if (w == 0) TS(wg, 10);
      const uint32_t fe_t = sb + kSlotFE * kSlot + ((4 * wg + w) * 4 + q) * 128;
      const uint32_t ge_t = sb + kOffGE + lane * kGEPitch;
      const int mi = lane >> 3, l8 = lane & 7;
      const uint32_t st = sb + (16 * w + (mi & 1) * 8 + l8) * 128;
      uint32_t A[64];
      float acc[2][32];
      {
        constexpr int PD = 3;
        float4 fa[PD], fb[PD], gg[PD];
#pragma unroll
        for (int kk = 0; kk < 16 + PD; kk++) {
          if (kk >= PD) {
            const int k = kk - PD, sl = k % PD;
            A[4 * k + 0] = pack_bf16(tanh_fast(fa[sl].x + gg[sl].x), tanh_fast(fa[sl].z + gg[sl].y));
            A[4 * k + 1] = pack_bf16(tanh_fast(fa[sl].y + gg[sl].x), tanh_fast(fa[sl].w + gg[sl].y));
            A[4 * k + 2] = pack_bf16(tanh_fast(fb[sl].x + gg[sl].z), tanh_fast(fb[sl].z + gg[sl].w));
            A[4 * k + 3] = pack_bf16(tanh_fast(fb[sl].y + gg[sl].z), tanh_fast(fb[sl].w + gg[sl].w));
          }
          if (kk < 16) {
            const int sl = kk % PD;
            fa[sl] = lds128(fe_t + (kk >> 2) * 4096 + ((((kk & 3) * 2) ^ (2 * q)) << 4));
            fb[sl] = lds128(fe_t + (kk >> 2) * 4096 + ((((kk & 3) * 2 + 1) ^ (2 * q)) << 4));
            gg[sl] = lds128(ge_t + kk * 16);
          }
        }
      }
      if (wg == 0) asm volatile("bar.arrive 4, 256;" ::: "memory");
      if (w == 0) TS(wg, 15);
#pragma unroll
      for (int kk = 0; kk < 16; kk++) {
        if ((kk & 3) == 0) { mbar_wait(bars + (kBarW + 28 + (kk >> 2)) * 8); wg_fence(); }
        wgmma_rs_n64(acc[0], A[4 * kk], A[4 * kk + 1], A[4 * kk + 2], A[4 * kk + 3],
                     desc_at(dB, unit_slot(28 + (kk >> 2)) * kSlot + (kk & 3) * 2048), kk != 0);
      }
      wg_commit();
      if (w == 0) TS(wg, 11);
#pragma unroll
      for (int j = 0; j < 4; j++) {
        const int jn = j + 1;
        if (jn == 2) {
#pragma unroll
          for (int i = 0; i < 4; i++) mbar_wait(bars + (kBarW + 32 + i) * 8);
        }
        if (j < 3) wg_fence();
        const uint32_t stj = st + (wg ? stage_off(1, j) : stage_off(0, j));
#pragma unroll
        for (int kk = 0; kk < 16; kk++) {
          if (j < 3)
            wgmma_rs_n64(acc[jn & 1], A[4 * kk], A[4 * kk + 1], A[4 * kk + 2], A[4 * kk + 3],
                         desc_at(dB, unit_slot(28 + (jn >> 1) * 4 + (kk >> 2)) * kSlot + (jn & 1) * 8192 + (kk & 3) * 2048), kk != 0);
          if (kk == 1) {
            if (j < 3) { wg_commit(); wg_wait<1>(); } else { wg_wait<0>(); }
          }
          if (kk >= 2 && kk < 10 && (kk & 1) == 0) {
            const int jb = kk - 2;
            const uint32_t r0_ = pack_bf16(acc[j & 1][4 * jb + 0], acc[j & 1][4 * jb + 1]), r1_ = pack_bf16(acc[j & 1][4 * jb + 2], acc[j & 1][4 * jb + 3]);
            const uint32_t r2_ = pack_bf16(acc[j & 1][4 * jb + 4], acc[j & 1][4 * jb + 5]), r3_ = pack_bf16(acc[j & 1][4 * jb + 6], acc[j & 1][4 * jb + 7]);
            stsm_x4(stj + (((jb + (mi >> 1)) ^ l8) << 4), r0_, r1_, r2_, r3_);
          }
          if (kk == 9) {
            fence_async_smem();
            __syncwarp();
            mbar_arrive_pred(bars + (kBarPR + wg * 4 + j) * 8, lane == 0);
          }
        }
        if (j < 3) wg_commit();
        if (j == 0 && w == 0) TS(wg, 12);
        if (j == 2 && w == 0) TS(wg, 13);
      }
      if (w == 0) TS(wg, 14);
    } else if (wg == 0) {
      asm volatile("bar.arrive 4, 256;" ::: "memory");
    }
    asm volatile("barrier.cluster.wait.aligned;" ::: "memory");
  }
}

typedef CUresult (*EncodeFn)(CUtensorMap*, CUtensorMapDataType, cuuint32_t, void*, const cuuint64_t*, const cuuint64_t*,
                             const cuuint32_t*, const cuuint32_t*, CUtensorMapInterleave, CUtensorMapSwizzle,
                             CUtensorMapL2promotion, CUtensorMapFloatOOBfill);

void make_map3(EncodeFn enc, CUtensorMap* tm, const void* ptr, uint64_t rows, uint32_t box_rows, uint32_t box_panels) {
  cuuint64_t gd[3] = {64, rows, 4};
  cuuint64_t gs[2] = {512, 128};
  cuuint32_t bd[3] = {64, box_rows, box_panels};
  cuuint32_t es[3] = {1, 1, 1};
  enc(tm, CU_TENSOR_MAP_DATA_TYPE_BFLOAT16, 3, const_cast<void*>(ptr), gd, gs, bd, es, CU_TENSOR_MAP_INTERLEAVE_NONE,
      CU_TENSOR_MAP_SWIZZLE_128B, CU_TENSOR_MAP_L2_PROMOTION_L2_256B, CU_TENSOR_MAP_FLOAT_OOB_FILL_NONE);
}

}

extern "C" void kernel_launch(void* const* d_in, const int* in_sizes, int n_in, void* d_out, int out_size) {
  static EncodeFn enc = nullptr;
  if (!enc) {
    cudaDriverEntryPointQueryResult qr;
    cudaGetDriverEntryPoint("cuTensorMapEncodeTiled", (void**)&enc, cudaEnableDefault, &qr);
    cudaFuncSetAttribute(rnnt_joint_kernel, cudaFuncAttributeMaxDynamicSharedMemorySize, kSmemBytes);
  }
  Params P;
  {
    cuuint64_t gd[4] = {256, 2, 2000, 2};
    cuuint64_t gs[3] = {512, 1024, 4000ull * 512};
    cuuint32_t bd[4] = {64, 1, 64, 1};
    cuuint32_t es[4] = {1, 1, 1, 1};
    enc(&P.x, CU_TENSOR_MAP_DATA_TYPE_BFLOAT16, 4, d_in[0], gd, gs, bd, es, CU_TENSOR_MAP_INTERLEAVE_NONE,
        CU_TENSOR_MAP_SWIZZLE_128B, XPROMO, CU_TENSOR_MAP_FLOAT_OOB_FILL_NONE);
  }
  make_map3(enc, &P.w1, d_in[1], 768, 64, 2);
  make_map3(enc, &P.w2, d_in[2], 768, 64, 2);
  make_map3(enc, &P.g, d_in[3], 16, 8, 4);
  make_map3(enc, &P.wf, d_in[4], 256, 64, 2);
  make_map3(enc, &P.wg, d_in[5], 256, 64, 2);
  make_map3(enc, &P.wo, d_in[6], 256, 64, 2);
  make_map3(enc, &P.out64, d_out, 16000, 64, 1);
  make_map3(enc, &P.out56, d_out, 16000, 56, 1);
  rnnt_joint_kernel<<<kNumCtas, kThreads, kSmemBytes>>>(P);
}
```

```cpp
#include <cuda_runtime.h>
#include <cuda_bf16.h>
#include <cuda.h>
#include <stdint.h>

#define XPREF 1
#define XFIRST 3
#define XSTEP 1
#define XPROMO CU_TENSOR_MAP_L2_PROMOTION_L2_128B
namespace {

constexpr int kT2 = 1000;
constexpr int kR = 31;
constexpr int kNumCtas = 132;
constexpr int kThreads = 384;
constexpr int kSlot = 16384;

constexpr int kSlotFE = 9, kSlotF = 10, kSlotH = 11;
constexpr int kOffG = 13 * kSlot;
constexpr int kOffGE = kOffG + 4096;
constexpr int kGEPitch = 272;
constexpr int kGEBytes = 32 * kGEPitch;
constexpr int kOffBar = kOffGE + kGEBytes;
constexpr int kBarX = 0;
constexpr int kBarW = 4;
constexpr int kBarE = 40;
constexpr int kBarHX = 67, kBarFX = 68, kBarFE = 69, kBarG = 70, kBarP0 = 71;
constexpr int kBarRH = 72, kBarRF = 74, kBarRE = 76;
constexpr int kBarPR = 78;
constexpr int kNumBars = 86;
constexpr int kSmemBytes = kOffBar + kNumBars * 8 + 1024;

__device__ __align__(128) float g_ge[2 * kGEBytes / 4];
__device__ unsigned int g_ge_flag[2];
__device__ unsigned int g_cta_count;

#define TS(slot_, idx_) do {} while (0)

__device__ __forceinline__ uint32_t smem_u32(const void* p) { return (uint32_t)__cvta_generic_to_shared(p); }
__device__ __forceinline__ void mbar_init(uint32_t a, uint32_t c) { asm volatile("mbarrier.init.shared.b64 [%0], %1;" ::"r"(a), "r"(c) : "memory"); }
__device__ __forceinline__ void mbar_expect(uint32_t a, uint32_t b) { asm volatile("mbarrier.arrive.expect_tx.shared.b64 _, [%0], %1;" ::"r"(a), "r"(b) : "memory"); }
__device__ __forceinline__ void mbar_arrive(uint32_t a) { asm volatile("mbarrier.arrive.shared.b64 _, [%0];" ::"r"(a) : "memory"); }
__device__ __forceinline__ void mbar_arrive_pred(uint32_t a, bool p) {
  asm volatile("{\n.reg .pred q;\nsetp.ne.u32 q, %1, 0;\n@q mbarrier.arrive.shared.b64 _, [%0];\n}\n" ::"r"(a), "r"((uint32_t)p) : "memory");
}
__device__ __forceinline__ bool mbar_try(uint32_t a) {
  uint32_t ok;
  asm volatile("{\n.reg .pred p;\nmbarrier.try_wait.parity.shared.b64 p, [%1], 0;\nselp.u32 %0, 1, 0, p;\n}\n" : "=r"(ok) : "r"(a) : "memory");
  return ok != 0;
}
__device__ __forceinline__ bool mbar_test(uint32_t a) {
  uint32_t ok;
  asm volatile("{\n.reg .pred p;\nmbarrier.test_wait.parity.shared.b64 p, [%1], 0;\nselp.u32 %0, 1, 0, p;\n}\n" : "=r"(ok) : "r"(a) : "memory");
  return ok != 0;
}
__device__ __forceinline__ bool mbar_try_cluster(uint32_t a) {
  uint32_t ok;
  asm volatile("{\n.reg .pred p;\nmbarrier.try_wait.parity.acquire.cluster.shared.b64 p, [%1], 0;\nselp.u32 %0, 1, 0, p;\n}\n" : "=r"(ok) : "r"(a) : "memory");
  return ok != 0;
}
__device__ __forceinline__ void mbar_wait_slow(uint32_t a) {
  const long long t0 = clock64();
  while (!mbar_try(a)) { if (clock64() - t0 > 4000000ll) break; }
}
__device__ __forceinline__ void mbar_wait_cluster_slow(uint32_t a) {
  const long long t0 = clock64();
  while (!mbar_try_cluster(a)) { if (clock64() - t0 > 4000000ll) break; }
}
__device__ __forceinline__ void mbar_wait(uint32_t a) { if (!mbar_try(a)) mbar_wait_slow(a); }
__device__ __forceinline__ void mbar_wait_cluster(uint32_t a) { if (!mbar_try_cluster(a)) mbar_wait_cluster_slow(a); }
__device__ __forceinline__ uint32_t mapa(uint32_t a, uint32_t r) { uint32_t d; asm volatile("mapa.shared::cluster.u32 %0, %1, %2;" : "=r"(d) : "r"(a), "r"(r)); return d; }
__device__ __forceinline__ bool elect_one() { uint32_t p; asm volatile("{\n.reg .pred P;\nelect.sync _|P, 0xffffffff;\nselp.u32 %0, 1, 0, P;\n}\n" : "=r"(p)); return p != 0; }
__device__ __forceinline__ void fence_async_smem() { asm volatile("fence.proxy.async.shared::cta;" ::: "memory"); }
__device__ __forceinline__ void bar_consumers() { asm volatile("bar.sync 1, 256;" ::: "memory"); }
__device__ __forceinline__ void bar_wg(int wg) { asm volatile("bar.sync %0, 128;" ::"r"(2 + wg) : "memory"); }
__device__ __forceinline__ void cluster_sync_relaxed() { asm volatile("barrier.cluster.arrive.relaxed.aligned;\nbarrier.cluster.wait.aligned;" ::: "memory"); }
__device__ __forceinline__ void wg_fence() { asm volatile("wgmma.fence.sync.aligned;" ::: "memory"); }
__device__ __forceinline__ void wg_commit() { asm volatile("wgmma.commit_group.sync.aligned;" ::: "memory"); }
template <int N> __device__ __forceinline__ void wg_wait() { asm volatile("wgmma.wait_group.sync.aligned %0;" ::"n"(N) : "memory"); }

__device__ __forceinline__ void tma_load_3d(uint32_t dst, const CUtensorMap* tm, uint32_t bar, int c0, int c1, int c2) {
  asm volatile("cp.async.bulk.tensor.3d.shared::cluster.global.mbarrier::complete_tx::bytes [%0], [%1, {%3, %4, %5}], [%2];"
               ::"r"(dst), "l"(tm), "r"(bar), "r"(c0), "r"(c1), "r"(c2) : "memory");
}
__device__ __forceinline__ void tma_load_4d_mc(uint32_t dst, const CUtensorMap* tm, uint32_t bar, int c0, int c1, int c2, int c3, uint16_t mask) {
  asm volatile("cp.async.bulk.tensor.4d.shared::cluster.global.mbarrier::complete_tx::bytes.multicast::cluster [%0], [%1, {%3, %4, %5, %6}], [%2], %7;"
               ::"r"(dst), "l"(tm), "r"(bar), "r"(c0), "r"(c1), "r"(c2), "r"(c3), "h"(mask) : "memory");
}
__device__ __forceinline__ void tma_store_3d(const CUtensorMap* tm, uint32_t src, int c0, int c1, int c2) {
  asm volatile("cp.async.bulk.tensor.3d.global.shared::cta.bulk_group [%0, {%2, %3, %4}], [%1];"
               ::"l"(tm), "r"(src), "r"(c0), "r"(c1), "r"(c2) : "memory");
}
__device__ __forceinline__ void bulk_load(uint32_t dst, const void* src, uint32_t bytes, uint32_t bar) {
  asm volatile("cp.async.bulk.shared::cluster.global.mbarrier::complete_tx::bytes [%0], [%1], %2, [%3];"
               ::"r"(dst), "l"(src), "r"(bytes), "r"(bar) : "memory");
}
__device__ __forceinline__ void dsmem_copy(uint32_t dst_remote, uint32_t src, uint32_t bytes, uint32_t bar_remote) {
  asm volatile("cp.async.bulk.shared::cluster.shared::cta.mbarrier::complete_tx::bytes [%0], [%1], %2, [%3];"
               ::"r"(dst_remote), "r"(src), "r"(bytes), "r"(bar_remote) : "memory");
}
__device__ __forceinline__ void stsm_x4_trans(uint32_t addr, uint32_t r0, uint32_t r1, uint32_t r2, uint32_t r3) {
  asm volatile("stmatrix.sync.aligned.m8n8.x4.trans.shared.b16 [%0], {%1, %2, %3, %4};" ::"r"(addr), "r"(r0), "r"(r1), "r"(r2), "r"(r3) : "memory");
}
__device__ __forceinline__ void stsm_x4(uint32_t addr, uint32_t r0, uint32_t r1, uint32_t r2, uint32_t r3) {
  asm volatile("stmatrix.sync.aligned.m8n8.x4.shared.b16 [%0], {%1, %2, %3, %4};" ::"r"(addr), "r"(r0), "r"(r1), "r"(r2), "r"(r3) : "memory");
}
__device__ __forceinline__ float2 lds64(uint32_t a) { float2 v; asm volatile("ld.shared.v2.f32 {%0, %1}, [%2];" : "=f"(v.x), "=f"(v.y) : "r"(a) : "memory"); return v; }
__device__ __forceinline__ float4 lds128(uint32_t a) { float4 v; asm volatile("ld.shared.v4.f32 {%0, %1, %2, %3}, [%4];" : "=f"(v.x), "=f"(v.y), "=f"(v.z), "=f"(v.w) : "r"(a) : "memory"); return v; }
__device__ __forceinline__ void sts64(uint32_t a, float x, float y) { asm volatile("st.shared.v2.f32 [%0], {%1, %2};" ::"r"(a), "f"(x), "f"(y) : "memory"); }
__device__ __forceinline__ float tanh_fast(float x) { float y; asm("tanh.approx.f32 %0, %1;" : "=f"(y) : "f"(x)); return y; }
__device__ __forceinline__ uint32_t tanh2_pack(float lo, float hi) {
  uint32_t r;
  asm volatile("{\n.reg .f32 a, b;\ntanh.approx.f32 a, %1;\ntanh.approx.f32 b, %2;\ncvt.rn.bf16x2.f32 %0, b, a;\n}\n" : "=r"(r) : "f"(lo), "f"(hi));
  return r;
}
__device__ __forceinline__ uint32_t pack_bf16(float lo, float hi) { uint32_t r; asm("cvt.rn.bf16x2.f32 %0, %1, %2;" : "=r"(r) : "f"(hi), "f"(lo)); return r; }
__device__ __forceinline__ float gelu_tanh(float x) {
  const float k0 = 0.7978845608028654f, k1 = 0.7978845608028654f * 0.044715f;
  float u = x * fmaf(x * x, k1, k0);
  float hx = 0.5f * x;
  return fmaf(hx, tanh_fast(u), hx);
}
__device__ __forceinline__ uint64_t make_desc(uint32_t addr, uint32_t lbo, uint32_t sbo) {
  return (uint64_t)((addr & 0x3FFFF) >> 4) | ((uint64_t)(lbo >> 4) << 16) | ((uint64_t)(sbo >> 4) << 32) | ((uint64_t)1 << 62);
}

__device__ __forceinline__ uint32_t desc_lo(uint32_t addr, uint32_t lbo) { return ((addr & 0x3FFFF) >> 4) | ((lbo >> 4) << 16); }
__device__ __forceinline__ uint64_t desc_at(uint32_t lo, uint32_t off) { return ((uint64_t)0x40000040u << 32) | (uint64_t)(lo + (off >> 4)); }

__device__ __forceinline__ void wgmma_ss_n64(float (&d)[32], uint64_t da, uint64_t db, int scale_d) {
  asm volatile("{\n.reg .pred p;\nsetp.ne.b32 p, %34, 0;\n"
    "wgmma.mma_async.sync.aligned.m64n64k16.f32.bf16.bf16 {%0, %1, %2, %3, %4, %5, %6, %7, %8, %9, %10, %11, %12, %13, %14, %15, %16, %17, %18, %19, %20, %21, %22, %23, %24, %25, %26, %27, %28, %29, %30, %31}, %32, %33, p, 1, 1, 1, 0;\n}\n"
    : "+f"(d[0]), "+f"(d[1]), "+f"(d[2]), "+f"(d[3]), "+f"(d[4]), "+f"(d[5]), "+f"(d[6]), "+f"(d[7]), "+f"(d[8]), "+f"(d[9]), "+f"(d[10]), "+f"(d[11]), "+f"(d[12]), "+f"(d[13]), "+f"(d[14]), "+f"(d[15]), "+f"(d[16]), "+f"(d[17]), "+f"(d[18]), "+f"(d[19]), "+f"(d[20]), "+f"(d[21]), "+f"(d[22]), "+f"(d[23]), "+f"(d[24]), "+f"(d[25]), "+f"(d[26]), "+f"(d[27]), "+f"(d[28]), "+f"(d[29]), "+f"(d[30]), "+f"(d[31])
    : "l"(da), "l"(db), "r"(scale_d));
}

__device__ __forceinline__ void wgmma_ss_n32(float (&d)[16], uint64_t da, uint64_t db, int scale_d) {
  asm volatile("{\n.reg .pred p;\nsetp.ne.b32 p, %18, 0;\n"
    "wgmma.mma_async.sync.aligned.m64n32k16.f32.bf16.bf16 {%0, %1, %2, %3, %4, %5, %6, %7, %8, %9, %10, %11, %12, %13, %14, %15}, %16, %17, p, 1, 1, 1, 0;\n}\n"
    : "+f"(d[0]), "+f"(d[1]), "+f"(d[2]), "+f"(d[3]), "+f"(d[4]), "+f"(d[5]), "+f"(d[6]), "+f"(d[7]), "+f"(d[8]), "+f"(d[9]), "+f"(d[10]), "+f"(d[11]), "+f"(d[12]), "+f"(d[13]), "+f"(d[14]), "+f"(d[15])
    : "l"(da), "l"(db), "r"(scale_d));
}

__device__ __forceinline__ void wgmma_ss_n8(float (&d)[4], uint64_t da, uint64_t db, int scale_d) {
  asm volatile("{\n.reg .pred p;\nsetp.ne.b32 p, %6, 0;\n"
    "wgmma.mma_async.sync.aligned.m64n8k16.f32.bf16.bf16 {%0, %1, %2, %3}, %4, %5, p, 1, 1, 1, 0;\n}\n"
    : "+f"(d[0]), "+f"(d[1]), "+f"(d[2]), "+f"(d[3])
    : "l"(da), "l"(db), "r"(scale_d));
}

__device__ __forceinline__ void wgmma_rs_n64(float (&d)[32], uint32_t a0, uint32_t a1, uint32_t a2, uint32_t a3, uint64_t db, int scale_d) {
  asm volatile("{\n.reg .pred p;\nsetp.ne.b32 p, %37, 0;\n"
    "wgmma.mma_async.sync.aligned.m64n64k16.f32.bf16.bf16 {%0, %1, %2, %3, %4, %5, %6, %7, %8, %9, %10, %11, %12, %13, %14, %15, %16, %17, %18, %19, %20, %21, %22, %23, %24, %25, %26, %27, %28, %29, %30, %31}, {%32, %33, %34, %35}, %36, p, 1, 1, 1;\n}\n"
    : "+f"(d[0]), "+f"(d[1]), "+f"(d[2]), "+f"(d[3]), "+f"(d[4]), "+f"(d[5]), "+f"(d[6]), "+f"(d[7]), "+f"(d[8]), "+f"(d[9]), "+f"(d[10]), "+f"(d[11]), "+f"(d[12]), "+f"(d[13]), "+f"(d[14]), "+f"(d[15]), "+f"(d[16]), "+f"(d[17]), "+f"(d[18]), "+f"(d[19]), "+f"(d[20]), "+f"(d[21]), "+f"(d[22]), "+f"(d[23]), "+f"(d[24]), "+f"(d[25]), "+f"(d[26]), "+f"(d[27]), "+f"(d[28]), "+f"(d[29]), "+f"(d[30]), "+f"(d[31])
    : "r"(a0), "r"(a1), "r"(a2), "r"(a3), "l"(db), "r"(scale_d));
}

__host__ __device__ constexpr int unit_slot(int u) {
  constexpr int t[36] = {4, 5, 6, 7, 8, 4, 5, 6, 0, 7, 8, 4,  1, 5, 6, 0, 2, 7, 8, 4, 3, 1, 5, 6,
                         0, 2, 7, 8,  4, 3, 1, 5, 6, 0, 2, 7};
  return t[u];
}
__host__ __device__ constexpr int unit_wait(int u) {
  constexpr int t[36] = {-1, -1, -1, -1, -1, 0, 1, 2, 2, 3, 4, 5,  5, 6, 7, 8, 8, 9, 10, 11, 11, 12, 13, 14,
                         15, 16, 17, 18,  19, 20, 21, 22, 23, 24, 25, 26};
  return t[u];
}

__device__ __forceinline__ uint32_t stage_off(int g, int j) {
  return g == 0 ? (j < 2 ? 8 * kSlot + j * 8192 : 10 * kSlot + (j - 2) * 8192)
                : (j < 2 ? 12 * kSlot + j * 8192 : (j == 2 ? 11 * kSlot + 8192 : 9 * kSlot));
}

struct Params {
  CUtensorMap x, w1, w2, wf, wg, wo, g, out64, out56;
};

__device__ __forceinline__ void init_bar(uint32_t bars, int i) {
  const uint32_t a = bars + i * 8;
  const bool is_e = (i >= kBarE && i < kBarE + 27);
  mbar_init(a, is_e ? 8 : (i == kBarFE ? 9 : 1));
  if (!is_e) {
    uint32_t bytes = 16384;
    if (i == kBarFX) bytes = 8192;
    if (i == kBarFE) bytes = 8192 + kGEBytes;
    mbar_expect(a, bytes);
  }
}

__global__ void __cluster_dims__(2, 1, 1) __launch_bounds__(kThreads, 1)
rnnt_joint_kernel(const __grid_constant__ Params P) {
  extern __shared__ uint8_t smem_raw[];
  const uint32_t sb = (smem_u32(smem_raw) + 1023u) & ~1023u;
  const uint32_t bars = sb + kOffBar;
  const int warp = threadIdx.x >> 5, lane = threadIdx.x & 31;
  uint32_t cta;
  asm volatile("mov.u32 %0, %%cluster_ctarank;" : "=r"(cta));
  const uint32_t peer = cta ^ 1u;
  const int cl = blockIdx.x >> 1;
  const bool ge_cta = cl < 2;
  const int b = ge_cta ? cl : ((cl - 2) >> 5);
  const int r0 = ge_cta ? 32 * kR : ((cl - 2) & 31) * kR;
  const int rvalid = ge_cta ? kT2 - 32 * kR : kR;

  if (warp >= 8) {
    asm volatile("setmaxnreg.dec.sync.aligned.u32 40;");
    if (warp > 8) {
      if (elect_one()) {
#pragma unroll
        for (int i = 0; i < 5; i++) if (57 + (warp - 9) * 5 + i < kBarG) init_bar(bars, 57 + (warp - 9) * 5 + i);
#pragma unroll
        for (int i = 0; i < 5; i++) if (kBarRH + (warp - 9) * 5 + i < kNumBars) mbar_init(bars + (kBarRH + (warp - 9) * 5 + i) * 8, 4);
        asm volatile("fence.mbarrier_init.release.cluster;" ::: "memory");
      }
      __syncwarp();
      cluster_sync_relaxed();
      if (warp > 9) return;
#pragma unroll
      for (int g = 0; g < 2; g++) {
        mbar_wait(bars + (kBarRH + g) * 8);
        if (elect_one()) {
          const uint32_t src = sb + kSlotH * kSlot + (2 * cta + g) * 8192;
          dsmem_copy(mapa(src, peer), src, 8192, mapa(bars + kBarHX * 8, peer));
        }
        __syncwarp();
      }
#pragma unroll
      for (int g = 0; g < 2; g++) {
        mbar_wait(bars + (kBarRF + g) * 8);
        if (elect_one()) {
          const uint32_t src = sb + kSlotF * kSlot + (2 * cta + g) * 4096;
          dsmem_copy(mapa(src, peer), src, 4096, mapa(bars + kBarFX * 8, peer));
        }
        __syncwarp();
      }
#pragma unroll
      for (int g = 0; g < 2; g++) {
        mbar_wait(bars + (kBarRE + g) * 8);
        if (elect_one())
          dsmem_copy(mapa(sb + kSlotFE * kSlot + (2 * cta + g) * 4096, peer), sb + kSlotH * kSlot + g * 4096, 4096, mapa(bars + kBarFE * 8, peer));
        __syncwarp();
      }
      {
        int nxt0 = ((int)cta * 16 < rvalid) ? 0 : 4, nxt1 = ((int)cta * 16 + 8 < rvalid) ? 0 : 4;
        const long long t0 = clock64();
        while ((nxt0 < 4 || nxt1 < 4) && clock64() - t0 < 8000000ll) {
#pragma unroll
          for (int g = 0; g < 2; g++) {
            const int j = g ? nxt1 : nxt0;
            if (j < 4 && mbar_test(bars + (kBarPR + g * 4 + j) * 8)) {
              if (elect_one()) {
                const int rl0 = cta * 16 + g * 8;
                tma_store_3d((rl0 + 8 <= rvalid) ? &P.out64 : &P.out56, sb + stage_off(g, j), 0, (b * kT2 + r0 + rl0) * 8, j);
                asm volatile("cp.async.bulk.commit_group;" ::: "memory");
              }
              __syncwarp();
              if (g) nxt1++; else nxt0++;
            }
          }
        }
        if (elect_one()) asm volatile("cp.async.bulk.wait_group.read 0;" ::: "memory");
        __syncwarp();
        TS(2, 11);
      }
      return;
    }
    TS(2, 0);
    unsigned int ticket = 0;
    const int par = cta == 0 ? 1 : 0;
    const int q0 = cta == 0 ? 2 * r0 - 2 : 2 * r0 - 1;
    if (elect_one()) {
      asm volatile("cp.async.bulk.prefetch.tensor.4d.L2.global.tile [%0, {%1, %2, %3, %4}];" ::"l"(&P.x), "r"(0), "r"(par), "r"(q0), "r"(b) : "memory");
#pragma unroll
      for (int i = 0; i < 9; i++) { mbar_init(bars + i * 8, 1); mbar_expect(bars + i * 8, 16384); }
      if (ge_cta) { mbar_init(bars + kBarG * 8, 1); mbar_expect(bars + kBarG * 8, 4 * 16384 + 4096); mbar_init(bars + kBarP0 * 8, 8); }
      TS(2, 7);
      asm volatile("fence.mbarrier_init.release.cluster;" ::: "memory");
      fence_async_smem();
      TS(2, 8);
      if (ge_cta) {
        tma_load_3d(sb + kOffG, &P.g, bars + kBarG * 8, 0, b * 8, 0);
#pragma unroll
        for (int i = 0; i < 4; i++) tma_load_3d(sb + (9 + i) * kSlot, &P.wg, bars + kBarG * 8, 0, i * 64, 2 * cta);
      }
#pragma unroll
      for (int u = 0; u < 5; u++)
      {
        tma_load_3d(sb + unit_slot(u) * kSlot, &P.w1, bars + (kBarW + u) * 8, 0, (u % 3) * 256 + (u / 3) * 64, 2 * cta);
        if (u == 0) TS(2, 9);
      }
      TS(2, 10);
    }
    __syncwarp();
    TS(2, 6);
    cluster_sync_relaxed();
    TS(2, 1);
    if (elect_one()) {
#pragma unroll
      for (int p = 0; p < XFIRST; p++)
        tma_load_4d_mc(sb + p * kSlot + cta * 8192, &P.x, bars + (kBarX + p) * 8, p * 64, par, q0, b, (uint16_t)3);
    }
    __syncwarp();
    if (lane == 0) ticket = atomicAdd(&g_cta_count, 1u);
#pragma unroll
    for (int p = XFIRST; p < 4; p++) {
      if (XSTEP == 1 || ((p - XFIRST) & 1) == 0) mbar_wait(bars + (kBarX + p - XFIRST) * 8);
      if (ge_cta && p == 3) mbar_wait(bars + kBarP0 * 8);
      if (elect_one())
        tma_load_4d_mc(sb + p * kSlot + cta * 8192, &P.x, bars + (kBarX + p) * 8, p * 64, par, q0, b, (uint16_t)3);
      __syncwarp();
    }
#pragma unroll
    for (int u = 5; u < 36; u++) {
      if (unit_wait(u) != unit_wait(u - 1)) mbar_wait(bars + (kBarE + unit_wait(u)) * 8);
      if (u == 27) ticket = __shfl_sync(0xffffffffu, ticket, 0);
      if (elect_one()) {
        const uint32_t dst = sb + unit_slot(u) * kSlot, bar = bars + (kBarW + u) * 8;
        if (u < 12) tma_load_3d(dst, &P.w1, bar, 0, (u % 3) * 256 + (u / 3) * 64, 2 * cta);
        else if (u < 24) tma_load_3d(dst, &P.w2, bar, 0, ((u - 12) % 3) * 256 + ((2 * cta + (u - 12) / 3) & 3) * 64, 2 * cta);
        else if (u < 28) tma_load_3d(dst, &P.wf, bar, 0, ((2 * cta + (u - 24)) & 3) * 64, 2 * cta);
        else tma_load_3d(dst, &P.wo, bar, 0, ((u - 28) & 3) * 64, ((u - 28) >> 2) * 2);
        if (u == 27) {
          const unsigned int want = (ticket / kNumCtas + 1u) * 2u;
          const long long t0 = clock64();
          unsigned int v;
          do {
            asm volatile("ld.acquire.gpu.global.u32 %0, [%1];" : "=r"(v) : "l"(&g_ge_flag[b]) : "memory");
          } while ((int)(v - want) < 0 && clock64() - t0 < 4000000ll);
          asm volatile("fence.proxy.async;" ::: "memory");
          bulk_load(sb + kOffGE, reinterpret_cast<const char*>(g_ge) + b * kGEBytes, kGEBytes, bars + kBarFE * 8);
        }
      }
      __syncwarp();
      if (u == 11) TS(2, 2);
      if (u == 23) TS(2, 3);
      if (u == 27) TS(2, 4);
      if (u == 35) TS(2, 5);
    }
  } else {
    asm volatile("setmaxnreg.inc.sync.aligned.u32 232;");
    const int wg = warp >> 2, w = warp & 3;
    const int gq = lane >> 2, q = lane & 3;
    const uint32_t panel = 2 * cta + wg;
    const int ch = panel * 64 + w * 16 + gq;
    const uint32_t dA = desc_lo(sb + wg * 8192, 8192);
    const uint32_t dB = desc_lo(sb, 16);
    const uint32_t dBo = desc_lo(sb + cta * 2 * 8192, 16), dBp = desc_lo(sb + (cta ^ 1) * 2 * 8192, 16);
    const uint32_t dFo = desc_lo(sb + cta * 2 * 4096, 16), dFp = desc_lo(sb + (cta ^ 1) * 2 * 4096, 16);
    if (elect_one()) {
#pragma unroll
      for (int i = 0; i < 6; i++) init_bar(bars, 9 + warp * 6 + i);
      asm volatile("fence.mbarrier_init.release.cluster;" ::: "memory");
    }
    __syncwarp();
    cluster_sync_relaxed();
    if (w == 0) TS(wg, 0);

    if (ge_cta) {
      float ga[4];
      mbar_wait(bars + kBarG * 8);
      wg_fence();
#pragma unroll
      for (int i = 0; i < 4; i++) {
#pragma unroll
        for (int s = 0; s < 4; s++)
          wgmma_ss_n8(ga, desc_at(dA, (9 + i) * kSlot + s * 2048), desc_at(dB, kOffG + i * 1024 + s * 32), (i | s) != 0);
      }
      wg_commit();
      wg_wait<0>();
      if (lane == 0) mbar_arrive(bars + kBarP0 * 8);
      float* gp = g_ge + b * (kGEBytes / 4) + ((ch & 7) >> 1) * (kGEPitch / 4) + (ch >> 4) * 4 + (ch & 1);
      gp[(2 * q) * 4 * (kGEPitch / 4)] = ga[0];
      gp[(2 * q + 1) * 4 * (kGEPitch / 4)] = ga[1];
      gp[(2 * q) * 4 * (kGEPitch / 4) + 2] = ga[2];
      gp[(2 * q + 1) * 4 * (kGEPitch / 4) + 2] = ga[3];
      __threadfence();
      bar_consumers();
      if (threadIdx.x == 0) asm volatile("red.release.gpu.global.add.u32 [%0], 1;" ::"l"(&g_ge_flag[b]) : "memory");
    }

    {
      float acc[32];
#pragma unroll
      for (int u = 0; u < 12; u++) {
        const int p = u / 3, tap = u % 3;
        if (tap == 0) mbar_wait(bars + (kBarX + p) * 8);
        mbar_wait(bars + (kBarW + u) * 8);
        if (u == 0 && w == 0) TS(wg, 1);
        wg_fence();
#pragma unroll
        for (int s = 0; s < 4; s++)
          wgmma_ss_n64(acc, desc_at(dA, unit_slot(u) * kSlot + s * 2048),
                       desc_at(dB, p * kSlot + (tap == 1 ? 8192 : (tap == 2 ? 128 : 0)) + s * 32), (u | s) != 0);
        wg_commit();
        if (u > 0) {
          wg_wait<1>();
          if (lane == 0) mbar_arrive(bars + (kBarE + u - 1) * 8);
        }
      }
      wg_wait<0>();
      if (lane == 0) mbar_arrive(bars + (kBarE + 11) * 8);
      if (w == 0) TS(wg, 2);
      const uint32_t hp = sb + kSlotH * kSlot + panel * 8192;
      const int mi = lane >> 3, l8 = lane & 7;
#pragma unroll
      for (int jb = 0; jb < 8; jb += 2) {
        uint32_t r[4];
#pragma unroll
        for (int t = 0; t < 2; t++) {
          r[2 * t + 0] = pack_bf16(gelu_tanh(acc[4 * (jb + t) + 0]), gelu_tanh(acc[4 * (jb + t) + 1]));
          r[2 * t + 1] = pack_bf16(gelu_tanh(acc[4 * (jb + t) + 2]), gelu_tanh(acc[4 * (jb + t) + 3]));
        }
        const int n = 8 * (jb + (mi >> 1)) + l8;
        const int row = n >> 1, chunk = 2 * w + (mi & 1);
        stsm_x4_trans(hp + (n & 1) * 4096 + row * 128 + ((chunk ^ (row & 7)) << 4), r[0], r[1], r[2], r[3]);
      }
      fence_async_smem();
      __syncwarp();
      if (lane == 0) mbar_arrive(bars + (kBarRH + wg) * 8);
      mbar_wait(bars + kBarRH * 8);
      mbar_wait(bars + (kBarRH + 1) * 8);
      if (w == 0) TS(wg, 3);
    }
    {
      float acc[16];
#pragma unroll
      for (int v = 0; v < 12; v++) {
        const int i = v / 3, tap = v % 3;
        if (v == 6) { mbar_wait_cluster(bars + kBarHX * 8); if (w == 0) TS(wg, 4); }
        mbar_wait(bars + (kBarW + 12 + v) * 8);
        wg_fence();
#pragma unroll
        for (int s = 0; s < 4; s++)
          wgmma_ss_n32(acc, desc_at(dA, unit_slot(12 + v) * kSlot + s * 2048),
                       desc_at(i < 2 ? dBo : dBp, kSlotH * kSlot + (i & 1) * 8192 + (tap == 1 ? 4096 : (tap == 2 ? 128 : 0)) + s * 32), (v | s) != 0);
        wg_commit();
        if (v > 0) {
          wg_wait<1>();
          if (lane == 0) mbar_arrive(bars + (kBarE + 12 + v - 1) * 8);
        }
      }
      wg_wait<0>();
      if (lane == 0) mbar_arrive(bars + (kBarE + 23) * 8);
      if (w == 0) TS(wg, 5);
      const uint32_t fp = sb + kSlotF * kSlot + panel * 4096;
      const int mi = lane >> 3, l8 = lane & 7;
#pragma unroll
      for (int jb = 0; jb < 4; jb += 2) {
        uint32_t r[4];
#pragma unroll
        for (int t = 0; t < 2; t++) {
          r[2 * t + 0] = pack_bf16(gelu_tanh(acc[4 * (jb + t) + 0]), gelu_tanh(acc[4 * (jb + t) + 1]));
          r[2 * t + 1] = pack_bf16(gelu_tanh(acc[4 * (jb + t) + 2]), gelu_tanh(acc[4 * (jb + t) + 3]));
        }
        const int n = 8 * (jb + (mi >> 1)) + l8;
        const int chunk = 2 * w + (mi & 1);
        stsm_x4_trans(fp + n * 128 + ((chunk ^ (n & 7)) << 4), r[0], r[1], r[2], r[3]);
      }
      fence_async_smem();
      __syncwarp();
      if (lane == 0) mbar_arrive(bars + (kBarRF + wg) * 8);
      mbar_wait(bars + kBarRF * 8);
      mbar_wait(bars + (kBarRF + 1) * 8);
      if (w == 0) TS(wg, 6);
    }
    {
      float acc[16];
#pragma unroll
      for (int i = 0; i < 4; i++) {
        if (i == 2) { mbar_wait_cluster(bars + kBarFX * 8); if (w == 0) TS(wg, 7); }
        mbar_wait(bars + (kBarW + 24 + i) * 8);
        wg_fence();
#pragma unroll
        for (int s = 0; s < 4; s++)
          wgmma_ss_n32(acc, desc_at(dA, unit_slot(24 + i) * kSlot + s * 2048),
                       desc_at(i < 2 ? dFo : dFp, kSlotF * kSlot + (i & 1) * 4096 + s * 32), (i | s) != 0);
        wg_commit();
        if (i > 0) {
          wg_wait<1>();
          if (lane == 0) mbar_arrive(bars + (kBarE + 24 + i - 1) * 8);
        }
      }
      wg_wait<0>();
      if (w == 0) TS(wg, 8);
      const uint32_t qk = gq >> 1;
      const uint32_t off0 = qk * 128 + (((2 * w) ^ (2 * qk)) << 4) + (gq & 1) * 8;
      const uint32_t off1 = qk * 128 + (((2 * w + 1) ^ (2 * qk)) << 4) + (gq & 1) * 8;
      const uint32_t own = sb + kSlotFE * kSlot + panel * 4096;
      const uint32_t stg = sb + kSlotH * kSlot + wg * 4096;
#pragma unroll
      for (int jb = 0; jb < 4; jb++) {
        const uint32_t base = (((uint32_t)(jb >> 1) == cta) ? own : stg) + (4 * (jb & 1) + q) * 512;
        sts64(base + off0, acc[4 * jb + 0], acc[4 * jb + 1]);
        sts64(base + off1, acc[4 * jb + 2], acc[4 * jb + 3]);
      }
      fence_async_smem();
      __syncwarp();
      if (lane == 0) { mbar_arrive(bars + (kBarRE + wg) * 8); mbar_arrive(bars + kBarFE * 8); }
      if (w == 0) TS(wg, 9);
    }
    const int rl0 = cta * 16 + wg * 8;
    mbar_wait_cluster(bars + kBarFE * 8);
    asm volatile("barrier.cluster.arrive.relaxed.aligned;" ::: "memory");
    if (wg == 1) asm volatile("bar.sync 4, 256;" ::: "memory");
    if (rl0 < rvalid) {
      if (w == 0) TS(wg, 10);
      const uint32_t fe_t = sb + kSlotFE * kSlot + ((4 * wg + w) * 4 + q) * 128;
      const uint32_t ge_t = sb + kOffGE + lane * kGEPitch;
      const int mi = lane >> 3, l8 = lane & 7;
      const uint32_t st = sb + (16 * w + (mi & 1) * 8 + l8) * 128;
      uint32_t A[64];
      float acc[2][32];
      {
        constexpr int PD = 3;
        float4 fa[PD], fb[PD], gg[PD];
#pragma unroll
        for (int kk = 0; kk < 16 + PD; kk++) {
          if (kk >= PD) {
            const int k = kk - PD, sl = k % PD;
            A[4 * k + 0] = tanh2_pack(fa[sl].x + gg[sl].x, fa[sl].z + gg[sl].y);
            A[4 * k + 1] = tanh2_pack(fa[sl].y + gg[sl].x, fa[sl].w + gg[sl].y);
            A[4 * k + 2] = tanh2_pack(fb[sl].x + gg[sl].z, fb[sl].z + gg[sl].w);
            A[4 * k + 3] = tanh2_pack(fb[sl].y + gg[sl].z, fb[sl].w + gg[sl].w);
          }
          if (kk < 16) {
            const int sl = kk % PD;
            fa[sl] = lds128(fe_t + (kk >> 2) * 4096 + ((((kk & 3) * 2) ^ (2 * q)) << 4));
            fb[sl] = lds128(fe_t + (kk >> 2) * 4096 + ((((kk & 3) * 2 + 1) ^ (2 * q)) << 4));
            gg[sl] = lds128(ge_t + kk * 16);
          }
        }
      }
      if (wg == 0) asm volatile("bar.arrive 4, 256;" ::: "memory");
      if (w == 0) TS(wg, 15);
#pragma unroll
      for (int kk = 0; kk < 16; kk++) {
        if ((kk & 3) == 0) { mbar_wait(bars + (kBarW + 28 + (kk >> 2)) * 8); wg_fence(); }
        wgmma_rs_n64(acc[0], A[4 * kk], A[4 * kk + 1], A[4 * kk + 2], A[4 * kk + 3],
                     desc_at(dB, unit_slot(28 + (kk >> 2)) * kSlot + (kk & 3) * 2048), kk != 0);
      }
      wg_commit();
      if (w == 0) TS(wg, 11);
#pragma unroll
      for (int j = 0; j < 4; j++) {
        const int jn = j + 1;
        if (jn == 2) {
#pragma unroll
          for (int i = 0; i < 4; i++) mbar_wait(bars + (kBarW + 32 + i) * 8);
        }
        if (j < 3) wg_fence();
        const uint32_t stj = st + (wg ? stage_off(1, j) : stage_off(0, j));
#pragma unroll
        for (int kk = 0; kk < 16; kk++) {
          if (j < 3)
            wgmma_rs_n64(acc[jn & 1], A[4 * kk], A[4 * kk + 1], A[4 * kk + 2], A[4 * kk + 3],
                         desc_at(dB, unit_slot(28 + (jn >> 1) * 4 + (kk >> 2)) * kSlot + (jn & 1) * 8192 + (kk & 3) * 2048), kk != 0);
          if (kk == 1) {
            if (j < 3) { wg_commit(); wg_wait<1>(); } else { wg_wait<0>(); }
          }
          if (kk >= 2 && kk < 10 && (kk & 1) == 0) {
            const int jb = kk - 2;
            const uint32_t r0_ = pack_bf16(acc[j & 1][4 * jb + 0], acc[j & 1][4 * jb + 1]), r1_ = pack_bf16(acc[j & 1][4 * jb + 2], acc[j & 1][4 * jb + 3]);
            const uint32_t r2_ = pack_bf16(acc[j & 1][4 * jb + 4], acc[j & 1][4 * jb + 5]), r3_ = pack_bf16(acc[j & 1][4 * jb + 6], acc[j & 1][4 * jb + 7]);
            stsm_x4(stj + (((jb + (mi >> 1)) ^ l8) << 4), r0_, r1_, r2_, r3_);
          }
          if (kk == 9) {
            fence_async_smem();
            __syncwarp();
            mbar_arrive_pred(bars + (kBarPR + wg * 4 + j) * 8, lane == 0);
          }
        }
        if (j < 3) wg_commit();
        if (j == 0 && w == 0) TS(wg, 12);
        if (j == 2 && w == 0) TS(wg, 13);
      }
      if (w == 0) TS(wg, 14);
    } else if (wg == 0) {
      asm volatile("bar.arrive 4, 256;" ::: "memory");
    }
    asm volatile("barrier.cluster.wait.aligned;" ::: "memory");
  }
}

typedef CUresult (*EncodeFn)(CUtensorMap*, CUtensorMapDataType, cuuint32_t, void*, const cuuint64_t*, const cuuint64_t*,
                             const cuuint32_t*, const cuuint32_t*, CUtensorMapInterleave, CUtensorMapSwizzle,
                             CUtensorMapL2promotion, CUtensorMapFloatOOBfill);

void make_map3(EncodeFn enc, CUtensorMap* tm, const void* ptr, uint64_t rows, uint32_t box_rows, uint32_t box_panels) {
  cuuint64_t gd[3] = {64, rows, 4};
  cuuint64_t gs[2] = {512, 128};
  cuuint32_t bd[3] = {64, box_rows, box_panels};
  cuuint32_t es[3] = {1, 1, 1};
  enc(tm, CU_TENSOR_MAP_DATA_TYPE_BFLOAT16, 3, const_cast<void*>(ptr), gd, gs, bd, es, CU_TENSOR_MAP_INTERLEAVE_NONE,
      CU_TENSOR_MAP_SWIZZLE_128B, CU_TENSOR_MAP_L2_PROMOTION_L2_256B, CU_TENSOR_MAP_FLOAT_OOB_FILL_NONE);
}

}

extern "C" void kernel_launch(void* const* d_in, const int* in_sizes, int n_in, void* d_out, int out_size) {
  static EncodeFn enc = nullptr;
  if (!enc) {
    cudaDriverEntryPointQueryResult qr;
    cudaGetDriverEntryPoint("cuTensorMapEncodeTiled", (void**)&enc, cudaEnableDefault, &qr);
    cudaFuncSetAttribute(rnnt_joint_kernel, cudaFuncAttributeMaxDynamicSharedMemorySize, kSmemBytes);
  }
  Params P;
  {
    cuuint64_t gd[4] = {256, 2, 2000, 2};
    cuuint64_t gs[3] = {512, 1024, 4000ull * 512};
    cuuint32_t bd[4] = {64, 1, 64, 1};
    cuuint32_t es[4] = {1, 1, 1, 1};
    enc(&P.x, CU_TENSOR_MAP_DATA_TYPE_BFLOAT16, 4, d_in[0], gd, gs, bd, es, CU_TENSOR_MAP_INTERLEAVE_NONE,
        CU_TENSOR_MAP_SWIZZLE_128B, XPROMO, CU_TENSOR_MAP_FLOAT_OOB_FILL_NONE);
  }
  make_map3(enc, &P.w1, d_in[1], 768, 64, 2);
  make_map3(enc, &P.w2, d_in[2], 768, 64, 2);
  make_map3(enc, &P.g, d_in[3], 16, 8, 4);
  make_map3(enc, &P.wf, d_in[4], 256, 64, 2);
  make_map3(enc, &P.wg, d_in[5], 256, 64, 2);
  make_map3(enc, &P.wo, d_in[6], 256, 64, 2);
  make_map3(enc, &P.out64, d_out, 16000, 64, 1);
  make_map3(enc, &P.out56, d_out, 16000, 56, 1);
  rnnt_joint_kernel<<<kNumCtas, kThreads, kSmemBytes>>>(P);
}
```

```cpp
#include <cuda_runtime.h>
#include <cuda_bf16.h>
#include <cuda.h>
#include <stdint.h>

#define ARRK 3
#define XPREF 1
#define XFIRST 3
#define XSTEP 1
#define XPROMO CU_TENSOR_MAP_L2_PROMOTION_L2_128B
namespace {

constexpr int kT2 = 1000;
constexpr int kR = 31;
constexpr int kNumCtas = 132;
constexpr int kThreads = 384;
constexpr int kSlot = 16384;

constexpr int kSlotFE = 9, kSlotF = 10, kSlotH = 11;
constexpr int kOffG = 13 * kSlot;
constexpr int kOffGE = kOffG + 4096;
constexpr int kGEPitch = 272;
constexpr int kGEBytes = 32 * kGEPitch;
constexpr int kOffBar = kOffGE + kGEBytes;
constexpr int kBarX = 0;
constexpr int kBarW = 4;
constexpr int kBarE = 40;
constexpr int kBarHX = 67, kBarFX = 68, kBarFE = 69, kBarG = 70, kBarP0 = 71;
constexpr int kBarRH = 72, kBarRF = 74, kBarRE = 76;
constexpr int kBarPR = 78;
constexpr int kNumBars = 86;
constexpr int kSmemBytes = kOffBar + kNumBars * 8 + 1024;

__device__ __align__(128) float g_ge[2 * kGEBytes / 4];
__device__ unsigned int g_ge_flag[2];
__device__ unsigned int g_cta_count;

#define TS(slot_, idx_) do {} while (0)
#define GT(idx_) do {} while (0)

__device__ __forceinline__ uint32_t smem_u32(const void* p) { return (uint32_t)__cvta_generic_to_shared(p); }
__device__ __forceinline__ void mbar_init(uint32_t a, uint32_t c) { asm volatile("mbarrier.init.shared.b64 [%0], %1;" ::"r"(a), "r"(c) : "memory"); }
__device__ __forceinline__ void mbar_expect(uint32_t a, uint32_t b) { asm volatile("mbarrier.arrive.expect_tx.shared.b64 _, [%0], %1;" ::"r"(a), "r"(b) : "memory"); }
__device__ __forceinline__ void mbar_arrive(uint32_t a) { asm volatile("mbarrier.arrive.shared.b64 _, [%0];" ::"r"(a) : "memory"); }
__device__ __forceinline__ void mbar_arrive_pred(uint32_t a, bool p) {
  asm volatile("{\n.reg .pred q;\nsetp.ne.u32 q, %1, 0;\n@q mbarrier.arrive.shared.b64 _, [%0];\n}\n" ::"r"(a), "r"((uint32_t)p) : "memory");
}
__device__ __forceinline__ void bar_arrive_pred(bool p) {
  asm volatile("{\n.reg .pred q;\nsetp.ne.u32 q, %0, 0;\n@q bar.arrive 4, 256;\n}\n" ::"r"((uint32_t)p) : "memory");
}
__device__ __forceinline__ bool mbar_try(uint32_t a) {
  uint32_t ok;
  asm volatile("{\n.reg .pred p;\nmbarrier.try_wait.parity.shared.b64 p, [%1], 0;\nselp.u32 %0, 1, 0, p;\n}\n" : "=r"(ok) : "r"(a) : "memory");
  return ok != 0;
}
__device__ __forceinline__ bool mbar_test(uint32_t a) {
  uint32_t ok;
  asm volatile("{\n.reg .pred p;\nmbarrier.test_wait.parity.shared.b64 p, [%1], 0;\nselp.u32 %0, 1, 0, p;\n}\n" : "=r"(ok) : "r"(a) : "memory");
  return ok != 0;
}
__device__ __forceinline__ bool mbar_try_cluster(uint32_t a) {
  uint32_t ok;
  asm volatile("{\n.reg .pred p;\nmbarrier.try_wait.parity.acquire.cluster.shared.b64 p, [%1], 0;\nselp.u32 %0, 1, 0, p;\n}\n" : "=r"(ok) : "r"(a) : "memory");
  return ok != 0;
}
__device__ __forceinline__ void mbar_wait_slow(uint32_t a) {
  const long long t0 = clock64();
  while (!mbar_try(a)) { if (clock64() - t0 > 4000000ll) break; }
}
__device__ __forceinline__ void mbar_wait_cluster_slow(uint32_t a) {
  const long long t0 = clock64();
  while (!mbar_try_cluster(a)) { if (clock64() - t0 > 4000000ll) break; }
}
__device__ __forceinline__ void mbar_wait(uint32_t a) { if (!mbar_try(a)) mbar_wait_slow(a); }
__device__ __forceinline__ void mbar_wait_cluster(uint32_t a) { if (!mbar_try_cluster(a)) mbar_wait_cluster_slow(a); }
__device__ __forceinline__ uint32_t mapa(uint32_t a, uint32_t r) { uint32_t d; asm volatile("mapa.shared::cluster.u32 %0, %1, %2;" : "=r"(d) : "r"(a), "r"(r)); return d; }
__device__ __forceinline__ bool elect_one() { uint32_t p; asm volatile("{\n.reg .pred P;\nelect.sync _|P, 0xffffffff;\nselp.u32 %0, 1, 0, P;\n}\n" : "=r"(p)); return p != 0; }
__device__ __forceinline__ void fence_async_smem() { asm volatile("fence.proxy.async.shared::cta;" ::: "memory"); }
__device__ __forceinline__ void bar_consumers() { asm volatile("bar.sync 1, 256;" ::: "memory"); }
__device__ __forceinline__ void bar_wg(int wg) { asm volatile("bar.sync %0, 128;" ::"r"(2 + wg) : "memory"); }
__device__ __forceinline__ void cluster_sync_relaxed() { asm volatile("barrier.cluster.arrive.relaxed.aligned;\nbarrier.cluster.wait.aligned;" ::: "memory"); }
__device__ __forceinline__ void wg_fence() { asm volatile("wgmma.fence.sync.aligned;" ::: "memory"); }
__device__ __forceinline__ void wg_commit() { asm volatile("wgmma.commit_group.sync.aligned;" ::: "memory"); }
template <int N> __device__ __forceinline__ void wg_wait() { asm volatile("wgmma.wait_group.sync.aligned %0;" ::"n"(N) : "memory"); }

__device__ __forceinline__ void tma_load_3d(uint32_t dst, const CUtensorMap* tm, uint32_t bar, int c0, int c1, int c2) {
  asm volatile("cp.async.bulk.tensor.3d.shared::cluster.global.mbarrier::complete_tx::bytes [%0], [%1, {%3, %4, %5}], [%2];"
               ::"r"(dst), "l"(tm), "r"(bar), "r"(c0), "r"(c1), "r"(c2) : "memory");
}
__device__ __forceinline__ void tma_load_4d(uint32_t dst, const CUtensorMap* tm, uint32_t bar, int c0, int c1, int c2, int c3) {
  asm volatile("cp.async.bulk.tensor.4d.shared::cluster.global.mbarrier::complete_tx::bytes [%0], [%1, {%3, %4, %5, %6}], [%2];"
               ::"r"(dst), "l"(tm), "r"(bar), "r"(c0), "r"(c1), "r"(c2), "r"(c3) : "memory");
}
__device__ __forceinline__ void tma_load_4d_mc(uint32_t dst, const CUtensorMap* tm, uint32_t bar, int c0, int c1, int c2, int c3, uint16_t mask) {
  asm volatile("cp.async.bulk.tensor.4d.shared::cluster.global.mbarrier::complete_tx::bytes.multicast::cluster [%0], [%1, {%3, %4, %5, %6}], [%2], %7;"
               ::"r"(dst), "l"(tm), "r"(bar), "r"(c0), "r"(c1), "r"(c2), "r"(c3), "h"(mask) : "memory");
}
__device__ __forceinline__ void tma_store_3d(const CUtensorMap* tm, uint32_t src, int c0, int c1, int c2) {
  asm volatile("cp.async.bulk.tensor.3d.global.shared::cta.bulk_group [%0, {%2, %3, %4}], [%1];"
               ::"l"(tm), "r"(src), "r"(c0), "r"(c1), "r"(c2) : "memory");
}
__device__ __forceinline__ void bulk_load(uint32_t dst, const void* src, uint32_t bytes, uint32_t bar) {
  asm volatile("cp.async.bulk.shared::cluster.global.mbarrier::complete_tx::bytes [%0], [%1], %2, [%3];"
               ::"r"(dst), "l"(src), "r"(bytes), "r"(bar) : "memory");
}
__device__ __forceinline__ void dsmem_copy(uint32_t dst_remote, uint32_t src, uint32_t bytes, uint32_t bar_remote) {
  asm volatile("cp.async.bulk.shared::cluster.shared::cta.mbarrier::complete_tx::bytes [%0], [%1], %2, [%3];"
               ::"r"(dst_remote), "r"(src), "r"(bytes), "r"(bar_remote) : "memory");
}
__device__ __forceinline__ void stsm_x4_trans(uint32_t addr, uint32_t r0, uint32_t r1, uint32_t r2, uint32_t r3) {
  asm volatile("stmatrix.sync.aligned.m8n8.x4.trans.shared.b16 [%0], {%1, %2, %3, %4};" ::"r"(addr), "r"(r0), "r"(r1), "r"(r2), "r"(r3) : "memory");
}
__device__ __forceinline__ void stsm_x4(uint32_t addr, uint32_t r0, uint32_t r1, uint32_t r2, uint32_t r3) {
  asm volatile("stmatrix.sync.aligned.m8n8.x4.shared.b16 [%0], {%1, %2, %3, %4};" ::"r"(addr), "r"(r0), "r"(r1), "r"(r2), "r"(r3) : "memory");
}
__device__ __forceinline__ float2 lds64(uint32_t a) { float2 v; asm volatile("ld.shared.v2.f32 {%0, %1}, [%2];" : "=f"(v.x), "=f"(v.y) : "r"(a) : "memory"); return v; }
__device__ __forceinline__ float4 lds128(uint32_t a) { float4 v; asm volatile("ld.shared.v4.f32 {%0, %1, %2, %3}, [%4];" : "=f"(v.x), "=f"(v.y), "=f"(v.z), "=f"(v.w) : "r"(a) : "memory"); return v; }
__device__ __forceinline__ void sts64(uint32_t a, float x, float y) { asm volatile("st.shared.v2.f32 [%0], {%1, %2};" ::"r"(a), "f"(x), "f"(y) : "memory"); }
__device__ __forceinline__ float tanh_fast(float x) { float y; asm("tanh.approx.f32 %0, %1;" : "=f"(y) : "f"(x)); return y; }
__device__ __forceinline__ uint32_t tanh2_pack(float lo, float hi) {
  uint32_t r;
  asm volatile("{\n.reg .f32 a, b;\ntanh.approx.f32 a, %1;\ntanh.approx.f32 b, %2;\ncvt.rn.bf16x2.f32 %0, b, a;\n}\n" : "=r"(r) : "f"(lo), "f"(hi));
  return r;
}
__device__ __forceinline__ uint32_t pack_bf16(float lo, float hi) { uint32_t r; asm("cvt.rn.bf16x2.f32 %0, %1, %2;" : "=r"(r) : "f"(hi), "f"(lo)); return r; }
__device__ __forceinline__ float gelu_tanh(float x) {
  const float k0 = 0.7978845608028654f, k1 = 0.7978845608028654f * 0.044715f;
  float u = x * fmaf(x * x, k1, k0);
  float hx = 0.5f * x;
  return fmaf(hx, tanh_fast(u), hx);
}
__device__ __forceinline__ uint64_t make_desc(uint32_t addr, uint32_t lbo, uint32_t sbo) {
  return (uint64_t)((addr & 0x3FFFF) >> 4) | ((uint64_t)(lbo >> 4) << 16) | ((uint64_t)(sbo >> 4) << 32) | ((uint64_t)1 << 62);
}

__device__ __forceinline__ uint32_t desc_lo(uint32_t addr, uint32_t lbo) { return ((addr & 0x3FFFF) >> 4) | ((lbo >> 4) << 16); }
__device__ __forceinline__ uint64_t desc_at(uint32_t lo, uint32_t off) { return ((uint64_t)0x40000040u << 32) | (uint64_t)(lo + (off >> 4)); }

__device__ __forceinline__ void wgmma_ss_n64(float (&d)[32], uint64_t da, uint64_t db, int scale_d) {
  asm volatile("{\n.reg .pred p;\nsetp.ne.b32 p, %34, 0;\n"
    "wgmma.mma_async.sync.aligned.m64n64k16.f32.bf16.bf16 {%0, %1, %2, %3, %4, %5, %6, %7, %8, %9, %10, %11, %12, %13, %14, %15, %16, %17, %18, %19, %20, %21, %22, %23, %24, %25, %26, %27, %28, %29, %30, %31}, %32, %33, p, 1, 1, 1, 0;\n}\n"
    : "+f"(d[0]), "+f"(d[1]), "+f"(d[2]), "+f"(d[3]), "+f"(d[4]), "+f"(d[5]), "+f"(d[6]), "+f"(d[7]), "+f"(d[8]), "+f"(d[9]), "+f"(d[10]), "+f"(d[11]), "+f"(d[12]), "+f"(d[13]), "+f"(d[14]), "+f"(d[15]), "+f"(d[16]), "+f"(d[17]), "+f"(d[18]), "+f"(d[19]), "+f"(d[20]), "+f"(d[21]), "+f"(d[22]), "+f"(d[23]), "+f"(d[24]), "+f"(d[25]), "+f"(d[26]), "+f"(d[27]), "+f"(d[28]), "+f"(d[29]), "+f"(d[30]), "+f"(d[31])
    : "l"(da), "l"(db), "r"(scale_d));
}

__device__ __forceinline__ void wgmma_ss_n32(float (&d)[16], uint64_t da, uint64_t db, int scale_d) {
  asm volatile("{\n.reg .pred p;\nsetp.ne.b32 p, %18, 0;\n"
    "wgmma.mma_async.sync.aligned.m64n32k16.f32.bf16.bf16 {%0, %1, %2, %3, %4, %5, %6, %7, %8, %9, %10, %11, %12, %13, %14, %15}, %16, %17, p, 1, 1, 1, 0;\n}\n"
    : "+f"(d[0]), "+f"(d[1]), "+f"(d[2]), "+f"(d[3]), "+f"(d[4]), "+f"(d[5]), "+f"(d[6]), "+f"(d[7]), "+f"(d[8]), "+f"(d[9]), "+f"(d[10]), "+f"(d[11]), "+f"(d[12]), "+f"(d[13]), "+f"(d[14]), "+f"(d[15])
    : "l"(da), "l"(db), "r"(scale_d));
}

__device__ __forceinline__ void wgmma_ss_n8(float (&d)[4], uint64_t da, uint64_t db, int scale_d) {
  asm volatile("{\n.reg .pred p;\nsetp.ne.b32 p, %6, 0;\n"
    "wgmma.mma_async.sync.aligned.m64n8k16.f32.bf16.bf16 {%0, %1, %2, %3}, %4, %5, p, 1, 1, 1, 0;\n}\n"
    : "+f"(d[0]), "+f"(d[1]), "+f"(d[2]), "+f"(d[3])
    : "l"(da), "l"(db), "r"(scale_d));
}

__device__ __forceinline__ void wgmma_rs_n64(float (&d)[32], uint32_t a0, uint32_t a1, uint32_t a2, uint32_t a3, uint64_t db, int scale_d) {
  asm volatile("{\n.reg .pred p;\nsetp.ne.b32 p, %37, 0;\n"
    "wgmma.mma_async.sync.aligned.m64n64k16.f32.bf16.bf16 {%0, %1, %2, %3, %4, %5, %6, %7, %8, %9, %10, %11, %12, %13, %14, %15, %16, %17, %18, %19, %20, %21, %22, %23, %24, %25, %26, %27, %28, %29, %30, %31}, {%32, %33, %34, %35}, %36, p, 1, 1, 1;\n}\n"
    : "+f"(d[0]), "+f"(d[1]), "+f"(d[2]), "+f"(d[3]), "+f"(d[4]), "+f"(d[5]), "+f"(d[6]), "+f"(d[7]), "+f"(d[8]), "+f"(d[9]), "+f"(d[10]), "+f"(d[11]), "+f"(d[12]), "+f"(d[13]), "+f"(d[14]), "+f"(d[15]), "+f"(d[16]), "+f"(d[17]), "+f"(d[18]), "+f"(d[19]), "+f"(d[20]), "+f"(d[21]), "+f"(d[22]), "+f"(d[23]), "+f"(d[24]), "+f"(d[25]), "+f"(d[26]), "+f"(d[27]), "+f"(d[28]), "+f"(d[29]), "+f"(d[30]), "+f"(d[31])
    : "r"(a0), "r"(a1), "r"(a2), "r"(a3), "l"(db), "r"(scale_d));
}

__host__ __device__ constexpr int unit_slot(int u) {
  constexpr int t[36] = {4, 5, 6, 7, 8, 4, 5, 6, 0, 7, 8, 4,  1, 5, 6, 0, 2, 7, 8, 4, 3, 1, 5, 6,
                         0, 2, 7, 8,  4, 3, 1, 5, 6, 0, 2, 7};
  return t[u];
}
__host__ __device__ constexpr int unit_wait(int u) {
  constexpr int t[36] = {-1, -1, -1, -1, -1, 0, 1, 2, 2, 3, 4, 5,  5, 6, 7, 8, 8, 9, 10, 11, 11, 12, 13, 14,
                         15, 16, 17, 18,  19, 20, 21, 22, 23, 24, 25, 26};
  return t[u];
}

__device__ __forceinline__ uint32_t stage_off(int g, int j) {
  return g == 0 ? (j < 2 ? 8 * kSlot + j * 8192 : 10 * kSlot + (j - 2) * 8192)
                : (j < 2 ? 12 * kSlot + j * 8192 : (j == 2 ? 11 * kSlot + 8192 : 9 * kSlot));
}

struct Params {
  CUtensorMap x, w1, w2, wf, wg, wo, g, out64, out56;
};

__device__ __forceinline__ void init_bar(uint32_t bars, int i) {
  const uint32_t a = bars + i * 8;
  const bool is_e = (i >= kBarE && i < kBarE + 27);
  mbar_init(a, is_e ? 8 : (i == kBarFE ? 9 : 1));
  if (!is_e) {
    uint32_t bytes = 16384;
    if (i == kBarFX) bytes = 8192;
    if (i == kBarFE) bytes = 8192 + kGEBytes;
    mbar_expect(a, bytes);
  }
}

__global__ void __cluster_dims__(2, 1, 1) __launch_bounds__(kThreads, 1)
rnnt_joint_kernel(const __grid_constant__ Params P) {
  extern __shared__ uint8_t smem_raw[];
  const uint32_t sb = (smem_u32(smem_raw) + 1023u) & ~1023u;
  const uint32_t bars = sb + kOffBar;
  const int warp = threadIdx.x >> 5, lane = threadIdx.x & 31;
  uint32_t cta;
  asm volatile("mov.u32 %0, %%cluster_ctarank;" : "=r"(cta));
  const uint32_t peer = cta ^ 1u;
  const int cl = blockIdx.x >> 1;
  const bool ge_cta = cl < 2;
  const int b = ge_cta ? cl : ((cl - 2) >> 5);
  const int r0 = ge_cta ? 32 * kR : ((cl - 2) & 31) * kR;
  const int rvalid = ge_cta ? kT2 - 32 * kR : kR;

  if (warp >= 8) {
    asm volatile("setmaxnreg.dec.sync.aligned.u32 40;");
    if (warp > 8) {
      if (elect_one()) {
#pragma unroll
        for (int i = 0; i < 5; i++) if (57 + (warp - 9) * 5 + i < kBarG) init_bar(bars, 57 + (warp - 9) * 5 + i);
#pragma unroll
        for (int i = 0; i < 5; i++) if (kBarRH + (warp - 9) * 5 + i < kNumBars) mbar_init(bars + (kBarRH + (warp - 9) * 5 + i) * 8, 4);
        asm volatile("fence.mbarrier_init.release.cluster;" ::: "memory");
      }
      __syncwarp();
      cluster_sync_relaxed();
      if (warp > 9) return;
#pragma unroll
      for (int g = 0; g < 2; g++) {
        mbar_wait(bars + (kBarRH + g) * 8);
        if (elect_one()) {
          const uint32_t src = sb + kSlotH * kSlot + (2 * cta + g) * 8192;
          dsmem_copy(mapa(src, peer), src, 8192, mapa(bars + kBarHX * 8, peer));
        }
        __syncwarp();
      }
#pragma unroll
      for (int g = 0; g < 2; g++) {
        mbar_wait(bars + (kBarRF + g) * 8);
        if (elect_one()) {
          const uint32_t src = sb + kSlotF * kSlot + (2 * cta + g) * 4096;
          dsmem_copy(mapa(src, peer), src, 4096, mapa(bars + kBarFX * 8, peer));
        }
        __syncwarp();
      }
#pragma unroll
      for (int g = 0; g < 2; g++) {
        mbar_wait(bars + (kBarRE + g) * 8);
        if (elect_one())
          dsmem_copy(mapa(sb + kSlotFE * kSlot + (2 * cta + g) * 4096, peer), sb + kSlotH * kSlot + g * 4096, 4096, mapa(bars + kBarFE * 8, peer));
        __syncwarp();
      }
      {
        int nxt0 = ((int)cta * 16 < rvalid) ? 0 : 4, nxt1 = ((int)cta * 16 + 8 < rvalid) ? 0 : 4;
        const long long t0 = clock64();
        while ((nxt0 < 4 || nxt1 < 4) && clock64() - t0 < 8000000ll) {
#pragma unroll
          for (int g = 0; g < 2; g++) {
            const int j = g ? nxt1 : nxt0;
            if (j < 4 && mbar_test(bars + (kBarPR + g * 4 + j) * 8)) {
              if (elect_one()) {
                const int rl0 = cta * 16 + g * 8;
                tma_store_3d((rl0 + 8 <= rvalid) ? &P.out64 : &P.out56, sb + stage_off(g, j), 0, (b * kT2 + r0 + rl0) * 8, j);
                asm volatile("cp.async.bulk.commit_group;" ::: "memory");
              }
              __syncwarp();
              if (g) nxt1++; else nxt0++;
            }
          }
        }
        if (elect_one()) asm volatile("cp.async.bulk.wait_group.read 0;" ::: "memory");
        __syncwarp();
        TS(2, 11);
        GT(1);
      }
      return;
    }
    TS(2, 0);
    GT(0);
    unsigned int ticket = 0;
    const int par = cta == 0 ? 1 : 0;
    const int q0 = cta == 0 ? 2 * r0 - 2 : 2 * r0 - 1;
    if (elect_one()) {
      mbar_init(bars + kBarX * 8, 1); mbar_expect(bars + kBarX * 8, 16384);
      mbar_init(bars + kBarW * 8, 1); mbar_expect(bars + kBarW * 8, 16384);
      fence_async_smem();
      tma_load_4d(sb, &P.x, bars + kBarX * 8, 0, 1, 2 * r0 - 2, b);
      tma_load_4d(sb + 8192, &P.x, bars + kBarX * 8, 0, 0, 2 * r0 - 1, b);
      tma_load_3d(sb + unit_slot(0) * kSlot, &P.w1, bars + kBarW * 8, 0, 0, 2 * cta);
      TS(2, 7);
#pragma unroll
      for (int i = 1; i < 9; i++) if (i != kBarW) { mbar_init(bars + i * 8, 1); mbar_expect(bars + i * 8, 16384); }
      if (ge_cta) { mbar_init(bars + kBarG * 8, 1); mbar_expect(bars + kBarG * 8, 4 * 16384 + 4096); mbar_init(bars + kBarP0 * 8, 8); }
      asm volatile("fence.mbarrier_init.release.cluster;" ::: "memory");
      fence_async_smem();
      TS(2, 8);
      if (ge_cta) {
        tma_load_3d(sb + kOffG, &P.g, bars + kBarG * 8, 0, b * 8, 0);
#pragma unroll
        for (int i = 0; i < 4; i++) tma_load_3d(sb + (9 + i) * kSlot, &P.wg, bars + kBarG * 8, 0, i * 64, 2 * cta);
      }
#pragma unroll
      for (int u = 1; u < 5; u++)
        tma_load_3d(sb + unit_slot(u) * kSlot, &P.w1, bars + (kBarW + u) * 8, 0, (u % 3) * 256 + (u / 3) * 64, 2 * cta);
      TS(2, 10);
    }
    __syncwarp();
    TS(2, 6);
    cluster_sync_relaxed();
    TS(2, 1);
    if (elect_one()) {
#pragma unroll
      for (int p = 1; p < XFIRST; p++)
        tma_load_4d_mc(sb + p * kSlot + cta * 8192, &P.x, bars + (kBarX + p) * 8, p * 64, par, q0, b, (uint16_t)3);
    }
    __syncwarp();
    if (lane == 0) ticket = atomicAdd(&g_cta_count, 1u);
#pragma unroll
    for (int p = XFIRST; p < 4; p++) {
      if (XSTEP == 1 || ((p - XFIRST) & 1) == 0) mbar_wait(bars + (kBarX + p - XFIRST) * 8);
      if (ge_cta && p == 3) mbar_wait(bars + kBarP0 * 8);
      if (elect_one())
        tma_load_4d_mc(sb + p * kSlot + cta * 8192, &P.x, bars + (kBarX + p) * 8, p * 64, par, q0, b, (uint16_t)3);
      __syncwarp();
    }
#pragma unroll
    for (int u = 5; u < 36; u++) {
      if (unit_wait(u) != unit_wait(u - 1)) mbar_wait(bars + (kBarE + unit_wait(u)) * 8);
      if (u == 27) ticket = __shfl_sync(0xffffffffu, ticket, 0);
      if (elect_one()) {
        const uint32_t dst = sb + unit_slot(u) * kSlot, bar = bars + (kBarW + u) * 8;
        if (u < 12) tma_load_3d(dst, &P.w1, bar, 0, (u % 3) * 256 + (u / 3) * 64, 2 * cta);
        else if (u < 24) tma_load_3d(dst, &P.w2, bar, 0, ((u - 12) % 3) * 256 + ((2 * cta + (u - 12) / 3) & 3) * 64, 2 * cta);
        else if (u < 28) tma_load_3d(dst, &P.wf, bar, 0, ((2 * cta + (u - 24)) & 3) * 64, 2 * cta);
        else tma_load_3d(dst, &P.wo, bar, 0, ((u - 28) & 3) * 64, ((u - 28) >> 2) * 2);
        if (u == 27) {
          const unsigned int want = (ticket / kNumCtas + 1u) * 2u;
          const long long t0 = clock64();
          unsigned int v;
          do {
            asm volatile("ld.acquire.gpu.global.u32 %0, [%1];" : "=r"(v) : "l"(&g_ge_flag[b]) : "memory");
          } while ((int)(v - want) < 0 && clock64() - t0 < 4000000ll);
          asm volatile("fence.proxy.async;" ::: "memory");
          bulk_load(sb + kOffGE, reinterpret_cast<const char*>(g_ge) + b * kGEBytes, kGEBytes, bars + kBarFE * 8);
        }
      }
      __syncwarp();
      if (u == 11) TS(2, 2);
      if (u == 23) TS(2, 3);
      if (u == 27) TS(2, 4);
      if (u == 35) TS(2, 5);
    }
  } else {
    asm volatile("setmaxnreg.inc.sync.aligned.u32 232;");
    const int wg = warp >> 2, w = warp & 3;
    const int gq = lane >> 2, q = lane & 3;
    const uint32_t panel = 2 * cta + wg;
    const int ch = panel * 64 + w * 16 + gq;
    const uint32_t dA = desc_lo(sb + wg * 8192, 8192);
    const uint32_t dB = desc_lo(sb, 16);
    const uint32_t dBo = desc_lo(sb + cta * 2 * 8192, 16), dBp = desc_lo(sb + (cta ^ 1) * 2 * 8192, 16);
    const uint32_t dFo = desc_lo(sb + cta * 2 * 4096, 16), dFp = desc_lo(sb + (cta ^ 1) * 2 * 4096, 16);
    if (elect_one()) {
#pragma unroll
      for (int i = 0; i < 6; i++) init_bar(bars, 9 + warp * 6 + i);
      asm volatile("fence.mbarrier_init.release.cluster;" ::: "memory");
    }
    __syncwarp();
    cluster_sync_relaxed();
    if (w == 0) TS(wg, 0);

    if (ge_cta) {
      float ga[4];
      mbar_wait(bars + kBarG * 8);
      wg_fence();
#pragma unroll
      for (int i = 0; i < 4; i++) {
#pragma unroll
        for (int s = 0; s < 4; s++)
          wgmma_ss_n8(ga, desc_at(dA, (9 + i) * kSlot + s * 2048), desc_at(dB, kOffG + i * 1024 + s * 32), (i | s) != 0);
      }
      wg_commit();
      wg_wait<0>();
      if (lane == 0) mbar_arrive(bars + kBarP0 * 8);
      float* gp = g_ge + b * (kGEBytes / 4) + ((ch & 7) >> 1) * (kGEPitch / 4) + (ch >> 4) * 4 + (ch & 1);
      gp[(2 * q) * 4 * (kGEPitch / 4)] = ga[0];
      gp[(2 * q + 1) * 4 * (kGEPitch / 4)] = ga[1];
      gp[(2 * q) * 4 * (kGEPitch / 4) + 2] = ga[2];
      gp[(2 * q + 1) * 4 * (kGEPitch / 4) + 2] = ga[3];
      __threadfence();
      bar_consumers();
      if (threadIdx.x == 0) asm volatile("red.release.gpu.global.add.u32 [%0], 1;" ::"l"(&g_ge_flag[b]) : "memory");
    }

    {
      float acc[32];
#pragma unroll
      for (int u = 0; u < 12; u++) {
        const int p = u / 3, tap = u % 3;
        if (tap == 0) mbar_wait(bars + (kBarX + p) * 8);
        mbar_wait(bars + (kBarW + u) * 8);
        if (u == 0 && w == 0) TS(wg, 1);
        wg_fence();
#pragma unroll
        for (int s = 0; s < 4; s++)
          wgmma_ss_n64(acc, desc_at(dA, unit_slot(u) * kSlot + s * 2048),
                       desc_at(dB, p * kSlot + (tap == 1 ? 8192 : (tap == 2 ? 128 : 0)) + s * 32), (u | s) != 0);
        wg_commit();
        if (u > 0) {
          wg_wait<1>();
          if (lane == 0) mbar_arrive(bars + (kBarE + u - 1) * 8);
        }
      }
      wg_wait<0>();
      if (lane == 0) mbar_arrive(bars + (kBarE + 11) * 8);
      if (w == 0) TS(wg, 2);
      const uint32_t hp = sb + kSlotH * kSlot + panel * 8192;
      const int mi = lane >> 3, l8 = lane & 7;
#pragma unroll
      for (int jb = 0; jb < 8; jb += 2) {
        uint32_t r[4];
#pragma unroll
        for (int t = 0; t < 2; t++) {
          r[2 * t + 0] = pack_bf16(gelu_tanh(acc[4 * (jb + t) + 0]), gelu_tanh(acc[4 * (jb + t) + 1]));
          r[2 * t + 1] = pack_bf16(gelu_tanh(acc[4 * (jb + t) + 2]), gelu_tanh(acc[4 * (jb + t) + 3]));
        }
        const int n = 8 * (jb + (mi >> 1)) + l8;
        const int row = n >> 1, chunk = 2 * w + (mi & 1);
        stsm_x4_trans(hp + (n & 1) * 4096 + row * 128 + ((chunk ^ (row & 7)) << 4), r[0], r[1], r[2], r[3]);
      }
      fence_async_smem();
      __syncwarp();
      if (lane == 0) mbar_arrive(bars + (kBarRH + wg) * 8);
      mbar_wait(bars + kBarRH * 8);
      mbar_wait(bars + (kBarRH + 1) * 8);
      if (w == 0) TS(wg, 3);
    }
    {
      float acc[16];
#pragma unroll
      for (int v = 0; v < 12; v++) {
        const int i = v / 3, tap = v % 3;
        if (v == 6) { mbar_wait_cluster(bars + kBarHX * 8); if (w == 0) TS(wg, 4); }
        mbar_wait(bars + (kBarW + 12 + v) * 8);
        wg_fence();
#pragma unroll
        for (int s = 0; s < 4; s++)
          wgmma_ss_n32(acc, desc_at(dA, unit_slot(12 + v) * kSlot + s * 2048),
                       desc_at(i < 2 ? dBo : dBp, kSlotH * kSlot + (i & 1) * 8192 + (tap == 1 ? 4096 : (tap == 2 ? 128 : 0)) + s * 32), (v | s) != 0);
        wg_commit();
        if (v > 0) {
          wg_wait<1>();
          if (lane == 0) mbar_arrive(bars + (kBarE + 12 + v - 1) * 8);
        }
      }
      wg_wait<0>();
      if (lane == 0) mbar_arrive(bars + (kBarE + 23) * 8);
      if (w == 0) TS(wg, 5);
      const uint32_t fp = sb + kSlotF * kSlot + panel * 4096;
      const int mi = lane >> 3, l8 = lane & 7;
#pragma unroll
      for (int jb = 0; jb < 4; jb += 2) {
        uint32_t r[4];
#pragma unroll
        for (int t = 0; t < 2; t++) {
          r[2 * t + 0] = pack_bf16(gelu_tanh(acc[4 * (jb + t) + 0]), gelu_tanh(acc[4 * (jb + t) + 1]));
          r[2 * t + 1] = pack_bf16(gelu_tanh(acc[4 * (jb + t) + 2]), gelu_tanh(acc[4 * (jb + t) + 3]));
        }
        const int n = 8 * (jb + (mi >> 1)) + l8;
        const int chunk = 2 * w + (mi & 1);
        stsm_x4_trans(fp + n * 128 + ((chunk ^ (n & 7)) << 4), r[0], r[1], r[2], r[3]);
      }
      fence_async_smem();
      __syncwarp();
      if (lane == 0) mbar_arrive(bars + (kBarRF + wg) * 8);
      mbar_wait(bars + kBarRF * 8);
      mbar_wait(bars + (kBarRF + 1) * 8);
      if (w == 0) TS(wg, 6);
    }
    {
      float acc[16];
#pragma unroll
      for (int i = 0; i < 4; i++) {
        if (i == 2) { mbar_wait_cluster(bars + kBarFX * 8); if (w == 0) TS(wg, 7); }
        mbar_wait(bars + (kBarW + 24 + i) * 8);
        wg_fence();
#pragma unroll
        for (int s = 0; s < 4; s++)
          wgmma_ss_n32(acc, desc_at(dA, unit_slot(24 + i) * kSlot + s * 2048),
                       desc_at(i < 2 ? dFo : dFp, kSlotF * kSlot + (i & 1) * 4096 + s * 32), (i | s) != 0);
        wg_commit();
        if (i > 0) {
          wg_wait<1>();
          if (lane == 0) mbar_arrive(bars + (kBarE + 24 + i - 1) * 8);
        }
      }
      wg_wait<0>();
      if (w == 0) TS(wg, 8);
      const uint32_t qk = gq >> 1;
      const uint32_t off0 = qk * 128 + (((2 * w) ^ (2 * qk)) << 4) + (gq & 1) * 8;
      const uint32_t off1 = qk * 128 + (((2 * w + 1) ^ (2 * qk)) << 4) + (gq & 1) * 8;
      const uint32_t own = sb + kSlotFE * kSlot + panel * 4096;
      const uint32_t stg = sb + kSlotH * kSlot + wg * 4096;
#pragma unroll
      for (int jb = 0; jb < 4; jb++) {
        const uint32_t base = (((uint32_t)(jb >> 1) == cta) ? own : stg) + (4 * (jb & 1) + q) * 512;
        sts64(base + off0, acc[4 * jb + 0], acc[4 * jb + 1]);
        sts64(base + off1, acc[4 * jb + 2], acc[4 * jb + 3]);
      }
      fence_async_smem();
      __syncwarp();
      if (lane == 0) { mbar_arrive(bars + (kBarRE + wg) * 8); mbar_arrive(bars + kBarFE * 8); }
      if (w == 0) TS(wg, 9);
    }
    const int rl0 = cta * 16 + wg * 8;
    mbar_wait_cluster(bars + kBarFE * 8);
    asm volatile("barrier.cluster.arrive.relaxed.aligned;" ::: "memory");
    if (wg == 1) asm volatile("bar.sync 4, 256;" ::: "memory");
    if (rl0 < rvalid) {
      if (w == 0) TS(wg, 10);
      const uint32_t fe_t = sb + kSlotFE * kSlot + ((4 * wg + w) * 4 + q) * 128;
      const uint32_t ge_t = sb + kOffGE + lane * kGEPitch;
      const int mi = lane >> 3, l8 = lane & 7;
      const uint32_t st = sb + (16 * w + (mi & 1) * 8 + l8) * 128;
      uint32_t A[64];
      float acc[2][32];
      {
        constexpr int PD = 3;
        float4 fa[PD], fb[PD], gg[PD];
#pragma unroll
        for (int kk = 0; kk < 16 + PD; kk++) {
          if (kk >= PD) {
            const int k = kk - PD, sl = k % PD;
            A[4 * k + 0] = tanh2_pack(fa[sl].x + gg[sl].x, fa[sl].z + gg[sl].y);
            A[4 * k + 1] = tanh2_pack(fa[sl].y + gg[sl].x, fa[sl].w + gg[sl].y);
            A[4 * k + 2] = tanh2_pack(fb[sl].x + gg[sl].z, fb[sl].z + gg[sl].w);
            A[4 * k + 3] = tanh2_pack(fb[sl].y + gg[sl].z, fb[sl].w + gg[sl].w);
          }
          if (kk < 16) {
            const int sl = kk % PD;
            fa[sl] = lds128(fe_t + (kk >> 2) * 4096 + ((((kk & 3) * 2) ^ (2 * q)) << 4));
            fb[sl] = lds128(fe_t + (kk >> 2) * 4096 + ((((kk & 3) * 2 + 1) ^ (2 * q)) << 4));
            gg[sl] = lds128(ge_t + kk * 16);
          }
        }
      }
#pragma unroll
      for (int kk = 0; kk < 16; kk++) {
        if ((kk & 3) == 0) { mbar_wait(bars + (kBarW + 28 + (kk >> 2)) * 8); wg_fence(); }
        wgmma_rs_n64(acc[0], A[4 * kk], A[4 * kk + 1], A[4 * kk + 2], A[4 * kk + 3],
                     desc_at(dB, unit_slot(28 + (kk >> 2)) * kSlot + (kk & 3) * 2048), kk != 0);
        if (kk == ARRK) bar_arrive_pred(wg == 0);
      }
      wg_commit();
      if (w == 0) TS(wg, 11);
#pragma unroll
      for (int j = 0; j < 4; j++) {
        const int jn = j + 1;
        if (jn == 2) {
#pragma unroll
          for (int i = 0; i < 4; i++) mbar_wait(bars + (kBarW + 32 + i) * 8);
        }
        if (j < 3) wg_fence();
        const uint32_t stj = st + (wg ? stage_off(1, j) : stage_off(0, j));
#pragma unroll
        for (int kk = 0; kk < 16; kk++) {
          if (j < 3)
            wgmma_rs_n64(acc[jn & 1], A[4 * kk], A[4 * kk + 1], A[4 * kk + 2], A[4 * kk + 3],
                         desc_at(dB, unit_slot(28 + (jn >> 1) * 4 + (kk >> 2)) * kSlot + (jn & 1) * 8192 + (kk & 3) * 2048), kk != 0);
          if (kk == 1) {
            if (j < 3) { wg_commit(); wg_wait<1>(); } else { wg_wait<0>(); }
          }
          if (kk >= 2 && kk < 10 && (kk & 1) == 0) {
            const int jb = kk - 2;
            const uint32_t r0_ = pack_bf16(acc[j & 1][4 * jb + 0], acc[j & 1][4 * jb + 1]), r1_ = pack_bf16(acc[j & 1][4 * jb + 2], acc[j & 1][4 * jb + 3]);
            const uint32_t r2_ = pack_bf16(acc[j & 1][4 * jb + 4], acc[j & 1][4 * jb + 5]), r3_ = pack_bf16(acc[j & 1][4 * jb + 6], acc[j & 1][4 * jb + 7]);
            stsm_x4(stj + (((jb + (mi >> 1)) ^ l8) << 4), r0_, r1_, r2_, r3_);
          }
          if (kk == 9) {
            fence_async_smem();
            __syncwarp();
            mbar_arrive_pred(bars + (kBarPR + wg * 4 + j) * 8, lane == 0);
          }
        }
        if (j < 3) wg_commit();
        if (j == 0 && w == 0) TS(wg, 12);
        if (j == 2 && w == 0) TS(wg, 13);
      }
      if (w == 0) TS(wg, 14);
    } else if (wg == 0) {
      asm volatile("bar.arrive 4, 256;" ::: "memory");
    }
    asm volatile("barrier.cluster.wait.aligned;" ::: "memory");
  }
}

typedef CUresult (*EncodeFn)(CUtensorMap*, CUtensorMapDataType, cuuint32_t, void*, const cuuint64_t*, const cuuint64_t*,
                             const cuuint32_t*, const cuuint32_t*, CUtensorMapInterleave, CUtensorMapSwizzle,
                             CUtensorMapL2promotion, CUtensorMapFloatOOBfill);

void make_map3(EncodeFn enc, CUtensorMap* tm, const void* ptr, uint64_t rows, uint32_t box_rows, uint32_t box_panels) {
  cuuint64_t gd[3] = {64, rows, 4};
  cuuint64_t gs[2] = {512, 128};
  cuuint32_t bd[3] = {64, box_rows, box_panels};
  cuuint32_t es[3] = {1, 1, 1};
  enc(tm, CU_TENSOR_MAP_DATA_TYPE_BFLOAT16, 3, const_cast<void*>(ptr), gd, gs, bd, es, CU_TENSOR_MAP_INTERLEAVE_NONE,
      CU_TENSOR_MAP_SWIZZLE_128B, CU_TENSOR_MAP_L2_PROMOTION_L2_256B, CU_TENSOR_MAP_FLOAT_OOB_FILL_NONE);
}

}

extern "C" void kernel_launch(void* const* d_in, const int* in_sizes, int n_in, void* d_out, int out_size) {
  static EncodeFn enc = nullptr;
  if (!enc) {
    cudaDriverEntryPointQueryResult qr;
    cudaGetDriverEntryPoint("cuTensorMapEncodeTiled", (void**)&enc, cudaEnableDefault, &qr);
    cudaFuncSetAttribute(rnnt_joint_kernel, cudaFuncAttributeMaxDynamicSharedMemorySize, kSmemBytes);
  }
  Params P;
  {
    cuuint64_t gd[4] = {256, 2, 2000, 2};
    cuuint64_t gs[3] = {512, 1024, 4000ull * 512};
    cuuint32_t bd[4] = {64, 1, 64, 1};
    cuuint32_t es[4] = {1, 1, 1, 1};
    enc(&P.x, CU_TENSOR_MAP_DATA_TYPE_BFLOAT16, 4, d_in[0], gd, gs, bd, es, CU_TENSOR_MAP_INTERLEAVE_NONE,
        CU_TENSOR_MAP_SWIZZLE_128B, XPROMO, CU_TENSOR_MAP_FLOAT_OOB_FILL_NONE);
  }
  make_map3(enc, &P.w1, d_in[1], 768, 64, 2);
  make_map3(enc, &P.w2, d_in[2], 768, 64, 2);
  make_map3(enc, &P.g, d_in[3], 16, 8, 4);
  make_map3(enc, &P.wf, d_in[4], 256, 64, 2);
  make_map3(enc, &P.wg, d_in[5], 256, 64, 2);
  make_map3(enc, &P.wo, d_in[6], 256, 64, 2);
  make_map3(enc, &P.out64, d_out, 16000, 64, 1);
  make_map3(enc, &P.out56, d_out, 16000, 56, 1);
  rnnt_joint_kernel<<<kNumCtas, kThreads, kSmemBytes>>>(P);
}
```

```cpp
#include <cuda_runtime.h>
#include <cuda_bf16.h>
#include <cuda.h>
#include <stdint.h>

#define ARRK 3
#define XBULK 1
#define XPREF 1
#define XFIRST 3
#define XSTEP 1
#define XPROMO CU_TENSOR_MAP_L2_PROMOTION_L2_128B
namespace {

constexpr int kT2 = 1000;
constexpr int kR = 31;
constexpr int kNumCtas = 132;
constexpr int kThreads = 384;
constexpr int kSlot = 16384;

constexpr int kSlotFE = 9, kSlotF = 10, kSlotH = 11;
constexpr int kOffG = 13 * kSlot;
constexpr int kOffGE = kOffG + 4096;
constexpr int kGEPitch = 272;
constexpr int kGEBytes = 32 * kGEPitch;
constexpr int kOffBar = kOffGE + kGEBytes;
constexpr int kBarX = 0;
constexpr int kBarW = 4;
constexpr int kBarE = 40;
constexpr int kBarHX = 67, kBarFX = 68, kBarFE = 69, kBarG = 70, kBarP0 = 71;
constexpr int kBarRH = 72, kBarRF = 74, kBarRE = 76;
constexpr int kBarPR = 78;
constexpr int kBarGW = 86;
constexpr int kBarFO = 87;
constexpr int kBarGE = 88;
constexpr int kNumBars = 89;
constexpr int kSmemBytes = kOffBar + kNumBars * 8 + 1024;

__device__ __align__(128) float g_ge[2 * kGEBytes / 4];
__device__ unsigned int g_ge_flag[2];
__device__ unsigned int g_cta_count;

#define TS(slot_, idx_) do {} while (0)
#define GT(idx_) do {} while (0)

__device__ __forceinline__ uint32_t smem_u32(const void* p) { return (uint32_t)__cvta_generic_to_shared(p); }
__device__ __forceinline__ void mbar_init(uint32_t a, uint32_t c) { asm volatile("mbarrier.init.shared.b64 [%0], %1;" ::"r"(a), "r"(c) : "memory"); }
__device__ __forceinline__ void mbar_expect(uint32_t a, uint32_t b) { asm volatile("mbarrier.arrive.expect_tx.shared.b64 _, [%0], %1;" ::"r"(a), "r"(b) : "memory"); }
__device__ __forceinline__ void mbar_arrive(uint32_t a) { asm volatile("mbarrier.arrive.shared.b64 _, [%0];" ::"r"(a) : "memory"); }
__device__ __forceinline__ void mbar_arrive_pred(uint32_t a, bool p) {
  asm volatile("{\n.reg .pred q;\nsetp.ne.u32 q, %1, 0;\n@q mbarrier.arrive.shared.b64 _, [%0];\n}\n" ::"r"(a), "r"((uint32_t)p) : "memory");
}
__device__ __forceinline__ void bar_arrive_pred(bool p) {
  asm volatile("{\n.reg .pred q;\nsetp.ne.u32 q, %0, 0;\n@q bar.arrive 4, 256;\n}\n" ::"r"((uint32_t)p) : "memory");
}
__device__ __forceinline__ bool mbar_try(uint32_t a) {
  uint32_t ok;
  asm volatile("{\n.reg .pred p;\nmbarrier.try_wait.parity.shared.b64 p, [%1], 0;\nselp.u32 %0, 1, 0, p;\n}\n" : "=r"(ok) : "r"(a) : "memory");
  return ok != 0;
}
__device__ __forceinline__ bool mbar_test(uint32_t a) {
  uint32_t ok;
  asm volatile("{\n.reg .pred p;\nmbarrier.test_wait.parity.shared.b64 p, [%1], 0;\nselp.u32 %0, 1, 0, p;\n}\n" : "=r"(ok) : "r"(a) : "memory");
  return ok != 0;
}
__device__ __forceinline__ bool mbar_try_cluster(uint32_t a) {
  uint32_t ok;
  asm volatile("{\n.reg .pred p;\nmbarrier.try_wait.parity.acquire.cluster.shared.b64 p, [%1], 0;\nselp.u32 %0, 1, 0, p;\n}\n" : "=r"(ok) : "r"(a) : "memory");
  return ok != 0;
}
__device__ __forceinline__ void mbar_wait_slow(uint32_t a) {
  const long long t0 = clock64();
  while (!mbar_try(a)) { if (clock64() - t0 > 4000000ll) break; }
}
__device__ __forceinline__ void mbar_wait_cluster_slow(uint32_t a) {
  const long long t0 = clock64();
  while (!mbar_try_cluster(a)) { if (clock64() - t0 > 4000000ll) break; }
}
__device__ __forceinline__ void mbar_wait(uint32_t a) { if (!mbar_try(a)) mbar_wait_slow(a); }
__device__ __forceinline__ void mbar_wait_cluster(uint32_t a) { if (!mbar_try_cluster(a)) mbar_wait_cluster_slow(a); }
__device__ __forceinline__ uint32_t mapa(uint32_t a, uint32_t r) { uint32_t d; asm volatile("mapa.shared::cluster.u32 %0, %1, %2;" : "=r"(d) : "r"(a), "r"(r)); return d; }
__device__ __forceinline__ bool elect_one() { uint32_t p; asm volatile("{\n.reg .pred P;\nelect.sync _|P, 0xffffffff;\nselp.u32 %0, 1, 0, P;\n}\n" : "=r"(p)); return p != 0; }
__device__ __forceinline__ void fence_async_smem() { asm volatile("fence.proxy.async.shared::cta;" ::: "memory"); }
__device__ __forceinline__ void bar_consumers() { asm volatile("bar.sync 1, 256;" ::: "memory"); }
__device__ __forceinline__ void bar_wg(int wg) { asm volatile("bar.sync %0, 128;" ::"r"(2 + wg) : "memory"); }
__device__ __forceinline__ void cluster_sync_relaxed() { asm volatile("barrier.cluster.arrive.relaxed.aligned;\nbarrier.cluster.wait.aligned;" ::: "memory"); }
__device__ __forceinline__ void wg_fence() { asm volatile("wgmma.fence.sync.aligned;" ::: "memory"); }
__device__ __forceinline__ void wg_commit() { asm volatile("wgmma.commit_group.sync.aligned;" ::: "memory"); }
template <int N> __device__ __forceinline__ void wg_wait() { asm volatile("wgmma.wait_group.sync.aligned %0;" ::"n"(N) : "memory"); }

__device__ __forceinline__ void tma_load_3d(uint32_t dst, const CUtensorMap* tm, uint32_t bar, int c0, int c1, int c2) {
  asm volatile("cp.async.bulk.tensor.3d.shared::cluster.global.mbarrier::complete_tx::bytes [%0], [%1, {%3, %4, %5}], [%2];"
               ::"r"(dst), "l"(tm), "r"(bar), "r"(c0), "r"(c1), "r"(c2) : "memory");
}
__device__ __forceinline__ void tma_load_4d(uint32_t dst, const CUtensorMap* tm, uint32_t bar, int c0, int c1, int c2, int c3) {
  asm volatile("cp.async.bulk.tensor.4d.shared::cluster.global.mbarrier::complete_tx::bytes [%0], [%1, {%3, %4, %5, %6}], [%2];"
               ::"r"(dst), "l"(tm), "r"(bar), "r"(c0), "r"(c1), "r"(c2), "r"(c3) : "memory");
}
__device__ __forceinline__ void tma_load_4d_mc(uint32_t dst, const CUtensorMap* tm, uint32_t bar, int c0, int c1, int c2, int c3, uint16_t mask) {
  asm volatile("cp.async.bulk.tensor.4d.shared::cluster.global.mbarrier::complete_tx::bytes.multicast::cluster [%0], [%1, {%3, %4, %5, %6}], [%2], %7;"
               ::"r"(dst), "l"(tm), "r"(bar), "r"(c0), "r"(c1), "r"(c2), "r"(c3), "h"(mask) : "memory");
}
__device__ __forceinline__ void tma_store_3d(const CUtensorMap* tm, uint32_t src, int c0, int c1, int c2) {
  asm volatile("cp.async.bulk.tensor.3d.global.shared::cta.bulk_group [%0, {%2, %3, %4}], [%1];"
               ::"l"(tm), "r"(src), "r"(c0), "r"(c1), "r"(c2) : "memory");
}
__device__ __forceinline__ void bulk_load(uint32_t dst, const void* src, uint32_t bytes, uint32_t bar) {
  asm volatile("cp.async.bulk.shared::cluster.global.mbarrier::complete_tx::bytes [%0], [%1], %2, [%3];"
               ::"r"(dst), "l"(src), "r"(bytes), "r"(bar) : "memory");
}
__device__ __forceinline__ void dsmem_copy(uint32_t dst_remote, uint32_t src, uint32_t bytes, uint32_t bar_remote) {
  asm volatile("cp.async.bulk.shared::cluster.shared::cta.mbarrier::complete_tx::bytes [%0], [%1], %2, [%3];"
               ::"r"(dst_remote), "r"(src), "r"(bytes), "r"(bar_remote) : "memory");
}
__device__ __forceinline__ void stsm_x4_trans(uint32_t addr, uint32_t r0, uint32_t r1, uint32_t r2, uint32_t r3) {
  asm volatile("stmatrix.sync.aligned.m8n8.x4.trans.shared.b16 [%0], {%1, %2, %3, %4};" ::"r"(addr), "r"(r0), "r"(r1), "r"(r2), "r"(r3) : "memory");
}
__device__ __forceinline__ void stsm_x4(uint32_t addr, uint32_t r0, uint32_t r1, uint32_t r2, uint32_t r3) {
  asm volatile("stmatrix.sync.aligned.m8n8.x4.shared.b16 [%0], {%1, %2, %3, %4};" ::"r"(addr), "r"(r0), "r"(r1), "r"(r2), "r"(r3) : "memory");
}
__device__ __forceinline__ float2 lds64(uint32_t a) { float2 v; asm volatile("ld.shared.v2.f32 {%0, %1}, [%2];" : "=f"(v.x), "=f"(v.y) : "r"(a) : "memory"); return v; }
__device__ __forceinline__ float4 lds128(uint32_t a) { float4 v; asm volatile("ld.shared.v4.f32 {%0, %1, %2, %3}, [%4];" : "=f"(v.x), "=f"(v.y), "=f"(v.z), "=f"(v.w) : "r"(a) : "memory"); return v; }
__device__ __forceinline__ void sts64(uint32_t a, float x, float y) { asm volatile("st.shared.v2.f32 [%0], {%1, %2};" ::"r"(a), "f"(x), "f"(y) : "memory"); }
__device__ __forceinline__ float tanh_fast(float x) { float y; asm("tanh.approx.f32 %0, %1;" : "=f"(y) : "f"(x)); return y; }
__device__ __forceinline__ uint32_t tanh2_pack(float lo, float hi) {
  uint32_t r;
  asm volatile("{\n.reg .f32 a, b;\ntanh.approx.f32 a, %1;\ntanh.approx.f32 b, %2;\ncvt.rn.bf16x2.f32 %0, b, a;\n}\n" : "=r"(r) : "f"(lo), "f"(hi));
  return r;
}
__device__ __forceinline__ uint32_t pack_bf16(float lo, float hi) { uint32_t r; asm("cvt.rn.bf16x2.f32 %0, %1, %2;" : "=r"(r) : "f"(hi), "f"(lo)); return r; }
__device__ __forceinline__ float gelu_tanh(float x) {
  const float k0 = 0.7978845608028654f, k1 = 0.7978845608028654f * 0.044715f;
  float u = x * fmaf(x * x, k1, k0);
  float hx = 0.5f * x;
  return fmaf(hx, tanh_fast(u), hx);
}
__device__ __forceinline__ uint64_t make_desc(uint32_t addr, uint32_t lbo, uint32_t sbo) {
  return (uint64_t)((addr & 0x3FFFF) >> 4) | ((uint64_t)(lbo >> 4) << 16) | ((uint64_t)(sbo >> 4) << 32) | ((uint64_t)1 << 62);
}

__device__ __forceinline__ uint32_t desc_lo(uint32_t addr, uint32_t lbo) { return ((addr & 0x3FFFF) >> 4) | ((lbo >> 4) << 16); }
__device__ __forceinline__ uint64_t desc_at(uint32_t lo, uint32_t off) { return ((uint64_t)0x40000040u << 32) | (uint64_t)(lo + (off >> 4)); }

__device__ __forceinline__ void wgmma_ss_n64(float (&d)[32], uint64_t da, uint64_t db, int scale_d) {
  asm volatile("{\n.reg .pred p;\nsetp.ne.b32 p, %34, 0;\n"
    "wgmma.mma_async.sync.aligned.m64n64k16.f32.bf16.bf16 {%0, %1, %2, %3, %4, %5, %6, %7, %8, %9, %10, %11, %12, %13, %14, %15, %16, %17, %18, %19, %20, %21, %22, %23, %24, %25, %26, %27, %28, %29, %30, %31}, %32, %33, p, 1, 1, 1, 0;\n}\n"
    : "+f"(d[0]), "+f"(d[1]), "+f"(d[2]), "+f"(d[3]), "+f"(d[4]), "+f"(d[5]), "+f"(d[6]), "+f"(d[7]), "+f"(d[8]), "+f"(d[9]), "+f"(d[10]), "+f"(d[11]), "+f"(d[12]), "+f"(d[13]), "+f"(d[14]), "+f"(d[15]), "+f"(d[16]), "+f"(d[17]), "+f"(d[18]), "+f"(d[19]), "+f"(d[20]), "+f"(d[21]), "+f"(d[22]), "+f"(d[23]), "+f"(d[24]), "+f"(d[25]), "+f"(d[26]), "+f"(d[27]), "+f"(d[28]), "+f"(d[29]), "+f"(d[30]), "+f"(d[31])
    : "l"(da), "l"(db), "r"(scale_d));
}

__device__ __forceinline__ void wgmma_ss_n32(float (&d)[16], uint64_t da, uint64_t db, int scale_d) {
  asm volatile("{\n.reg .pred p;\nsetp.ne.b32 p, %18, 0;\n"
    "wgmma.mma_async.sync.aligned.m64n32k16.f32.bf16.bf16 {%0, %1, %2, %3, %4, %5, %6, %7, %8, %9, %10, %11, %12, %13, %14, %15}, %16, %17, p, 1, 1, 1, 0;\n}\n"
    : "+f"(d[0]), "+f"(d[1]), "+f"(d[2]), "+f"(d[3]), "+f"(d[4]), "+f"(d[5]), "+f"(d[6]), "+f"(d[7]), "+f"(d[8]), "+f"(d[9]), "+f"(d[10]), "+f"(d[11]), "+f"(d[12]), "+f"(d[13]), "+f"(d[14]), "+f"(d[15])
    : "l"(da), "l"(db), "r"(scale_d));
}

__device__ __forceinline__ void wgmma_ss_n8(float (&d)[4], uint64_t da, uint64_t db, int scale_d) {
  asm volatile("{\n.reg .pred p;\nsetp.ne.b32 p, %6, 0;\n"
    "wgmma.mma_async.sync.aligned.m64n8k16.f32.bf16.bf16 {%0, %1, %2, %3}, %4, %5, p, 1, 1, 1, 0;\n}\n"
    : "+f"(d[0]), "+f"(d[1]), "+f"(d[2]), "+f"(d[3])
    : "l"(da), "l"(db), "r"(scale_d));
}

__device__ __forceinline__ void wgmma_rs_n64(float (&d)[32], uint32_t a0, uint32_t a1, uint32_t a2, uint32_t a3, uint64_t db, int scale_d) {
  asm volatile("{\n.reg .pred p;\nsetp.ne.b32 p, %37, 0;\n"
    "wgmma.mma_async.sync.aligned.m64n64k16.f32.bf16.bf16 {%0, %1, %2, %3, %4, %5, %6, %7, %8, %9, %10, %11, %12, %13, %14, %15, %16, %17, %18, %19, %20, %21, %22, %23, %24, %25, %26, %27, %28, %29, %30, %31}, {%32, %33, %34, %35}, %36, p, 1, 1, 1;\n}\n"
    : "+f"(d[0]), "+f"(d[1]), "+f"(d[2]), "+f"(d[3]), "+f"(d[4]), "+f"(d[5]), "+f"(d[6]), "+f"(d[7]), "+f"(d[8]), "+f"(d[9]), "+f"(d[10]), "+f"(d[11]), "+f"(d[12]), "+f"(d[13]), "+f"(d[14]), "+f"(d[15]), "+f"(d[16]), "+f"(d[17]), "+f"(d[18]), "+f"(d[19]), "+f"(d[20]), "+f"(d[21]), "+f"(d[22]), "+f"(d[23]), "+f"(d[24]), "+f"(d[25]), "+f"(d[26]), "+f"(d[27]), "+f"(d[28]), "+f"(d[29]), "+f"(d[30]), "+f"(d[31])
    : "r"(a0), "r"(a1), "r"(a2), "r"(a3), "l"(db), "r"(scale_d));
}

__host__ __device__ constexpr int unit_slot(int u) {
  constexpr int t[36] = {4, 5, 6, 7, 8, 4, 5, 6, 0, 7, 8, 4,  1, 5, 6, 0, 2, 7, 8, 4, 3, 1, 5, 6,
                         0, 2, 7, 8,  4, 3, 1, 5, 6, 0, 2, 7};
  return t[u];
}
__host__ __device__ constexpr int unit_wait(int u) {
  constexpr int t[36] = {-1, -1, -1, -1, -1, 0, 1, 2, 2, 3, 4, 5,  5, 6, 7, 8, 8, 9, 10, 11, 11, 12, 13, 14,
                         15, 16, 17, 18,  19, 20, 21, 22, 23, 24, 25, 26};
  return t[u];
}

__device__ __forceinline__ uint32_t stage_off(int g, int j) {
  return g == 0 ? (j < 2 ? 8 * kSlot + j * 8192 : 10 * kSlot + (j - 2) * 8192)
                : (j < 2 ? 12 * kSlot + j * 8192 : (j == 2 ? 11 * kSlot + 8192 : 9 * kSlot));
}

struct Params {
  CUtensorMap x, w1, w2, wf, wg, wo, g, out64, out56;
  const void* xptr;
};

__device__ __forceinline__ void init_bar(uint32_t bars, int i) {
  const uint32_t a = bars + i * 8;
  const bool is_e = (i >= kBarE && i < kBarE + 27);
  mbar_init(a, is_e ? 8 : 1);
  if (!is_e) {
    uint32_t bytes = 16384;
    if (i == kBarFX) bytes = 8192;
    if (i == kBarFE) bytes = 8192;
    mbar_expect(a, bytes);
  }
}

__global__ void __cluster_dims__(2, 1, 1) __launch_bounds__(kThreads, 1)
rnnt_joint_kernel(const __grid_constant__ Params P) {
  extern __shared__ uint8_t smem_raw[];
  const uint32_t sb = (smem_u32(smem_raw) + 1023u) & ~1023u;
  const uint32_t bars = sb + kOffBar;
  const int warp = threadIdx.x >> 5, lane = threadIdx.x & 31;
  uint32_t cta;
  asm volatile("mov.u32 %0, %%cluster_ctarank;" : "=r"(cta));
  const uint32_t peer = cta ^ 1u;
  const int cl = blockIdx.x >> 1;
  const bool ge_cta = cl < 2;
  const int b = ge_cta ? cl : ((cl - 2) >> 5);
  const int r0 = ge_cta ? 32 * kR : ((cl - 2) & 31) * kR;
  const int rvalid = ge_cta ? kT2 - 32 * kR : kR;

  if (warp >= 8) {
    asm volatile("setmaxnreg.dec.sync.aligned.u32 40;");
    if (warp > 8) {
      if (elect_one()) {
#pragma unroll
        for (int i = 0; i < 5; i++) if (57 + (warp - 9) * 5 + i < kBarG) init_bar(bars, 57 + (warp - 9) * 5 + i);
#pragma unroll
        for (int i = 0; i < 5; i++) if (kBarRH + (warp - 9) * 5 + i < kBarGW) mbar_init(bars + (kBarRH + (warp - 9) * 5 + i) * 8, 4);
        if (warp == 11) { mbar_init(bars + kBarGW * 8, 8); mbar_init(bars + kBarFO * 8, 8); mbar_init(bars + kBarGE * 8, 1); mbar_expect(bars + kBarGE * 8, kGEBytes); }
        asm volatile("fence.mbarrier_init.release.cluster;" ::: "memory");
      }
      __syncwarp();
      cluster_sync_relaxed();
      if (warp == 10 && ge_cta) {
        mbar_wait(bars + kBarGW * 8);
        if (elect_one()) {
          __threadfence();
          asm volatile("red.release.gpu.global.add.u32 [%0], 1;" ::"l"(&g_ge_flag[b]) : "memory");
        }
        __syncwarp();
      }
      if (warp > 9) return;
#pragma unroll
      for (int g = 0; g < 2; g++) {
        mbar_wait(bars + (kBarRH + g) * 8);
        if (elect_one()) {
          const uint32_t src = sb + kSlotH * kSlot + (2 * cta + g) * 8192;
          dsmem_copy(mapa(src, peer), src, 8192, mapa(bars + kBarHX * 8, peer));
        }
        __syncwarp();
      }
#pragma unroll
      for (int g = 0; g < 2; g++) {
        mbar_wait(bars + (kBarRF + g) * 8);
        if (elect_one()) {
          const uint32_t src = sb + kSlotF * kSlot + (2 * cta + g) * 4096;
          dsmem_copy(mapa(src, peer), src, 4096, mapa(bars + kBarFX * 8, peer));
        }
        __syncwarp();
      }
#pragma unroll
      for (int g = 0; g < 2; g++) {
        mbar_wait(bars + (kBarRE + g) * 8);
        if (elect_one())
          dsmem_copy(mapa(sb + kSlotFE * kSlot + (2 * cta + g) * 4096, peer), sb + kSlotH * kSlot + g * 4096, 4096, mapa(bars + kBarFE * 8, peer));
        __syncwarp();
      }
      {
        int nxt0 = ((int)cta * 16 < rvalid) ? 0 : 4, nxt1 = ((int)cta * 16 + 8 < rvalid) ? 0 : 4;
        const long long t0 = clock64();
        while ((nxt0 < 4 || nxt1 < 4) && clock64() - t0 < 8000000ll) {
#pragma unroll
          for (int g = 0; g < 2; g++) {
            const int j = g ? nxt1 : nxt0;
            if (j < 4 && mbar_test(bars + (kBarPR + g * 4 + j) * 8)) {
              if (elect_one()) {
                const int rl0 = cta * 16 + g * 8;
                tma_store_3d((rl0 + 8 <= rvalid) ? &P.out64 : &P.out56, sb + stage_off(g, j), 0, (b * kT2 + r0 + rl0) * 8, j);
                asm volatile("cp.async.bulk.commit_group;" ::: "memory");
              }
              __syncwarp();
              if (g) nxt1++; else nxt0++;
            }
          }
        }
        if (elect_one()) asm volatile("cp.async.bulk.wait_group.read 0;" ::: "memory");
        __syncwarp();
        TS(2, 11);
        GT(1);
      }
      return;
    }
    TS(2, 0);
    GT(0);
    unsigned int ticket = 0;
    const int par = cta == 0 ? 1 : 0;
    const int q0 = cta == 0 ? 2 * r0 - 2 : 2 * r0 - 1;
    if (elect_one()) {
      mbar_init(bars + kBarX * 8, 1); mbar_expect(bars + kBarX * 8, 16384);
      mbar_init(bars + kBarW * 8, 1); mbar_expect(bars + kBarW * 8, 16384);
      fence_async_smem();
      tma_load_4d(sb, &P.x, bars + kBarX * 8, 0, 1, 2 * r0 - 2, b);
      tma_load_4d(sb + 8192, &P.x, bars + kBarX * 8, 0, 0, 2 * r0 - 1, b);
      tma_load_3d(sb + unit_slot(0) * kSlot, &P.w1, bars + kBarW * 8, 0, 0, 2 * cta);
      {
        const int t_lo = max(4 * r0 - 3 + (int)cta * 64, 0), t_hi = min(4 * r0 - 3 + (int)cta * 64 + 64, 4000);
        if (t_hi > t_lo)
          asm volatile("cp.async.bulk.prefetch.L2.global [%0], %1;" ::"l"(reinterpret_cast<const char*>(P.xptr) + ((size_t)b * 4000 + t_lo) * 512), "r"((t_hi - t_lo) * 512) : "memory");
      }
      TS(2, 7);
#pragma unroll
      for (int i = 1; i < 9; i++) if (i != kBarW) { mbar_init(bars + i * 8, 1); mbar_expect(bars + i * 8, 16384); }
      if (ge_cta) { mbar_init(bars + kBarG * 8, 1); mbar_expect(bars + kBarG * 8, 4 * 16384 + 4096); mbar_init(bars + kBarP0 * 8, 8); }
      asm volatile("fence.mbarrier_init.release.cluster;" ::: "memory");
      fence_async_smem();
      TS(2, 8);
      if (ge_cta) {
        tma_load_3d(sb + kOffG, &P.g, bars + kBarG * 8, 0, b * 8, 0);
#pragma unroll
        for (int i = 0; i < 4; i++) tma_load_3d(sb + (9 + i) * kSlot, &P.wg, bars + kBarG * 8, 0, i * 64, 2 * cta);
      }
#pragma unroll
      for (int u = 1; u < 5; u++)
        tma_load_3d(sb + unit_slot(u) * kSlot, &P.w1, bars + (kBarW + u) * 8, 0, (u % 3) * 256 + (u / 3) * 64, 2 * cta);
      TS(2, 10);
    }
    __syncwarp();
    TS(2, 6);
    cluster_sync_relaxed();
    TS(2, 1);
    if (elect_one()) {
#pragma unroll
      for (int p = 1; p < XFIRST; p++)
        tma_load_4d_mc(sb + p * kSlot + cta * 8192, &P.x, bars + (kBarX + p) * 8, p * 64, par, q0, b, (uint16_t)3);
    }
    __syncwarp();
    if (lane == 0) ticket = atomicAdd(&g_cta_count, 1u);
#pragma unroll
    for (int p = XFIRST; p < 4; p++) {
      if (XSTEP == 1 || ((p - XFIRST) & 1) == 0) mbar_wait(bars + (kBarX + p - XFIRST) * 8);
      if (ge_cta && p == 3) mbar_wait(bars + kBarP0 * 8);
      if (elect_one())
        tma_load_4d_mc(sb + p * kSlot + cta * 8192, &P.x, bars + (kBarX + p) * 8, p * 64, par, q0, b, (uint16_t)3);
      __syncwarp();
    }
#pragma unroll
    for (int u = 5; u < 36; u++) {
      if (unit_wait(u) != unit_wait(u - 1)) mbar_wait(bars + (kBarE + unit_wait(u)) * 8);
      if (u == 27) ticket = __shfl_sync(0xffffffffu, ticket, 0);
      if (elect_one()) {
        const uint32_t dst = sb + unit_slot(u) * kSlot, bar = bars + (kBarW + u) * 8;
        if (u < 12) tma_load_3d(dst, &P.w1, bar, 0, (u % 3) * 256 + (u / 3) * 64, 2 * cta);
        else if (u < 24) tma_load_3d(dst, &P.w2, bar, 0, ((u - 12) % 3) * 256 + ((2 * cta + (u - 12) / 3) & 3) * 64, 2 * cta);
        else if (u < 28) tma_load_3d(dst, &P.wf, bar, 0, ((2 * cta + (u - 24)) & 3) * 64, 2 * cta);
        else tma_load_3d(dst, &P.wo, bar, 0, ((2 * cta + (u - 28)) & 3) * 64, ((u - 28) >> 2) * 2);
        if (u == 27) {
          const unsigned int want = (ticket / kNumCtas + 1u) * 2u;
          const long long t0 = clock64();
          unsigned int v;
          do {
            asm volatile("ld.acquire.gpu.global.u32 %0, [%1];" : "=r"(v) : "l"(&g_ge_flag[b]) : "memory");
          } while ((int)(v - want) < 0 && clock64() - t0 < 4000000ll);
          asm volatile("fence.proxy.async;" ::: "memory");
          bulk_load(sb + kOffGE, reinterpret_cast<const char*>(g_ge) + b * kGEBytes, kGEBytes, bars + kBarGE * 8);
        }
      }
      __syncwarp();
      if (u == 11) TS(2, 2);
      if (u == 23) TS(2, 3);
      if (u == 27) TS(2, 4);
      if (u == 35) TS(2, 5);
    }
  } else {
    asm volatile("setmaxnreg.inc.sync.aligned.u32 232;");
    const int wg = warp >> 2, w = warp & 3;
    const int gq = lane >> 2, q = lane & 3;
    const uint32_t panel = 2 * cta + wg;
    const int ch = panel * 64 + w * 16 + gq;
    const uint32_t dA = desc_lo(sb + wg * 8192, 8192);
    const uint32_t dB = desc_lo(sb, 16);
    const uint32_t dBo = desc_lo(sb + cta * 2 * 8192, 16), dBp = desc_lo(sb + (cta ^ 1) * 2 * 8192, 16);
    const uint32_t dFo = desc_lo(sb + cta * 2 * 4096, 16), dFp = desc_lo(sb + (cta ^ 1) * 2 * 4096, 16);
    if (elect_one()) {
#pragma unroll
      for (int i = 0; i < 6; i++) init_bar(bars, 9 + warp * 6 + i);
      asm volatile("fence.mbarrier_init.release.cluster;" ::: "memory");
    }
    __syncwarp();
    cluster_sync_relaxed();
    if (w == 0) TS(wg, 0);

    if (ge_cta) {
      float ga[4];
      mbar_wait(bars + kBarG * 8);
      wg_fence();
#pragma unroll
      for (int i = 0; i < 4; i++) {
#pragma unroll
        for (int s = 0; s < 4; s++)
          wgmma_ss_n8(ga, desc_at(dA, (9 + i) * kSlot + s * 2048), desc_at(dB, kOffG + i * 1024 + s * 32), (i | s) != 0);
      }
      wg_commit();
      wg_wait<0>();
      if (lane == 0) mbar_arrive(bars + kBarP0 * 8);
      float* gp = g_ge + b * (kGEBytes / 4) + ((ch & 7) >> 1) * (kGEPitch / 4) + (ch >> 4) * 4 + (ch & 1);
      gp[(2 * q) * 4 * (kGEPitch / 4)] = ga[0];
      gp[(2 * q + 1) * 4 * (kGEPitch / 4)] = ga[1];
      gp[(2 * q) * 4 * (kGEPitch / 4) + 2] = ga[2];
      gp[(2 * q + 1) * 4 * (kGEPitch / 4) + 2] = ga[3];
      __syncwarp();
      if (lane == 0) mbar_arrive(bars + kBarGW * 8);
    }

    {
      float acc[32];
#pragma unroll
      for (int u = 0; u < 12; u++) {
        const int p = u / 3, tap = u % 3;
        if (tap == 0) mbar_wait(bars + (kBarX + p) * 8);
        mbar_wait(bars + (kBarW + u) * 8);
        if (u == 0 && w == 0) TS(wg, 1);
        wg_fence();
#pragma unroll
        for (int s = 0; s < 4; s++)
          wgmma_ss_n64(acc, desc_at(dA, unit_slot(u) * kSlot + s * 2048),
                       desc_at(dB, p * kSlot + (tap == 1 ? 8192 : (tap == 2 ? 128 : 0)) + s * 32), (u | s) != 0);
        wg_commit();
        if (u > 0) {
          wg_wait<1>();
          if (lane == 0) mbar_arrive(bars + (kBarE + u - 1) * 8);
        }
      }
      wg_wait<0>();
      if (lane == 0) mbar_arrive(bars + (kBarE + 11) * 8);
      if (w == 0) TS(wg, 2);
      const uint32_t hp = sb + kSlotH * kSlot + panel * 8192;
      const int mi = lane >> 3, l8 = lane & 7;
#pragma unroll
      for (int jb = 0; jb < 8; jb += 2) {
        uint32_t r[4];
#pragma unroll
        for (int t = 0; t < 2; t++) {
          r[2 * t + 0] = pack_bf16(gelu_tanh(acc[4 * (jb + t) + 0]), gelu_tanh(acc[4 * (jb + t) + 1]));
          r[2 * t + 1] = pack_bf16(gelu_tanh(acc[4 * (jb + t) + 2]), gelu_tanh(acc[4 * (jb + t) + 3]));
        }
        const int n = 8 * (jb + (mi >> 1)) + l8;
        const int row = n >> 1, chunk = 2 * w + (mi & 1);
        stsm_x4_trans(hp + (n & 1) * 4096 + row * 128 + ((chunk ^ (row & 7)) << 4), r[0], r[1], r[2], r[3]);
      }
      fence_async_smem();
      __syncwarp();
      if (lane == 0) mbar_arrive(bars + (kBarRH + wg) * 8);
      mbar_wait(bars + kBarRH * 8);
      mbar_wait(bars + (kBarRH + 1) * 8);
      if (w == 0) TS(wg, 3);
    }
    {
      float acc[16];
#pragma unroll
      for (int v = 0; v < 12; v++) {
        const int i = v / 3, tap = v % 3;
        if (v == 6) { mbar_wait_cluster(bars + kBarHX * 8); if (w == 0) TS(wg, 4); }
        mbar_wait(bars + (kBarW + 12 + v) * 8);
        wg_fence();
#pragma unroll
        for (int s = 0; s < 4; s++)
          wgmma_ss_n32(acc, desc_at(dA, unit_slot(12 + v) * kSlot + s * 2048),
                       desc_at(i < 2 ? dBo : dBp, kSlotH * kSlot + (i & 1) * 8192 + (tap == 1 ? 4096 : (tap == 2 ? 128 : 0)) + s * 32), (v | s) != 0);
        wg_commit();
        if (v > 0) {
          wg_wait<1>();
          if (lane == 0) mbar_arrive(bars + (kBarE + 12 + v - 1) * 8);
        }
      }
      wg_wait<0>();
      if (lane == 0) mbar_arrive(bars + (kBarE + 23) * 8);
      if (w == 0) TS(wg, 5);
      const uint32_t fp = sb + kSlotF * kSlot + panel * 4096;
      const int mi = lane >> 3, l8 = lane & 7;
#pragma unroll
      for (int jb = 0; jb < 4; jb += 2) {
        uint32_t r[4];
#pragma unroll
        for (int t = 0; t < 2; t++) {
          r[2 * t + 0] = pack_bf16(gelu_tanh(acc[4 * (jb + t) + 0]), gelu_tanh(acc[4 * (jb + t) + 1]));
          r[2 * t + 1] = pack_bf16(gelu_tanh(acc[4 * (jb + t) + 2]), gelu_tanh(acc[4 * (jb + t) + 3]));
        }
        const int n = 8 * (jb + (mi >> 1)) + l8;
        const int chunk = 2 * w + (mi & 1);
        stsm_x4_trans(fp + n * 128 + ((chunk ^ (n & 7)) << 4), r[0], r[1], r[2], r[3]);
      }
      fence_async_smem();
      __syncwarp();
      if (lane == 0) mbar_arrive(bars + (kBarRF + wg) * 8);
      mbar_wait(bars + kBarRF * 8);
      mbar_wait(bars + (kBarRF + 1) * 8);
      if (w == 0) TS(wg, 6);
    }
    {
      float acc[16];
#pragma unroll
      for (int i = 0; i < 4; i++) {
        if (i == 2) { mbar_wait_cluster(bars + kBarFX * 8); if (w == 0) TS(wg, 7); }
        mbar_wait(bars + (kBarW + 24 + i) * 8);
        wg_fence();
#pragma unroll
        for (int s = 0; s < 4; s++)
          wgmma_ss_n32(acc, desc_at(dA, unit_slot(24 + i) * kSlot + s * 2048),
                       desc_at(i < 2 ? dFo : dFp, kSlotF * kSlot + (i & 1) * 4096 + s * 32), (i | s) != 0);
        wg_commit();
        if (i > 0) {
          wg_wait<1>();
          if (lane == 0) mbar_arrive(bars + (kBarE + 24 + i - 1) * 8);
        }
      }
      wg_wait<0>();
      if (w == 0) TS(wg, 8);
      const uint32_t qk = gq >> 1;
      const uint32_t off0 = qk * 128 + (((2 * w) ^ (2 * qk)) << 4) + (gq & 1) * 8;
      const uint32_t off1 = qk * 128 + (((2 * w + 1) ^ (2 * qk)) << 4) + (gq & 1) * 8;
      const uint32_t own = sb + kSlotFE * kSlot + panel * 4096;
      const uint32_t stg = sb + kSlotH * kSlot + wg * 4096;
#pragma unroll
      for (int jb = 0; jb < 4; jb++) {
        const uint32_t base = (((uint32_t)(jb >> 1) == cta) ? own : stg) + (4 * (jb & 1) + q) * 512;
        sts64(base + off0, acc[4 * jb + 0], acc[4 * jb + 1]);
        sts64(base + off1, acc[4 * jb + 2], acc[4 * jb + 3]);
      }
      fence_async_smem();
      __syncwarp();
      if (lane == 0) { mbar_arrive(bars + (kBarRE + wg) * 8); mbar_arrive(bars + kBarFO * 8); }
      if (w == 0) TS(wg, 9);
    }
    const int rl0 = cta * 16 + wg * 8;
    mbar_wait(bars + kBarFO * 8);
    mbar_wait(bars + kBarGE * 8);
    if (wg == 1) asm volatile("bar.sync 4, 256;" ::: "memory");
    if (rl0 < rvalid) {
      if (w == 0) TS(wg, 10);
      const uint32_t fe_row = sb + kSlotFE * kSlot + ((4 * wg + w) * 4 + q) * 128;
      const uint32_t fe_h[2] = {fe_row + cta * 8192, fe_row + (cta ^ 1) * 8192};
      const uint32_t ge_h[2] = {sb + kOffGE + lane * kGEPitch + cta * 128, sb + kOffGE + lane * kGEPitch + (cta ^ 1) * 128};
      const int mi = lane >> 3, l8 = lane & 7;
      const uint32_t st = sb + (16 * w + (mi & 1) * 8 + l8) * 128;
      uint32_t A[64];
      float acc[2][32];
      {
        constexpr int PD = 3;
        float4 fa[PD], fb[PD], gg[PD];
#pragma unroll
        for (int kk = 0; kk < 16 + PD; kk++) {
          if (kk >= PD) {
            const int k = kk - PD, sl = k % PD;
            A[4 * k + 0] = tanh2_pack(fa[sl].x + gg[sl].x, fa[sl].z + gg[sl].y);
            A[4 * k + 1] = tanh2_pack(fa[sl].y + gg[sl].x, fa[sl].w + gg[sl].y);
            A[4 * k + 2] = tanh2_pack(fb[sl].x + gg[sl].z, fb[sl].z + gg[sl].w);
            A[4 * k + 3] = tanh2_pack(fb[sl].y + gg[sl].z, fb[sl].w + gg[sl].w);
          }
          if (kk < 16) {
            const int sl = kk % PD;
            if (kk == 8) mbar_wait_cluster(bars + kBarFE * 8);
            fa[sl] = lds128(fe_h[kk >> 3] + ((kk >> 2) & 1) * 4096 + ((((kk & 3) * 2) ^ (2 * q)) << 4));
            fb[sl] = lds128(fe_h[kk >> 3] + ((kk >> 2) & 1) * 4096 + ((((kk & 3) * 2 + 1) ^ (2 * q)) << 4));
            gg[sl] = lds128(ge_h[kk >> 3] + (kk & 7) * 16);
          }
        }
      }
      asm volatile("barrier.cluster.arrive.relaxed.aligned;" ::: "memory");
#pragma unroll
      for (int kk = 0; kk < 16; kk++) {
        if ((kk & 3) == 0) { mbar_wait(bars + (kBarW + 28 + (kk >> 2)) * 8); wg_fence(); }
        wgmma_rs_n64(acc[0], A[4 * kk], A[4 * kk + 1], A[4 * kk + 2], A[4 * kk + 3],
                     desc_at(dB, unit_slot(28 + (kk >> 2)) * kSlot + (kk & 3) * 2048), kk != 0);
        if (kk == ARRK) bar_arrive_pred(wg == 0);
      }
      wg_commit();
      if (w == 0) TS(wg, 11);
#pragma unroll
      for (int j = 0; j < 4; j++) {
        const int jn = j + 1;
        if (jn == 2) {
#pragma unroll
          for (int i = 0; i < 4; i++) mbar_wait(bars + (kBarW + 32 + i) * 8);
        }
        if (j < 3) wg_fence();
        const uint32_t stj = st + (wg ? stage_off(1, j) : stage_off(0, j));
#pragma unroll
        for (int kk = 0; kk < 16; kk++) {
          if (j < 3)
            wgmma_rs_n64(acc[jn & 1], A[4 * kk], A[4 * kk + 1], A[4 * kk + 2], A[4 * kk + 3],
                         desc_at(dB, unit_slot(28 + (jn >> 1) * 4 + (kk >> 2)) * kSlot + (jn & 1) * 8192 + (kk & 3) * 2048), kk != 0);
          if (kk == 1) {
            if (j < 3) { wg_commit(); wg_wait<1>(); } else { wg_wait<0>(); }
          }
          if (kk >= 2 && kk < 10 && (kk & 1) == 0) {
            const int jb = kk - 2;
            const uint32_t r0_ = pack_bf16(acc[j & 1][4 * jb + 0], acc[j & 1][4 * jb + 1]), r1_ = pack_bf16(acc[j & 1][4 * jb + 2], acc[j & 1][4 * jb + 3]);
            const uint32_t r2_ = pack_bf16(acc[j & 1][4 * jb + 4], acc[j & 1][4 * jb + 5]), r3_ = pack_bf16(acc[j & 1][4 * jb + 6], acc[j & 1][4 * jb + 7]);
            stsm_x4(stj + (((jb + (mi >> 1)) ^ l8) << 4), r0_, r1_, r2_, r3_);
          }
          if (kk == 9) {
            fence_async_smem();
            __syncwarp();
            mbar_arrive_pred(bars + (kBarPR + wg * 4 + j) * 8, lane == 0);
          }
        }
        if (j < 3) wg_commit();
        if (j == 0 && w == 0) TS(wg, 12);
        if (j == 2 && w == 0) TS(wg, 13);
      }
      if (w == 0) TS(wg, 14);
    } else {
      if (wg == 0) asm volatile("bar.arrive 4, 256;" ::: "memory");
      mbar_wait_cluster(bars + kBarFE * 8);
      asm volatile("barrier.cluster.arrive.relaxed.aligned;" ::: "memory");
    }
    asm volatile("barrier.cluster.wait.aligned;" ::: "memory");
  }
}

typedef CUresult (*EncodeFn)(CUtensorMap*, CUtensorMapDataType, cuuint32_t, void*, const cuuint64_t*, const cuuint64_t*,
                             const cuuint32_t*, const cuuint32_t*, CUtensorMapInterleave, CUtensorMapSwizzle,
                             CUtensorMapL2promotion, CUtensorMapFloatOOBfill);

void make_map3(EncodeFn enc, CUtensorMap* tm, const void* ptr, uint64_t rows, uint32_t box_rows, uint32_t box_panels) {
  cuuint64_t gd[3] = {64, rows, 4};
  cuuint64_t gs[2] = {512, 128};
  cuuint32_t bd[3] = {64, box_rows, box_panels};
  cuuint32_t es[3] = {1, 1, 1};
  enc(tm, CU_TENSOR_MAP_DATA_TYPE_BFLOAT16, 3, const_cast<void*>(ptr), gd, gs, bd, es, CU_TENSOR_MAP_INTERLEAVE_NONE,
      CU_TENSOR_MAP_SWIZZLE_128B, CU_TENSOR_MAP_L2_PROMOTION_L2_256B, CU_TENSOR_MAP_FLOAT_OOB_FILL_NONE);
}

}

extern "C" void kernel_launch(void* const* d_in, const int* in_sizes, int n_in, void* d_out, int out_size) {
  static EncodeFn enc = nullptr;
  if (!enc) {
    cudaDriverEntryPointQueryResult qr;
    cudaGetDriverEntryPoint("cuTensorMapEncodeTiled", (void**)&enc, cudaEnableDefault, &qr);
    cudaFuncSetAttribute(rnnt_joint_kernel, cudaFuncAttributeMaxDynamicSharedMemorySize, kSmemBytes);
  }
  Params P;
  {
    cuuint64_t gd[4] = {256, 2, 2000, 2};
    cuuint64_t gs[3] = {512, 1024, 4000ull * 512};
    cuuint32_t bd[4] = {64, 1, 64, 1};
    cuuint32_t es[4] = {1, 1, 1, 1};
    enc(&P.x, CU_TENSOR_MAP_DATA_TYPE_BFLOAT16, 4, d_in[0], gd, gs, bd, es, CU_TENSOR_MAP_INTERLEAVE_NONE,
        CU_TENSOR_MAP_SWIZZLE_128B, XPROMO, CU_TENSOR_MAP_FLOAT_OOB_FILL_NONE);
  }
  P.xptr = d_in[0];
  make_map3(enc, &P.w1, d_in[1], 768, 64, 2);
  make_map3(enc, &P.w2, d_in[2], 768, 64, 2);
  make_map3(enc, &P.g, d_in[3], 16, 8, 4);
  make_map3(enc, &P.wf, d_in[4], 256, 64, 2);
  make_map3(enc, &P.wg, d_in[5], 256, 64, 2);
  make_map3(enc, &P.wo, d_in[6], 256, 64, 2);
  make_map3(enc, &P.out64, d_out, 16000, 64, 1);
  make_map3(enc, &P.out56, d_out, 16000, 56, 1);
  rnnt_joint_kernel<<<kNumCtas, kThreads, kSmemBytes>>>(P);
}
```

```cpp
#include <cuda_runtime.h>
#include <cuda_bf16.h>
#include <cuda.h>
#include <stdint.h>

#define ARRK 3
#define XBULK 0
#define XPREF 1
#define XFIRST 3
#define XSTEP 1
#define XPROMO CU_TENSOR_MAP_L2_PROMOTION_L2_128B
namespace {

constexpr int kT2 = 1000;
constexpr int kR = 31;
constexpr int kNumCtas = 132;
constexpr int kThreads = 384;
constexpr int kSlot = 16384;

constexpr int kSlotFE = 9, kSlotF = 10, kSlotH = 11;
constexpr int kOffG = 13 * kSlot;
constexpr int kOffGE = kOffG + 4096;
constexpr int kGEPitch = 272;
constexpr int kGEBytes = 32 * kGEPitch;
constexpr int kOffBar = kOffGE + kGEBytes;
constexpr int kBarX = 0;
constexpr int kBarW = 4;
constexpr int kBarE = 40;
constexpr int kBarHX = 67, kBarFX = 68, kBarFE = 69, kBarG = 70, kBarP0 = 71;
constexpr int kBarRH = 72, kBarRF = 74, kBarRE = 76;
constexpr int kBarPR = 78;
constexpr int kBarGW = 86;
constexpr int kBarFO = 87;
constexpr int kBarGE = 88;
constexpr int kNumBars = 89;
constexpr int kSmemBytes = kOffBar + kNumBars * 8 + 1024;

__device__ __align__(128) float g_ge[2 * kGEBytes / 4];
__device__ unsigned int g_ge_flag[2];
__device__ unsigned int g_cta_count;

#define TS(slot_, idx_) do {} while (0)
#define GT(idx_) do {} while (0)

__device__ __forceinline__ uint32_t smem_u32(const void* p) { return (uint32_t)__cvta_generic_to_shared(p); }
__device__ __forceinline__ void mbar_init(uint32_t a, uint32_t c) { asm volatile("mbarrier.init.shared.b64 [%0], %1;" ::"r"(a), "r"(c) : "memory"); }
__device__ __forceinline__ void mbar_expect(uint32_t a, uint32_t b) { asm volatile("mbarrier.arrive.expect_tx.shared.b64 _, [%0], %1;" ::"r"(a), "r"(b) : "memory"); }
__device__ __forceinline__ void mbar_arrive(uint32_t a) { asm volatile("mbarrier.arrive.shared.b64 _, [%0];" ::"r"(a) : "memory"); }
__device__ __forceinline__ void mbar_arrive_pred(uint32_t a, bool p) {
  asm volatile("{\n.reg .pred q;\nsetp.ne.u32 q, %1, 0;\n@q mbarrier.arrive.shared.b64 _, [%0];\n}\n" ::"r"(a), "r"((uint32_t)p) : "memory");
}
__device__ __forceinline__ void bar_arrive_pred(bool p) {
  asm volatile("{\n.reg .pred q;\nsetp.ne.u32 q, %0, 0;\n@q bar.arrive 4, 256;\n}\n" ::"r"((uint32_t)p) : "memory");
}
__device__ __forceinline__ bool mbar_try(uint32_t a) {
  uint32_t ok;
  asm volatile("{\n.reg .pred p;\nmbarrier.try_wait.parity.shared.b64 p, [%1], 0;\nselp.u32 %0, 1, 0, p;\n}\n" : "=r"(ok) : "r"(a) : "memory");
  return ok != 0;
}
__device__ __forceinline__ bool mbar_test(uint32_t a) {
  uint32_t ok;
  asm volatile("{\n.reg .pred p;\nmbarrier.test_wait.parity.shared.b64 p, [%1], 0;\nselp.u32 %0, 1, 0, p;\n}\n" : "=r"(ok) : "r"(a) : "memory");
  return ok != 0;
}
__device__ __forceinline__ bool mbar_try_cluster(uint32_t a) {
  uint32_t ok;
  asm volatile("{\n.reg .pred p;\nmbarrier.try_wait.parity.acquire.cluster.shared.b64 p, [%1], 0;\nselp.u32 %0, 1, 0, p;\n}\n" : "=r"(ok) : "r"(a) : "memory");
  return ok != 0;
}
__device__ __forceinline__ void mbar_wait_slow(uint32_t a) {
  const long long t0 = clock64();
  while (!mbar_try(a)) { if (clock64() - t0 > 4000000ll) break; }
}
__device__ __forceinline__ void mbar_wait_cluster_slow(uint32_t a) {
  const long long t0 = clock64();
  while (!mbar_try_cluster(a)) { if (clock64() - t0 > 4000000ll) break; }
}
__device__ __forceinline__ void mbar_wait(uint32_t a) { if (!mbar_try(a)) mbar_wait_slow(a); }
__device__ __forceinline__ void mbar_wait_cluster(uint32_t a) { if (!mbar_try_cluster(a)) mbar_wait_cluster_slow(a); }
__device__ __forceinline__ uint32_t mapa(uint32_t a, uint32_t r) { uint32_t d; asm volatile("mapa.shared::cluster.u32 %0, %1, %2;" : "=r"(d) : "r"(a), "r"(r)); return d; }
__device__ __forceinline__ bool elect_one() { uint32_t p; asm volatile("{\n.reg .pred P;\nelect.sync _|P, 0xffffffff;\nselp.u32 %0, 1, 0, P;\n}\n" : "=r"(p)); return p != 0; }
__device__ __forceinline__ void fence_async_smem() { asm volatile("fence.proxy.async.shared::cta;" ::: "memory"); }
__device__ __forceinline__ void bar_consumers() { asm volatile("bar.sync 1, 256;" ::: "memory"); }
__device__ __forceinline__ void bar_wg(int wg) { asm volatile("bar.sync %0, 128;" ::"r"(2 + wg) : "memory"); }
__device__ __forceinline__ void cluster_sync_relaxed() { asm volatile("barrier.cluster.arrive.relaxed.aligned;\nbarrier.cluster.wait.aligned;" ::: "memory"); }
__device__ __forceinline__ void wg_fence() { asm volatile("wgmma.fence.sync.aligned;" ::: "memory"); }
__device__ __forceinline__ void wg_commit() { asm volatile("wgmma.commit_group.sync.aligned;" ::: "memory"); }
template <int N> __device__ __forceinline__ void wg_wait() { asm volatile("wgmma.wait_group.sync.aligned %0;" ::"n"(N) : "memory"); }

__device__ __forceinline__ void tma_load_3d(uint32_t dst, const CUtensorMap* tm, uint32_t bar, int c0, int c1, int c2) {
  asm volatile("cp.async.bulk.tensor.3d.shared::cluster.global.mbarrier::complete_tx::bytes [%0], [%1, {%3, %4, %5}], [%2];"
               ::"r"(dst), "l"(tm), "r"(bar), "r"(c0), "r"(c1), "r"(c2) : "memory");
}
__device__ __forceinline__ void tma_load_4d(uint32_t dst, const CUtensorMap* tm, uint32_t bar, int c0, int c1, int c2, int c3) {
  asm volatile("cp.async.bulk.tensor.4d.shared::cluster.global.mbarrier::complete_tx::bytes [%0], [%1, {%3, %4, %5, %6}], [%2];"
               ::"r"(dst), "l"(tm), "r"(bar), "r"(c0), "r"(c1), "r"(c2), "r"(c3) : "memory");
}
__device__ __forceinline__ void tma_load_4d_mc(uint32_t dst, const CUtensorMap* tm, uint32_t bar, int c0, int c1, int c2, int c3, uint16_t mask) {
  asm volatile("cp.async.bulk.tensor.4d.shared::cluster.global.mbarrier::complete_tx::bytes.multicast::cluster [%0], [%1, {%3, %4, %5, %6}], [%2], %7;"
               ::"r"(dst), "l"(tm), "r"(bar), "r"(c0), "r"(c1), "r"(c2), "r"(c3), "h"(mask) : "memory");
}
__device__ __forceinline__ void tma_store_3d(const CUtensorMap* tm, uint32_t src, int c0, int c1, int c2) {
  asm volatile("cp.async.bulk.tensor.3d.global.shared::cta.bulk_group [%0, {%2, %3, %4}], [%1];"
               ::"l"(tm), "r"(src), "r"(c0), "r"(c1), "r"(c2) : "memory");
}
__device__ __forceinline__ void bulk_load(uint32_t dst, const void* src, uint32_t bytes, uint32_t bar) {
  asm volatile("cp.async.bulk.shared::cluster.global.mbarrier::complete_tx::bytes [%0], [%1], %2, [%3];"
               ::"r"(dst), "l"(src), "r"(bytes), "r"(bar) : "memory");
}
__device__ __forceinline__ void dsmem_copy(uint32_t dst_remote, uint32_t src, uint32_t bytes, uint32_t bar_remote) {
  asm volatile("cp.async.bulk.shared::cluster.shared::cta.mbarrier::complete_tx::bytes [%0], [%1], %2, [%3];"
               ::"r"(dst_remote), "r"(src), "r"(bytes), "r"(bar_remote) : "memory");
}
__device__ __forceinline__ void stsm_x4_trans(uint32_t addr, uint32_t r0, uint32_t r1, uint32_t r2, uint32_t r3) {
  asm volatile("stmatrix.sync.aligned.m8n8.x4.trans.shared.b16 [%0], {%1, %2, %3, %4};" ::"r"(addr), "r"(r0), "r"(r1), "r"(r2), "r"(r3) : "memory");
}
__device__ __forceinline__ void stsm_x4(uint32_t addr, uint32_t r0, uint32_t r1, uint32_t r2, uint32_t r3) {
  asm volatile("stmatrix.sync.aligned.m8n8.x4.shared.b16 [%0], {%1, %2, %3, %4};" ::"r"(addr), "r"(r0), "r"(r1), "r"(r2), "r"(r3) : "memory");
}
__device__ __forceinline__ float2 lds64(uint32_t a) { float2 v; asm volatile("ld.shared.v2.f32 {%0, %1}, [%2];" : "=f"(v.x), "=f"(v.y) : "r"(a) : "memory"); return v; }
__device__ __forceinline__ float4 lds128(uint32_t a) { float4 v; asm volatile("ld.shared.v4.f32 {%0, %1, %2, %3}, [%4];" : "=f"(v.x), "=f"(v.y), "=f"(v.z), "=f"(v.w) : "r"(a) : "memory"); return v; }
__device__ __forceinline__ void sts64(uint32_t a, float x, float y) { asm volatile("st.shared.v2.f32 [%0], {%1, %2};" ::"r"(a), "f"(x), "f"(y) : "memory"); }
__device__ __forceinline__ float tanh_fast(float x) { float y; asm("tanh.approx.f32 %0, %1;" : "=f"(y) : "f"(x)); return y; }
__device__ __forceinline__ uint32_t tanh2_pack(float lo, float hi) {
  uint32_t r;
  asm volatile("{\n.reg .f32 a, b;\ntanh.approx.f32 a, %1;\ntanh.approx.f32 b, %2;\ncvt.rn.bf16x2.f32 %0, b, a;\n}\n" : "=r"(r) : "f"(lo), "f"(hi));
  return r;
}
__device__ __forceinline__ uint32_t pack_bf16(float lo, float hi) { uint32_t r; asm("cvt.rn.bf16x2.f32 %0, %1, %2;" : "=r"(r) : "f"(hi), "f"(lo)); return r; }
__device__ __forceinline__ float gelu_tanh(float x) {
  const float k0 = 0.7978845608028654f, k1 = 0.7978845608028654f * 0.044715f;
  float u = x * fmaf(x * x, k1, k0);
  float hx = 0.5f * x;
  return fmaf(hx, tanh_fast(u), hx);
}
__device__ __forceinline__ uint64_t make_desc(uint32_t addr, uint32_t lbo, uint32_t sbo) {
  return (uint64_t)((addr & 0x3FFFF) >> 4) | ((uint64_t)(lbo >> 4) << 16) | ((uint64_t)(sbo >> 4) << 32) | ((uint64_t)1 << 62);
}

__device__ __forceinline__ uint32_t desc_lo(uint32_t addr, uint32_t lbo) { return ((addr & 0x3FFFF) >> 4) | ((lbo >> 4) << 16); }
__device__ __forceinline__ uint64_t desc_at(uint32_t lo, uint32_t off) { return ((uint64_t)0x40000040u << 32) | (uint64_t)(lo + (off >> 4)); }

__device__ __forceinline__ void wgmma_ss_n64(float (&d)[32], uint64_t da, uint64_t db, int scale_d) {
  asm volatile("{\n.reg .pred p;\nsetp.ne.b32 p, %34, 0;\n"
    "wgmma.mma_async.sync.aligned.m64n64k16.f32.bf16.bf16 {%0, %1, %2, %3, %4, %5, %6, %7, %8, %9, %10, %11, %12, %13, %14, %15, %16, %17, %18, %19, %20, %21, %22, %23, %24, %25, %26, %27, %28, %29, %30, %31}, %32, %33, p, 1, 1, 1, 0;\n}\n"
    : "+f"(d[0]), "+f"(d[1]), "+f"(d[2]), "+f"(d[3]), "+f"(d[4]), "+f"(d[5]), "+f"(d[6]), "+f"(d[7]), "+f"(d[8]), "+f"(d[9]), "+f"(d[10]), "+f"(d[11]), "+f"(d[12]), "+f"(d[13]), "+f"(d[14]), "+f"(d[15]), "+f"(d[16]), "+f"(d[17]), "+f"(d[18]), "+f"(d[19]), "+f"(d[20]), "+f"(d[21]), "+f"(d[22]), "+f"(d[23]), "+f"(d[24]), "+f"(d[25]), "+f"(d[26]), "+f"(d[27]), "+f"(d[28]), "+f"(d[29]), "+f"(d[30]), "+f"(d[31])
    : "l"(da), "l"(db), "r"(scale_d));
}

__device__ __forceinline__ void wgmma_ss_n32(float (&d)[16], uint64_t da, uint64_t db, int scale_d) {
  asm volatile("{\n.reg .pred p;\nsetp.ne.b32 p, %18, 0;\n"
    "wgmma.mma_async.sync.aligned.m64n32k16.f32.bf16.bf16 {%0, %1, %2, %3, %4, %5, %6, %7, %8, %9, %10, %11, %12, %13, %14, %15}, %16, %17, p, 1, 1, 1, 0;\n}\n"
    : "+f"(d[0]), "+f"(d[1]), "+f"(d[2]), "+f"(d[3]), "+f"(d[4]), "+f"(d[5]), "+f"(d[6]), "+f"(d[7]), "+f"(d[8]), "+f"(d[9]), "+f"(d[10]), "+f"(d[11]), "+f"(d[12]), "+f"(d[13]), "+f"(d[14]), "+f"(d[15])
    : "l"(da), "l"(db), "r"(scale_d));
}

__device__ __forceinline__ void wgmma_ss_n8(float (&d)[4], uint64_t da, uint64_t db, int scale_d) {
  asm volatile("{\n.reg .pred p;\nsetp.ne.b32 p, %6, 0;\n"
    "wgmma.mma_async.sync.aligned.m64n8k16.f32.bf16.bf16 {%0, %1, %2, %3}, %4, %5, p, 1, 1, 1, 0;\n}\n"
    : "+f"(d[0]), "+f"(d[1]), "+f"(d[2]), "+f"(d[3])
    : "l"(da), "l"(db), "r"(scale_d));
}

__device__ __forceinline__ void wgmma_rs_n64(float (&d)[32], uint32_t a0, uint32_t a1, uint32_t a2, uint32_t a3, uint64_t db, int scale_d) {
  asm volatile("{\n.reg .pred p;\nsetp.ne.b32 p, %37, 0;\n"
    "wgmma.mma_async.sync.aligned.m64n64k16.f32.bf16.bf16 {%0, %1, %2, %3, %4, %5, %6, %7, %8, %9, %10, %11, %12, %13, %14, %15, %16, %17, %18, %19, %20, %21, %22, %23, %24, %25, %26, %27, %28, %29, %30, %31}, {%32, %33, %34, %35}, %36, p, 1, 1, 1;\n}\n"
    : "+f"(d[0]), "+f"(d[1]), "+f"(d[2]), "+f"(d[3]), "+f"(d[4]), "+f"(d[5]), "+f"(d[6]), "+f"(d[7]), "+f"(d[8]), "+f"(d[9]), "+f"(d[10]), "+f"(d[11]), "+f"(d[12]), "+f"(d[13]), "+f"(d[14]), "+f"(d[15]), "+f"(d[16]), "+f"(d[17]), "+f"(d[18]), "+f"(d[19]), "+f"(d[20]), "+f"(d[21]), "+f"(d[22]), "+f"(d[23]), "+f"(d[24]), "+f"(d[25]), "+f"(d[26]), "+f"(d[27]), "+f"(d[28]), "+f"(d[29]), "+f"(d[30]), "+f"(d[31])
    : "r"(a0), "r"(a1), "r"(a2), "r"(a3), "l"(db), "r"(scale_d));
}

__host__ __device__ constexpr int unit_slot(int u) {
  constexpr int t[36] = {4, 5, 6, 7, 8, 4, 5, 6, 0, 7, 8, 4,  1, 5, 6, 0, 2, 7, 8, 4, 3, 1, 5, 6,
                         0, 2, 7, 8,  4, 3, 1, 5, 6, 0, 2, 7};
  return t[u];
}
__host__ __device__ constexpr int unit_wait(int u) {
  constexpr int t[36] = {-1, -1, -1, -1, -1, 0, 1, 2, 2, 3, 4, 5,  5, 6, 7, 8, 8, 9, 10, 11, 11, 12, 13, 14,
                         15, 16, 17, 18,  19, 20, 21, 22, 23, 24, 25, 26};
  return t[u];
}

__device__ __forceinline__ uint32_t stage_off(int g, int j) {
  return g == 0 ? (j < 2 ? 8 * kSlot + j * 8192 : 10 * kSlot + (j - 2) * 8192)
                : (j < 2 ? 12 * kSlot + j * 8192 : (j == 2 ? 11 * kSlot + 8192 : 9 * kSlot));
}

struct Params {
  CUtensorMap x, w1, w2, wf, wg, wo, g, out64, out56;
  const void* xptr;
};

__device__ __forceinline__ void init_bar(uint32_t bars, int i) {
  const uint32_t a = bars + i * 8;
  const bool is_e = (i >= kBarE && i < kBarE + 27);
  mbar_init(a, is_e ? 8 : 1);
  if (!is_e) {
    uint32_t bytes = 16384;
    if (i == kBarFX) bytes = 8192;
    if (i == kBarFE) bytes = 8192;
    mbar_expect(a, bytes);
  }
}

__global__ void __cluster_dims__(2, 1, 1) __launch_bounds__(kThreads, 1)
rnnt_joint_kernel(const __grid_constant__ Params P) {
  extern __shared__ uint8_t smem_raw[];
  const uint32_t sb = (smem_u32(smem_raw) + 1023u) & ~1023u;
  const uint32_t bars = sb + kOffBar;
  const int warp = threadIdx.x >> 5, lane = threadIdx.x & 31;
  uint32_t cta;
  asm volatile("mov.u32 %0, %%cluster_ctarank;" : "=r"(cta));
  const uint32_t peer = cta ^ 1u;
  const int cl = blockIdx.x >> 1;
  const bool ge_cta = cl < 2;
  const int b = ge_cta ? cl : ((cl - 2) >> 5);
  const int r0 = ge_cta ? 32 * kR : ((cl - 2) & 31) * kR;
  const int rvalid = ge_cta ? kT2 - 32 * kR : kR;

  if (warp >= 8) {
    asm volatile("setmaxnreg.dec.sync.aligned.u32 40;");
    if (warp > 8) {
      if (elect_one()) {
#pragma unroll
        for (int i = 0; i < 5; i++) if (57 + (warp - 9) * 5 + i < kBarG) init_bar(bars, 57 + (warp - 9) * 5 + i);
#pragma unroll
        for (int i = 0; i < 5; i++) if (kBarRH + (warp - 9) * 5 + i < kBarGW) mbar_init(bars + (kBarRH + (warp - 9) * 5 + i) * 8, 4);
        if (warp == 11) { mbar_init(bars + kBarGW * 8, 8); mbar_init(bars + kBarFO * 8, 8); mbar_init(bars + kBarGE * 8, 1); mbar_expect(bars + kBarGE * 8, kGEBytes); }
        asm volatile("fence.mbarrier_init.release.cluster;" ::: "memory");
      }
      __syncwarp();
      cluster_sync_relaxed();
      if (warp == 10 && ge_cta) {
        mbar_wait(bars + kBarGW * 8);
        if (elect_one()) {
          __threadfence();
          asm volatile("red.release.gpu.global.add.u32 [%0], 1;" ::"l"(&g_ge_flag[b]) : "memory");
        }
        __syncwarp();
      }
      if (warp > 9) return;
#pragma unroll
      for (int g = 0; g < 2; g++) {
        mbar_wait(bars + (kBarRH + g) * 8);
        if (elect_one()) {
          const uint32_t src = sb + kSlotH * kSlot + (2 * cta + g) * 8192;
          dsmem_copy(mapa(src, peer), src, 8192, mapa(bars + kBarHX * 8, peer));
        }
        __syncwarp();
      }
#pragma unroll
      for (int g = 0; g < 2; g++) {
        mbar_wait(bars + (kBarRF + g) * 8);
        if (elect_one()) {
          const uint32_t src = sb + kSlotF * kSlot + (2 * cta + g) * 4096;
          dsmem_copy(mapa(src, peer), src, 4096, mapa(bars + kBarFX * 8, peer));
        }
        __syncwarp();
      }
#pragma unroll
      for (int g = 0; g < 2; g++) {
        mbar_wait(bars + (kBarRE + g) * 8);
        if (elect_one())
          dsmem_copy(mapa(sb + kSlotFE * kSlot + (2 * cta + g) * 4096, peer), sb + kSlotH * kSlot + g * 4096, 4096, mapa(bars + kBarFE * 8, peer));
        __syncwarp();
      }
      {
        int nxt0 = ((int)cta * 16 < rvalid) ? 0 : 4, nxt1 = ((int)cta * 16 + 8 < rvalid) ? 0 : 4;
        const long long t0 = clock64();
        while ((nxt0 < 4 || nxt1 < 4) && clock64() - t0 < 8000000ll) {
#pragma unroll
          for (int g = 0; g < 2; g++) {
            const int j = g ? nxt1 : nxt0;
            if (j < 4 && mbar_test(bars + (kBarPR + g * 4 + j) * 8)) {
              if (elect_one()) {
                const int rl0 = cta * 16 + g * 8;
                tma_store_3d((rl0 + 8 <= rvalid) ? &P.out64 : &P.out56, sb + stage_off(g, j), 0, (b * kT2 + r0 + rl0) * 8, j);
                asm volatile("cp.async.bulk.commit_group;" ::: "memory");
              }
              __syncwarp();
              if (g) nxt1++; else nxt0++;
            }
          }
        }
        if (elect_one()) asm volatile("cp.async.bulk.wait_group.read 0;" ::: "memory");
        __syncwarp();
        TS(2, 11);
        GT(1);
      }
      return;
    }
    TS(2, 0);
    GT(0);
    unsigned int ticket = 0;
    const int par = cta == 0 ? 1 : 0;
    const int q0 = cta == 0 ? 2 * r0 - 2 : 2 * r0 - 1;
    if (elect_one()) {
      mbar_init(bars + kBarX * 8, 1); mbar_expect(bars + kBarX * 8, 16384);
      mbar_init(bars + kBarW * 8, 1); mbar_expect(bars + kBarW * 8, 16384);
      fence_async_smem();
      tma_load_4d(sb, &P.x, bars + kBarX * 8, 0, 1, 2 * r0 - 2, b);
      tma_load_4d(sb + 8192, &P.x, bars + kBarX * 8, 0, 0, 2 * r0 - 1, b);
      tma_load_3d(sb + unit_slot(0) * kSlot, &P.w1, bars + kBarW * 8, 0, 0, 2 * cta);
      TS(2, 7);
#pragma unroll
      for (int i = 1; i < 9; i++) if (i != kBarW) { mbar_init(bars + i * 8, 1); mbar_expect(bars + i * 8, 16384); }
      if (ge_cta) { mbar_init(bars + kBarG * 8, 1); mbar_expect(bars + kBarG * 8, 4 * 16384 + 4096); mbar_init(bars + kBarP0 * 8, 8); }
      asm volatile("fence.mbarrier_init.release.cluster;" ::: "memory");
      fence_async_smem();
      TS(2, 8);
      if (ge_cta) {
        tma_load_3d(sb + kOffG, &P.g, bars + kBarG * 8, 0, b * 8, 0);
#pragma unroll
        for (int i = 0; i < 4; i++) tma_load_3d(sb + (9 + i) * kSlot, &P.wg, bars + kBarG * 8, 0, i * 64, 2 * cta);
      }
#pragma unroll
      for (int u = 1; u < 5; u++)
        tma_load_3d(sb + unit_slot(u) * kSlot, &P.w1, bars + (kBarW + u) * 8, 0, (u % 3) * 256 + (u / 3) * 64, 2 * cta);
      TS(2, 10);
    }
    __syncwarp();
    TS(2, 6);
    cluster_sync_relaxed();
    TS(2, 1);
    if (elect_one()) {
#pragma unroll
      for (int p = 1; p < XFIRST; p++)
        tma_load_4d_mc(sb + p * kSlot + cta * 8192, &P.x, bars + (kBarX + p) * 8, p * 64, par, q0, b, (uint16_t)3);
    }
    __syncwarp();
    if (lane == 0) ticket = atomicAdd(&g_cta_count, 1u);
#pragma unroll
    for (int p = XFIRST; p < 4; p++) {
      if (XSTEP == 1 || ((p - XFIRST) & 1) == 0) mbar_wait(bars + (kBarX + p - XFIRST) * 8);
      if (ge_cta && p == 3) mbar_wait(bars + kBarP0 * 8);
      if (elect_one())
        tma_load_4d_mc(sb + p * kSlot + cta * 8192, &P.x, bars + (kBarX + p) * 8, p * 64, par, q0, b, (uint16_t)3);
      __syncwarp();
    }
#pragma unroll
    for (int u = 5; u < 36; u++) {
      if (unit_wait(u) != unit_wait(u - 1)) mbar_wait(bars + (kBarE + unit_wait(u)) * 8);
      if (u == 27) ticket = __shfl_sync(0xffffffffu, ticket, 0);
      if (elect_one()) {
        const uint32_t dst = sb + unit_slot(u) * kSlot, bar = bars + (kBarW + u) * 8;
        if (u < 12) tma_load_3d(dst, &P.w1, bar, 0, (u % 3) * 256 + (u / 3) * 64, 2 * cta);
        else if (u < 24) tma_load_3d(dst, &P.w2, bar, 0, ((u - 12) % 3) * 256 + ((2 * cta + (u - 12) / 3) & 3) * 64, 2 * cta);
        else if (u < 28) tma_load_3d(dst, &P.wf, bar, 0, ((2 * cta + (u - 24)) & 3) * 64, 2 * cta);
        else tma_load_3d(dst, &P.wo, bar, 0, ((2 * cta + (u - 28)) & 3) * 64, ((u - 28) >> 2) * 2);
        if (u == 27) {
          const unsigned int want = (ticket / kNumCtas + 1u) * 2u;
          const long long t0 = clock64();
          unsigned int v;
          do {
            asm volatile("ld.acquire.gpu.global.u32 %0, [%1];" : "=r"(v) : "l"(&g_ge_flag[b]) : "memory");
          } while ((int)(v - want) < 0 && clock64() - t0 < 4000000ll);
          asm volatile("fence.proxy.async;" ::: "memory");
          bulk_load(sb + kOffGE, reinterpret_cast<const char*>(g_ge) + b * kGEBytes, kGEBytes, bars + kBarGE * 8);
        }
      }
      __syncwarp();
      if (u == 11) TS(2, 2);
      if (u == 23) TS(2, 3);
      if (u == 27) TS(2, 4);
      if (u == 35) TS(2, 5);
    }
  } else {
    asm volatile("setmaxnreg.inc.sync.aligned.u32 232;");
    const int wg = warp >> 2, w = warp & 3;
    const int gq = lane >> 2, q = lane & 3;
    const uint32_t panel = 2 * cta + wg;
    const int ch = panel * 64 + w * 16 + gq;
    const uint32_t dA = desc_lo(sb + wg * 8192, 8192);
    const uint32_t dB = desc_lo(sb, 16);
    const uint32_t dBo = desc_lo(sb + cta * 2 * 8192, 16), dBp = desc_lo(sb + (cta ^ 1) * 2 * 8192, 16);
    const uint32_t dFo = desc_lo(sb + cta * 2 * 4096, 16), dFp = desc_lo(sb + (cta ^ 1) * 2 * 4096, 16);
    if (elect_one()) {
#pragma unroll
      for (int i = 0; i < 6; i++) init_bar(bars, 9 + warp * 6 + i);
      asm volatile("fence.mbarrier_init.release.cluster;" ::: "memory");
    }
    __syncwarp();
    cluster_sync_relaxed();
    if (w == 0) TS(wg, 0);

    if (ge_cta) {
      float ga[4];
      mbar_wait(bars + kBarG * 8);
      wg_fence();
#pragma unroll
      for (int i = 0; i < 4; i++) {
#pragma unroll
        for (int s = 0; s < 4; s++)
          wgmma_ss_n8(ga, desc_at(dA, (9 + i) * kSlot + s * 2048), desc_at(dB, kOffG + i * 1024 + s * 32), (i | s) != 0);
      }
      wg_commit();
      wg_wait<0>();
      if (lane == 0) mbar_arrive(bars + kBarP0 * 8);
      float* gp = g_ge + b * (kGEBytes / 4) + ((ch & 7) >> 1) * (kGEPitch / 4) + (ch >> 4) * 4 + (ch & 1);
      gp[(2 * q) * 4 * (kGEPitch / 4)] = ga[0];
      gp[(2 * q + 1) * 4 * (kGEPitch / 4)] = ga[1];
      gp[(2 * q) * 4 * (kGEPitch / 4) + 2] = ga[2];
      gp[(2 * q + 1) * 4 * (kGEPitch / 4) + 2] = ga[3];
      __syncwarp();
      if (lane == 0) mbar_arrive(bars + kBarGW * 8);
    }

    {
      float acc[32];
#pragma unroll
      for (int u = 0; u < 12; u++) {
        const int p = u / 3, tap = u % 3;
        if (tap == 0) mbar_wait(bars + (kBarX + p) * 8);
        mbar_wait(bars + (kBarW + u) * 8);
        if (u == 0 && w == 0) TS(wg, 1);
        wg_fence();
#pragma unroll
        for (int s = 0; s < 4; s++)
          wgmma_ss_n64(acc, desc_at(dA, unit_slot(u) * kSlot + s * 2048),
                       desc_at(dB, p * kSlot + (tap == 1 ? 8192 : (tap == 2 ? 128 : 0)) + s * 32), (u | s) != 0);
        wg_commit();
        if (u > 0) {
          wg_wait<1>();
          if (lane == 0) mbar_arrive(bars + (kBarE + u - 1) * 8);
        }
      }
      wg_wait<0>();
      if (lane == 0) mbar_arrive(bars + (kBarE + 11) * 8);
      if (w == 0) TS(wg, 2);
      const uint32_t hp = sb + kSlotH * kSlot + panel * 8192;
      const int mi = lane >> 3, l8 = lane & 7;
#pragma unroll
      for (int jb = 0; jb < 8; jb += 2) {
        uint32_t r[4];
#pragma unroll
        for (int t = 0; t < 2; t++) {
          r[2 * t + 0] = pack_bf16(gelu_tanh(acc[4 * (jb + t) + 0]), gelu_tanh(acc[4 * (jb + t) + 1]));
          r[2 * t + 1] = pack_bf16(gelu_tanh(acc[4 * (jb + t) + 2]), gelu_tanh(acc[4 * (jb + t) + 3]));
        }
        const int n = 8 * (jb + (mi >> 1)) + l8;
        const int row = n >> 1, chunk = 2 * w + (mi & 1);
        stsm_x4_trans(hp + (n & 1) * 4096 + row * 128 + ((chunk ^ (row & 7)) << 4), r[0], r[1], r[2], r[3]);
      }
      fence_async_smem();
      __syncwarp();
      if (lane == 0) mbar_arrive(bars + (kBarRH + wg) * 8);
      mbar_wait(bars + kBarRH * 8);
      mbar_wait(bars + (kBarRH + 1) * 8);
      if (w == 0) TS(wg, 3);
    }
    {
      float acc[16];
#pragma unroll
      for (int v = 0; v < 12; v++) {
        const int i = v / 3, tap = v % 3;
        if (v == 6) { mbar_wait_cluster(bars + kBarHX * 8); if (w == 0) TS(wg, 4); }
        mbar_wait(bars + (kBarW + 12 + v) * 8);
        wg_fence();
#pragma unroll
        for (int s = 0; s < 4; s++)
          wgmma_ss_n32(acc, desc_at(dA, unit_slot(12 + v) * kSlot + s * 2048),
                       desc_at(i < 2 ? dBo : dBp, kSlotH * kSlot + (i & 1) * 8192 + (tap == 1 ? 4096 : (tap == 2 ? 128 : 0)) + s * 32), (v | s) != 0);
        wg_commit();
        if (v > 0) {
          wg_wait<1>();
          if (lane == 0) mbar_arrive(bars + (kBarE + 12 + v - 1) * 8);
        }
      }
      wg_wait<0>();
      if (lane == 0) mbar_arrive(bars + (kBarE + 23) * 8);
      if (w == 0) TS(wg, 5);
      const uint32_t fp = sb + kSlotF * kSlot + panel * 4096;
      const int mi = lane >> 3, l8 = lane & 7;
#pragma unroll
      for (int jb = 0; jb < 4; jb += 2) {
        uint32_t r[4];
#pragma unroll
        for (int t = 0; t < 2; t++) {
          r[2 * t + 0] = pack_bf16(gelu_tanh(acc[4 * (jb + t) + 0]), gelu_tanh(acc[4 * (jb + t) + 1]));
          r[2 * t + 1] = pack_bf16(gelu_tanh(acc[4 * (jb + t) + 2]), gelu_tanh(acc[4 * (jb + t) + 3]));
        }
        const int n = 8 * (jb + (mi >> 1)) + l8;
        const int chunk = 2 * w + (mi & 1);
        stsm_x4_trans(fp + n * 128 + ((chunk ^ (n & 7)) << 4), r[0], r[1], r[2], r[3]);
      }
      fence_async_smem();
      __syncwarp();
      if (lane == 0) mbar_arrive(bars + (kBarRF + wg) * 8);
      mbar_wait(bars + kBarRF * 8);
      mbar_wait(bars + (kBarRF + 1) * 8);
      if (w == 0) TS(wg, 6);
    }
    {
      float acc[16];
#pragma unroll
      for (int i = 0; i < 4; i++) {
        if (i == 2) { mbar_wait_cluster(bars + kBarFX * 8); if (w == 0) TS(wg, 7); }
        mbar_wait(bars + (kBarW + 24 + i) * 8);
        wg_fence();
#pragma unroll
        for (int s = 0; s < 4; s++)
          wgmma_ss_n32(acc, desc_at(dA, unit_slot(24 + i) * kSlot + s * 2048),
                       desc_at(i < 2 ? dFo : dFp, kSlotF * kSlot + (i & 1) * 4096 + s * 32), (i | s) != 0);
        wg_commit();
        if (i > 0) {
          wg_wait<1>();
          if (lane == 0) mbar_arrive(bars + (kBarE + 24 + i - 1) * 8);
        }
      }
      wg_wait<0>();
      if (w == 0) TS(wg, 8);
      const uint32_t qk = gq >> 1;
      const uint32_t off0 = qk * 128 + (((2 * w) ^ (2 * qk)) << 4) + (gq & 1) * 8;
      const uint32_t off1 = qk * 128 + (((2 * w + 1) ^ (2 * qk)) << 4) + (gq & 1) * 8;
      const uint32_t own = sb + kSlotFE * kSlot + panel * 4096;
      const uint32_t stg = sb + kSlotH * kSlot + wg * 4096;
#pragma unroll
      for (int jb = 0; jb < 4; jb++) {
        const uint32_t base = (((uint32_t)(jb >> 1) == cta) ? own : stg) + (4 * (jb & 1) + q) * 512;
        sts64(base + off0, acc[4 * jb + 0], acc[4 * jb + 1]);
        sts64(base + off1, acc[4 * jb + 2], acc[4 * jb + 3]);
      }
      fence_async_smem();
      __syncwarp();
      if (lane == 0) { mbar_arrive(bars + (kBarRE + wg) * 8); mbar_arrive(bars + kBarFO * 8); }
      if (w == 0) TS(wg, 9);
    }
    const int rl0 = cta * 16 + wg * 8;
    mbar_wait(bars + kBarFO * 8);
    mbar_wait(bars + kBarGE * 8);
    if (wg == 1) asm volatile("bar.sync 4, 256;" ::: "memory");
    if (rl0 < rvalid) {
      if (w == 0) TS(wg, 10);
      const uint32_t fe_row = sb + kSlotFE * kSlot + ((4 * wg + w) * 4 + q) * 128;
      const uint32_t fe_h[2] = {fe_row + cta * 8192, fe_row + (cta ^ 1) * 8192};
      const uint32_t ge_h[2] = {sb + kOffGE + lane * kGEPitch + cta * 128, sb + kOffGE + lane * kGEPitch + (cta ^ 1) * 128};
      const int mi = lane >> 3, l8 = lane & 7;
      const uint32_t st = sb + (16 * w + (mi & 1) * 8 + l8) * 128;
      uint32_t A[64];
      float acc[2][32];
#pragma unroll
      for (int hf = 0; hf < 2; hf++) {
        constexpr int PD = 3;
        float4 fa[PD], fb[PD], gg[PD];
        if (hf == 1) {
          mbar_wait_cluster(bars + kBarFE * 8);
          asm volatile("barrier.cluster.arrive.relaxed.aligned;" ::: "memory");
        }
#pragma unroll
        for (int kk = 0; kk < 8 + PD; kk++) {
          if (kk >= PD) {
            const int k = hf * 8 + kk - PD, sl = (kk - PD) % PD;
            A[4 * k + 0] = tanh2_pack(fa[sl].x + gg[sl].x, fa[sl].z + gg[sl].y);
            A[4 * k + 1] = tanh2_pack(fa[sl].y + gg[sl].x, fa[sl].w + gg[sl].y);
            A[4 * k + 2] = tanh2_pack(fb[sl].x + gg[sl].z, fb[sl].z + gg[sl].w);
            A[4 * k + 3] = tanh2_pack(fb[sl].y + gg[sl].z, fb[sl].w + gg[sl].w);
          }
          if (kk < 8) {
            const int sl = kk % PD;
            fa[sl] = lds128(fe_h[hf] + (kk >> 2) * 4096 + ((((kk & 3) * 2) ^ (2 * q)) << 4));
            fb[sl] = lds128(fe_h[hf] + (kk >> 2) * 4096 + ((((kk & 3) * 2 + 1) ^ (2 * q)) << 4));
            gg[sl] = lds128(ge_h[hf] + kk * 16);
          }
        }
        mbar_wait(bars + (kBarW + 28 + 2 * hf) * 8);
        mbar_wait(bars + (kBarW + 29 + 2 * hf) * 8);
        wg_fence();
#pragma unroll
        for (int k8 = 0; k8 < 8; k8++) {
          const int kk = hf * 8 + k8;
          wgmma_rs_n64(acc[0], A[4 * kk], A[4 * kk + 1], A[4 * kk + 2], A[4 * kk + 3],
                       desc_at(dB, unit_slot(28 + (kk >> 2)) * kSlot + (kk & 3) * 2048), kk != 0);
        }
        wg_commit();
      }
      bar_arrive_pred(wg == 0);
      wg_wait<0>();
#pragma unroll
      for (int jb = 0; jb < 8; jb += 2) {
        const uint32_t r0_ = pack_bf16(acc[0][4 * jb + 0], acc[0][4 * jb + 1]), r1_ = pack_bf16(acc[0][4 * jb + 2], acc[0][4 * jb + 3]);
        const uint32_t r2_ = pack_bf16(acc[0][4 * jb + 4], acc[0][4 * jb + 5]), r3_ = pack_bf16(acc[0][4 * jb + 6], acc[0][4 * jb + 7]);
        stsm_x4(st + (wg ? stage_off(1, 0) : stage_off(0, 0)) + (((jb + (mi >> 1)) ^ l8) << 4), r0_, r1_, r2_, r3_);
      }
      fence_async_smem();
      __syncwarp();
      mbar_arrive_pred(bars + (kBarPR + wg * 4) * 8, lane == 0);
      if (w == 0) TS(wg, 11);
#pragma unroll
      for (int j = 0; j < 4; j++) {
        const int jn = j + 1;
        if (jn == 2) {
#pragma unroll
          for (int i = 0; i < 4; i++) mbar_wait(bars + (kBarW + 32 + i) * 8);
        }
        if (j < 3) wg_fence();
        const uint32_t stj = st + (wg ? stage_off(1, j) : stage_off(0, j));
#pragma unroll
        for (int kk = 0; kk < 16; kk++) {
          if (j < 3)
            wgmma_rs_n64(acc[jn & 1], A[4 * kk], A[4 * kk + 1], A[4 * kk + 2], A[4 * kk + 3],
                         desc_at(dB, unit_slot(28 + (jn >> 1) * 4 + (kk >> 2)) * kSlot + (jn & 1) * 8192 + (kk & 3) * 2048), kk != 0);
          if (kk == 1 && j > 0) {
            if (j < 3) { wg_commit(); wg_wait<1>(); } else { wg_wait<0>(); }
          }
          if (j > 0 && kk >= 2 && kk < 10 && (kk & 1) == 0) {
            const int jb = kk - 2;
            const uint32_t r0_ = pack_bf16(acc[j & 1][4 * jb + 0], acc[j & 1][4 * jb + 1]), r1_ = pack_bf16(acc[j & 1][4 * jb + 2], acc[j & 1][4 * jb + 3]);
            const uint32_t r2_ = pack_bf16(acc[j & 1][4 * jb + 4], acc[j & 1][4 * jb + 5]), r3_ = pack_bf16(acc[j & 1][4 * jb + 6], acc[j & 1][4 * jb + 7]);
            stsm_x4(stj + (((jb + (mi >> 1)) ^ l8) << 4), r0_, r1_, r2_, r3_);
          }
          if (j > 0 && kk == 9) {
            fence_async_smem();
            __syncwarp();
            mbar_arrive_pred(bars + (kBarPR + wg * 4 + j) * 8, lane == 0);
          }
        }
        if (j < 3) wg_commit();
        if (j == 0 && w == 0) TS(wg, 12);
        if (j == 2 && w == 0) TS(wg, 13);
      }
      if (w == 0) TS(wg, 14);
    } else {
      if (wg == 0) asm volatile("bar.arrive 4, 256;" ::: "memory");
      mbar_wait_cluster(bars + kBarFE * 8);
      asm volatile("barrier.cluster.arrive.relaxed.aligned;" ::: "memory");
    }
    asm volatile("barrier.cluster.wait.aligned;" ::: "memory");
  }
}

typedef CUresult (*EncodeFn)(CUtensorMap*, CUtensorMapDataType, cuuint32_t, void*, const cuuint64_t*, const cuuint64_t*,
                             const cuuint32_t*, const cuuint32_t*, CUtensorMapInterleave, CUtensorMapSwizzle,
                             CUtensorMapL2promotion, CUtensorMapFloatOOBfill);

void make_map3(EncodeFn enc, CUtensorMap* tm, const void* ptr, uint64_t rows, uint32_t box_rows, uint32_t box_panels) {
  cuuint64_t gd[3] = {64, rows, 4};
  cuuint64_t gs[2] = {512, 128};
  cuuint32_t bd[3] = {64, box_rows, box_panels};
  cuuint32_t es[3] = {1, 1, 1};
  enc(tm, CU_TENSOR_MAP_DATA_TYPE_BFLOAT16, 3, const_cast<void*>(ptr), gd, gs, bd, es, CU_TENSOR_MAP_INTERLEAVE_NONE,
      CU_TENSOR_MAP_SWIZZLE_128B, CU_TENSOR_MAP_L2_PROMOTION_L2_256B, CU_TENSOR_MAP_FLOAT_OOB_FILL_NONE);
}

}

extern "C" void kernel_launch(void* const* d_in, const int* in_sizes, int n_in, void* d_out, int out_size) {
  static EncodeFn enc = nullptr;
  if (!enc) {
    cudaDriverEntryPointQueryResult qr;
    cudaGetDriverEntryPoint("cuTensorMapEncodeTiled", (void**)&enc, cudaEnableDefault, &qr);
    cudaFuncSetAttribute(rnnt_joint_kernel, cudaFuncAttributeMaxDynamicSharedMemorySize, kSmemBytes);
  }
  Params P;
  {
    cuuint64_t gd[4] = {256, 2, 2000, 2};
    cuuint64_t gs[3] = {512, 1024, 4000ull * 512};
    cuuint32_t bd[4] = {64, 1, 64, 1};
    cuuint32_t es[4] = {1, 1, 1, 1};
    enc(&P.x, CU_TENSOR_MAP_DATA_TYPE_BFLOAT16, 4, d_in[0], gd, gs, bd, es, CU_TENSOR_MAP_INTERLEAVE_NONE,
        CU_TENSOR_MAP_SWIZZLE_128B, XPROMO, CU_TENSOR_MAP_FLOAT_OOB_FILL_NONE);
  }
  P.xptr = d_in[0];
  make_map3(enc, &P.w1, d_in[1], 768, 64, 2);
  make_map3(enc, &P.w2, d_in[2], 768, 64, 2);
  make_map3(enc, &P.g, d_in[3], 16, 8, 4);
  make_map3(enc, &P.wf, d_in[4], 256, 64, 2);
  make_map3(enc, &P.wg, d_in[5], 256, 64, 2);
  make_map3(enc, &P.wo, d_in[6], 256, 64, 2);
  make_map3(enc, &P.out64, d_out, 16000, 64, 1);
  make_map3(enc, &P.out56, d_out, 16000, 56, 1);
  rnnt_joint_kernel<<<kNumCtas, kThreads, kSmemBytes>>>(P);
}
```

```cpp
#include <cuda_runtime.h>
#include <cuda_bf16.h>
#include <cuda.h>
#include <stdint.h>

#define ARRK 3
#define XBULK 0
#define XPREF 1
#define XFIRST 3
#define XSTEP 1
#define XPROMO CU_TENSOR_MAP_L2_PROMOTION_L2_128B
namespace {

constexpr int kT2 = 1000;
constexpr int kR = 31;
constexpr int kNumCtas = 132;
constexpr int kThreads = 384;
constexpr int kSlot = 16384;

constexpr int kSlotFE = 9, kSlotF = 10, kSlotH = 11;
constexpr int kOffG = 13 * kSlot;
constexpr int kOffGE = kOffG + 4096;
constexpr int kGEPitch = 272;
constexpr int kGEBytes = 32 * kGEPitch;
constexpr int kOffBar = kOffGE + kGEBytes;
constexpr int kBarX = 0;
constexpr int kBarW = 4;
constexpr int kBarE = 40;
constexpr int kBarHX = 67, kBarFX = 68, kBarFE = 69, kBarG = 70, kBarP0 = 71;
constexpr int kBarRH = 72, kBarRF = 74, kBarRE = 76;
constexpr int kBarPR = 78;
constexpr int kBarGW = 86;
constexpr int kBarFO = 87;
constexpr int kBarGE = 88;
constexpr int kNumBars = 89;
constexpr int kSmemBytes = kOffBar + kNumBars * 8 + 1024;

__device__ __align__(128) float g_ge[2 * kGEBytes / 4];
__device__ unsigned int g_ge_flag[2];
__device__ unsigned int g_cta_count;

#define TS(slot_, idx_) do {} while (0)
#define GT(idx_) do {} while (0)

__device__ __forceinline__ uint32_t smem_u32(const void* p) { return (uint32_t)__cvta_generic_to_shared(p); }
__device__ __forceinline__ void mbar_init(uint32_t a, uint32_t c) { asm volatile("mbarrier.init.shared.b64 [%0], %1;" ::"r"(a), "r"(c) : "memory"); }
__device__ __forceinline__ void mbar_expect(uint32_t a, uint32_t b) { asm volatile("mbarrier.arrive.expect_tx.shared.b64 _, [%0], %1;" ::"r"(a), "r"(b) : "memory"); }
__device__ __forceinline__ void mbar_arrive(uint32_t a) { asm volatile("mbarrier.arrive.shared.b64 _, [%0];" ::"r"(a) : "memory"); }
__device__ __forceinline__ void mbar_arrive_pred(uint32_t a, bool p) {
  asm volatile("{\n.reg .pred q;\nsetp.ne.u32 q, %1, 0;\n@q mbarrier.arrive.shared.b64 _, [%0];\n}\n" ::"r"(a), "r"((uint32_t)p) : "memory");
}
__device__ __forceinline__ void bar_arrive_pred(bool p) {
  asm volatile("{\n.reg .pred q;\nsetp.ne.u32 q, %0, 0;\n@q bar.arrive 4, 256;\n}\n" ::"r"((uint32_t)p) : "memory");
}
__device__ __forceinline__ bool mbar_try(uint32_t a) {
  uint32_t ok;
  asm volatile("{\n.reg .pred p;\nmbarrier.try_wait.parity.shared.b64 p, [%1], 0;\nselp.u32 %0, 1, 0, p;\n}\n" : "=r"(ok) : "r"(a) : "memory");
  return ok != 0;
}
__device__ __forceinline__ bool mbar_test(uint32_t a) {
  uint32_t ok;
  asm volatile("{\n.reg .pred p;\nmbarrier.test_wait.parity.shared.b64 p, [%1], 0;\nselp.u32 %0, 1, 0, p;\n}\n" : "=r"(ok) : "r"(a) : "memory");
  return ok != 0;
}
__device__ __forceinline__ bool mbar_try_cluster(uint32_t a) {
  uint32_t ok;
  asm volatile("{\n.reg .pred p;\nmbarrier.try_wait.parity.acquire.cluster.shared.b64 p, [%1], 0;\nselp.u32 %0, 1, 0, p;\n}\n" : "=r"(ok) : "r"(a) : "memory");
  return ok != 0;
}
__device__ __forceinline__ void mbar_wait_slow(uint32_t a) {
  const long long t0 = clock64();
  while (!mbar_try(a)) { if (clock64() - t0 > 4000000ll) break; }
}
__device__ __forceinline__ void mbar_wait_cluster_slow(uint32_t a) {
  const long long t0 = clock64();
  while (!mbar_try_cluster(a)) { if (clock64() - t0 > 4000000ll) break; }
}
__device__ __forceinline__ void mbar_wait(uint32_t a) { if (!mbar_try(a)) mbar_wait_slow(a); }
__device__ __forceinline__ void mbar_wait_cluster(uint32_t a) { if (!mbar_try_cluster(a)) mbar_wait_cluster_slow(a); }
__device__ __forceinline__ uint32_t mapa(uint32_t a, uint32_t r) { uint32_t d; asm volatile("mapa.shared::cluster.u32 %0, %1, %2;" : "=r"(d) : "r"(a), "r"(r)); return d; }
__device__ __forceinline__ bool elect_one() { uint32_t p; asm volatile("{\n.reg .pred P;\nelect.sync _|P, 0xffffffff;\nselp.u32 %0, 1, 0, P;\n}\n" : "=r"(p)); return p != 0; }
__device__ __forceinline__ void fence_async_smem() { asm volatile("fence.proxy.async.shared::cta;" ::: "memory"); }
__device__ __forceinline__ void bar_consumers() { asm volatile("bar.sync 1, 256;" ::: "memory"); }
__device__ __forceinline__ void bar_wg(int wg) { asm volatile("bar.sync %0, 128;" ::"r"(2 + wg) : "memory"); }
__device__ __forceinline__ void cluster_sync_relaxed() { asm volatile("barrier.cluster.arrive.relaxed.aligned;\nbarrier.cluster.wait.aligned;" ::: "memory"); }
__device__ __forceinline__ void wg_fence() { asm volatile("wgmma.fence.sync.aligned;" ::: "memory"); }
__device__ __forceinline__ void wg_commit() { asm volatile("wgmma.commit_group.sync.aligned;" ::: "memory"); }
template <int N> __device__ __forceinline__ void wg_wait() { asm volatile("wgmma.wait_group.sync.aligned %0;" ::"n"(N) : "memory"); }

__device__ __forceinline__ void tma_load_3d(uint32_t dst, const CUtensorMap* tm, uint32_t bar, int c0, int c1, int c2) {
  asm volatile("cp.async.bulk.tensor.3d.shared::cluster.global.mbarrier::complete_tx::bytes [%0], [%1, {%3, %4, %5}], [%2];"
               ::"r"(dst), "l"(tm), "r"(bar), "r"(c0), "r"(c1), "r"(c2) : "memory");
}
__device__ __forceinline__ void tma_load_4d(uint32_t dst, const CUtensorMap* tm, uint32_t bar, int c0, int c1, int c2, int c3) {
  asm volatile("cp.async.bulk.tensor.4d.shared::cluster.global.mbarrier::complete_tx::bytes [%0], [%1, {%3, %4, %5, %6}], [%2];"
               ::"r"(dst), "l"(tm), "r"(bar), "r"(c0), "r"(c1), "r"(c2), "r"(c3) : "memory");
}
__device__ __forceinline__ void tma_load_4d_mc(uint32_t dst, const CUtensorMap* tm, uint32_t bar, int c0, int c1, int c2, int c3, uint16_t mask) {
  asm volatile("cp.async.bulk.tensor.4d.shared::cluster.global.mbarrier::complete_tx::bytes.multicast::cluster [%0], [%1, {%3, %4, %5, %6}], [%2], %7;"
               ::"r"(dst), "l"(tm), "r"(bar), "r"(c0), "r"(c1), "r"(c2), "r"(c3), "h"(mask) : "memory");
}
__device__ __forceinline__ void tma_store_3d(const CUtensorMap* tm, uint32_t src, int c0, int c1, int c2) {
  asm volatile("cp.async.bulk.tensor.3d.global.shared::cta.bulk_group [%0, {%2, %3, %4}], [%1];"
               ::"l"(tm), "r"(src), "r"(c0), "r"(c1), "r"(c2) : "memory");
}
__device__ __forceinline__ void bulk_load(uint32_t dst, const void* src, uint32_t bytes, uint32_t bar) {
  asm volatile("cp.async.bulk.shared::cluster.global.mbarrier::complete_tx::bytes [%0], [%1], %2, [%3];"
               ::"r"(dst), "l"(src), "r"(bytes), "r"(bar) : "memory");
}
__device__ __forceinline__ void dsmem_copy(uint32_t dst_remote, uint32_t src, uint32_t bytes, uint32_t bar_remote) {
  asm volatile("cp.async.bulk.shared::cluster.shared::cta.mbarrier::complete_tx::bytes [%0], [%1], %2, [%3];"
               ::"r"(dst_remote), "r"(src), "r"(bytes), "r"(bar_remote) : "memory");
}
__device__ __forceinline__ void stsm_x4_trans(uint32_t addr, uint32_t r0, uint32_t r1, uint32_t r2, uint32_t r3) {
  asm volatile("stmatrix.sync.aligned.m8n8.x4.trans.shared.b16 [%0], {%1, %2, %3, %4};" ::"r"(addr), "r"(r0), "r"(r1), "r"(r2), "r"(r3) : "memory");
}
__device__ __forceinline__ void stsm_x4(uint32_t addr, uint32_t r0, uint32_t r1, uint32_t r2, uint32_t r3) {
  asm volatile("stmatrix.sync.aligned.m8n8.x4.shared.b16 [%0], {%1, %2, %3, %4};" ::"r"(addr), "r"(r0), "r"(r1), "r"(r2), "r"(r3) : "memory");
}
__device__ __forceinline__ float2 lds64(uint32_t a) { float2 v; asm volatile("ld.shared.v2.f32 {%0, %1}, [%2];" : "=f"(v.x), "=f"(v.y) : "r"(a) : "memory"); return v; }
__device__ __forceinline__ float4 lds128(uint32_t a) { float4 v; asm volatile("ld.shared.v4.f32 {%0, %1, %2, %3}, [%4];" : "=f"(v.x), "=f"(v.y), "=f"(v.z), "=f"(v.w) : "r"(a) : "memory"); return v; }
__device__ __forceinline__ void sts64(uint32_t a, float x, float y) { asm volatile("st.shared.v2.f32 [%0], {%1, %2};" ::"r"(a), "f"(x), "f"(y) : "memory"); }
__device__ __forceinline__ float tanh_fast(float x) { float y; asm("tanh.approx.f32 %0, %1;" : "=f"(y) : "f"(x)); return y; }
__device__ __forceinline__ uint32_t tanh2_pack(float lo, float hi) {
  uint32_t r;
  asm volatile("{\n.reg .f32 a, b;\ntanh.approx.f32 a, %1;\ntanh.approx.f32 b, %2;\ncvt.rn.bf16x2.f32 %0, b, a;\n}\n" : "=r"(r) : "f"(lo), "f"(hi));
  return r;
}
__device__ __forceinline__ uint32_t pack_bf16(float lo, float hi) { uint32_t r; asm("cvt.rn.bf16x2.f32 %0, %1, %2;" : "=r"(r) : "f"(hi), "f"(lo)); return r; }
__device__ __forceinline__ float gelu_tanh(float x) {
  const float k0 = 0.7978845608028654f, k1 = 0.7978845608028654f * 0.044715f;
  float u = x * fmaf(x * x, k1, k0);
  float hx = 0.5f * x;
  return fmaf(hx, tanh_fast(u), hx);
}
__device__ __forceinline__ uint64_t make_desc(uint32_t addr, uint32_t lbo, uint32_t sbo) {
  return (uint64_t)((addr & 0x3FFFF) >> 4) | ((uint64_t)(lbo >> 4) << 16) | ((uint64_t)(sbo >> 4) << 32) | ((uint64_t)1 << 62);
}

__device__ __forceinline__ uint32_t desc_lo(uint32_t addr, uint32_t lbo) { return ((addr & 0x3FFFF) >> 4) | ((lbo >> 4) << 16); }
__device__ __forceinline__ uint64_t desc_at(uint32_t lo, uint32_t off) { return ((uint64_t)0x40000040u << 32) | (uint64_t)(lo + (off >> 4)); }

__device__ __forceinline__ void wgmma_ss_n64(float (&d)[32], uint64_t da, uint64_t db, int scale_d) {
  asm volatile("{\n.reg .pred p;\nsetp.ne.b32 p, %34, 0;\n"
    "wgmma.mma_async.sync.aligned.m64n64k16.f32.bf16.bf16 {%0, %1, %2, %3, %4, %5, %6, %7, %8, %9, %10, %11, %12, %13, %14, %15, %16, %17, %18, %19, %20, %21, %22, %23, %24, %25, %26, %27, %28, %29, %30, %31}, %32, %33, p, 1, 1, 1, 0;\n}\n"
    : "+f"(d[0]), "+f"(d[1]), "+f"(d[2]), "+f"(d[3]), "+f"(d[4]), "+f"(d[5]), "+f"(d[6]), "+f"(d[7]), "+f"(d[8]), "+f"(d[9]), "+f"(d[10]), "+f"(d[11]), "+f"(d[12]), "+f"(d[13]), "+f"(d[14]), "+f"(d[15]), "+f"(d[16]), "+f"(d[17]), "+f"(d[18]), "+f"(d[19]), "+f"(d[20]), "+f"(d[21]), "+f"(d[22]), "+f"(d[23]), "+f"(d[24]), "+f"(d[25]), "+f"(d[26]), "+f"(d[27]), "+f"(d[28]), "+f"(d[29]), "+f"(d[30]), "+f"(d[31])
    : "l"(da), "l"(db), "r"(scale_d));
}

__device__ __forceinline__ void wgmma_ss_n32(float (&d)[16], uint64_t da, uint64_t db, int scale_d) {
  asm volatile("{\n.reg .pred p;\nsetp.ne.b32 p, %18, 0;\n"
    "wgmma.mma_async.sync.aligned.m64n32k16.f32.bf16.bf16 {%0, %1, %2, %3, %4, %5, %6, %7, %8, %9, %10, %11, %12, %13, %14, %15}, %16, %17, p, 1, 1, 1, 0;\n}\n"
    : "+f"(d[0]), "+f"(d[1]), "+f"(d[2]), "+f"(d[3]), "+f"(d[4]), "+f"(d[5]), "+f"(d[6]), "+f"(d[7]), "+f"(d[8]), "+f"(d[9]), "+f"(d[10]), "+f"(d[11]), "+f"(d[12]), "+f"(d[13]), "+f"(d[14]), "+f"(d[15])
    : "l"(da), "l"(db), "r"(scale_d));
}

__device__ __forceinline__ void wgmma_ss_n8(float (&d)[4], uint64_t da, uint64_t db, int scale_d) {
  asm volatile("{\n.reg .pred p;\nsetp.ne.b32 p, %6, 0;\n"
    "wgmma.mma_async.sync.aligned.m64n8k16.f32.bf16.bf16 {%0, %1, %2, %3}, %4, %5, p, 1, 1, 1, 0;\n}\n"
    : "+f"(d[0]), "+f"(d[1]), "+f"(d[2]), "+f"(d[3])
    : "l"(da), "l"(db), "r"(scale_d));
}

__device__ __forceinline__ void wgmma_rs_n64(float (&d)[32], uint32_t a0, uint32_t a1, uint32_t a2, uint32_t a3, uint64_t db, int scale_d) {
  asm volatile("{\n.reg .pred p;\nsetp.ne.b32 p, %37, 0;\n"
    "wgmma.mma_async.sync.aligned.m64n64k16.f32.bf16.bf16 {%0, %1, %2, %3, %4, %5, %6, %7, %8, %9, %10, %11, %12, %13, %14, %15, %16, %17, %18, %19, %20, %21, %22, %23, %24, %25, %26, %27, %28, %29, %30, %31}, {%32, %33, %34, %35}, %36, p, 1, 1, 1;\n}\n"
    : "+f"(d[0]), "+f"(d[1]), "+f"(d[2]), "+f"(d[3]), "+f"(d[4]), "+f"(d[5]), "+f"(d[6]), "+f"(d[7]), "+f"(d[8]), "+f"(d[9]), "+f"(d[10]), "+f"(d[11]), "+f"(d[12]), "+f"(d[13]), "+f"(d[14]), "+f"(d[15]), "+f"(d[16]), "+f"(d[17]), "+f"(d[18]), "+f"(d[19]), "+f"(d[20]), "+f"(d[21]), "+f"(d[22]), "+f"(d[23]), "+f"(d[24]), "+f"(d[25]), "+f"(d[26]), "+f"(d[27]), "+f"(d[28]), "+f"(d[29]), "+f"(d[30]), "+f"(d[31])
    : "r"(a0), "r"(a1), "r"(a2), "r"(a3), "l"(db), "r"(scale_d));
}

__host__ __device__ constexpr int unit_slot(int u) {
  constexpr int t[36] = {4, 5, 6, 7, 8, 4, 5, 6, 0, 7, 8, 4,  1, 5, 6, 0, 2, 7, 8, 4, 3, 1, 5, 6,
                         0, 2, 7, 8,  4, 3, 1, 5, 6, 0, 2, 7};
  return t[u];
}
__host__ __device__ constexpr int unit_wait(int u) {
  constexpr int t[36] = {-1, -1, -1, -1, -1, 0, 1, 2, 2, 3, 4, 5,  5, 6, 7, 8, 8, 9, 10, 11, 11, 12, 13, 14,
                         15, 16, 17, 18,  19, 20, 21, 22, 23, 24, 25, 26};
  return t[u];
}

__device__ __forceinline__ uint32_t stage_off(int g, int j) {
  return g == 0 ? (j < 2 ? 8 * kSlot + j * 8192 : 10 * kSlot + (j - 2) * 8192)
                : (j < 2 ? 12 * kSlot + j * 8192 : (j == 2 ? 11 * kSlot + 8192 : 9 * kSlot));
}

struct Params {
  CUtensorMap x, w1, w2, wf, wg, wo, g, out64, out56;
  const void* xptr;
};

__device__ __forceinline__ void init_bar(uint32_t bars, int i) {
  const uint32_t a = bars + i * 8;
  const bool is_e = (i >= kBarE && i < kBarE + 27);
  mbar_init(a, is_e ? 8 : 1);
  if (!is_e) {
    uint32_t bytes = 16384;
    if (i == kBarFX) bytes = 8192;
    if (i == kBarFE) bytes = 8192;
    mbar_expect(a, bytes);
  }
}

__global__ void __cluster_dims__(2, 1, 1) __launch_bounds__(kThreads, 1)
rnnt_joint_kernel(const __grid_constant__ Params P) {
  extern __shared__ uint8_t smem_raw[];
  const uint32_t sb = (smem_u32(smem_raw) + 1023u) & ~1023u;
  const uint32_t bars = sb + kOffBar;
  const int warp = threadIdx.x >> 5, lane = threadIdx.x & 31;
  uint32_t cta;
  asm volatile("mov.u32 %0, %%cluster_ctarank;" : "=r"(cta));
  const uint32_t peer = cta ^ 1u;
  const int cl = blockIdx.x >> 1;
  const bool ge_cta = cl < 2;
  const int b = ge_cta ? cl : ((cl - 2) >> 5);
  const int r0 = ge_cta ? 32 * kR : ((cl - 2) & 31) * kR;
  const int rvalid = ge_cta ? kT2 - 32 * kR : kR;

  if (warp >= 8) {
    asm volatile("setmaxnreg.dec.sync.aligned.u32 40;");
    if (warp > 8) {
      if (elect_one()) {
#pragma unroll
        for (int i = 0; i < 5; i++) if (57 + (warp - 9) * 5 + i < kBarG) init_bar(bars, 57 + (warp - 9) * 5 + i);
#pragma unroll
        for (int i = 0; i < 5; i++) if (kBarRH + (warp - 9) * 5 + i < kBarGW) mbar_init(bars + (kBarRH + (warp - 9) * 5 + i) * 8, 4);
        if (warp == 11) { mbar_init(bars + kBarGW * 8, 8); mbar_init(bars + kBarFO * 8, 8); mbar_init(bars + kBarGE * 8, 1); mbar_expect(bars + kBarGE * 8, kGEBytes); }
        asm volatile("fence.mbarrier_init.release.cluster;" ::: "memory");
      }
      __syncwarp();
      cluster_sync_relaxed();
      if (warp == 10 && ge_cta) {
        mbar_wait(bars + kBarGW * 8);
        if (elect_one()) {
          __threadfence();
          asm volatile("red.release.gpu.global.add.u32 [%0], 1;" ::"l"(&g_ge_flag[b]) : "memory");
        }
        __syncwarp();
      }
      if (warp > 9) return;
#pragma unroll
      for (int g = 0; g < 2; g++) {
        mbar_wait(bars + (kBarRH + g) * 8);
        if (elect_one()) {
          const uint32_t src = sb + kSlotH * kSlot + (2 * cta + g) * 8192;
          dsmem_copy(mapa(src, peer), src, 8192, mapa(bars + kBarHX * 8, peer));
        }
        __syncwarp();
      }
#pragma unroll
      for (int g = 0; g < 2; g++) {
        mbar_wait(bars + (kBarRF + g) * 8);
        if (elect_one()) {
          const uint32_t src = sb + kSlotF * kSlot + (2 * cta + g) * 4096;
          dsmem_copy(mapa(src, peer), src, 4096, mapa(bars + kBarFX * 8, peer));
        }
        __syncwarp();
      }
#pragma unroll
      for (int g = 0; g < 2; g++) {
        mbar_wait(bars + (kBarRE + g) * 8);
        if (elect_one())
          dsmem_copy(mapa(sb + kSlotFE * kSlot + (2 * cta + g) * 4096, peer), sb + kSlotH * kSlot + g * 4096, 4096, mapa(bars + kBarFE * 8, peer));
        __syncwarp();
      }
      {
        int nxt0 = ((int)cta * 16 < rvalid) ? 0 : 4, nxt1 = ((int)cta * 16 + 8 < rvalid) ? 0 : 4;
        const long long t0 = clock64();
        while ((nxt0 < 4 || nxt1 < 4) && clock64() - t0 < 8000000ll) {
#pragma unroll
          for (int g = 0; g < 2; g++) {
            const int j = g ? nxt1 : nxt0;
            if (j < 4 && mbar_test(bars + (kBarPR + g * 4 + j) * 8)) {
              if (elect_one()) {
                const int rl0 = cta * 16 + g * 8;
                tma_store_3d((rl0 + 8 <= rvalid) ? &P.out64 : &P.out56, sb + stage_off(g, j), 0, (b * kT2 + r0 + rl0) * 8, j);
                asm volatile("cp.async.bulk.commit_group;" ::: "memory");
              }
              __syncwarp();
              if (g == 0 && j == 0) TS(2, 12);
              if (g == 1 && j == 0) TS(2, 13);
              if (g == 0 && j == 3) TS(2, 14);
              if (g == 1 && j == 3) TS(2, 15);
              if (g) nxt1++; else nxt0++;
            }
          }
        }
        if (elect_one()) asm volatile("cp.async.bulk.wait_group.read 0;" ::: "memory");
        __syncwarp();
        TS(2, 11);
        GT(1);
      }
      return;
    }
    TS(2, 0);
    GT(0);
    unsigned int ticket = 0;
    const int par = cta == 0 ? 1 : 0;
    const int q0 = cta == 0 ? 2 * r0 - 2 : 2 * r0 - 1;
    if (elect_one()) {
      mbar_init(bars + kBarX * 8, 1); mbar_expect(bars + kBarX * 8, 16384);
      mbar_init(bars + kBarW * 8, 1); mbar_expect(bars + kBarW * 8, 16384);
      fence_async_smem();
      tma_load_4d(sb, &P.x, bars + kBarX * 8, 0, 1, 2 * r0 - 2, b);
      tma_load_4d(sb + 8192, &P.x, bars + kBarX * 8, 0, 0, 2 * r0 - 1, b);
      tma_load_3d(sb + unit_slot(0) * kSlot, &P.w1, bars + kBarW * 8, 0, 0, 2 * cta);
      TS(2, 7);
#pragma unroll
      for (int i = 1; i < 9; i++) if (i != kBarW) { mbar_init(bars + i * 8, 1); mbar_expect(bars + i * 8, 16384); }
      if (ge_cta) { mbar_init(bars + kBarG * 8, 1); mbar_expect(bars + kBarG * 8, 4 * 16384 + 4096); mbar_init(bars + kBarP0 * 8, 8); }
      asm volatile("fence.mbarrier_init.release.cluster;" ::: "memory");
      fence_async_smem();
      TS(2, 8);
      if (ge_cta) {
        tma_load_3d(sb + kOffG, &P.g, bars + kBarG * 8, 0, b * 8, 0);
#pragma unroll
        for (int i = 0; i < 4; i++) tma_load_3d(sb + (9 + i) * kSlot, &P.wg, bars + kBarG * 8, 0, i * 64, 2 * cta);
      }
#pragma unroll
      for (int u = 1; u < 5; u++)
        tma_load_3d(sb + unit_slot(u) * kSlot, &P.w1, bars + (kBarW + u) * 8, 0, (u % 3) * 256 + (u / 3) * 64, 2 * cta);
      TS(2, 10);
    }
    __syncwarp();
    TS(2, 6);
    cluster_sync_relaxed();
    TS(2, 1);
    if (elect_one()) {
#pragma unroll
      for (int p = 1; p < XFIRST; p++)
        tma_load_4d_mc(sb + p * kSlot + cta * 8192, &P.x, bars + (kBarX + p) * 8, p * 64, par, q0, b, (uint16_t)3);
    }
    __syncwarp();
    if (lane == 0) ticket = atomicAdd(&g_cta_count, 1u);
#pragma unroll
    for (int p = XFIRST; p < 4; p++) {
      if (XSTEP == 1 || ((p - XFIRST) & 1) == 0) mbar_wait(bars + (kBarX + p - XFIRST) * 8);
      if (ge_cta && p == 3) mbar_wait(bars + kBarP0 * 8);
      if (elect_one())
        tma_load_4d_mc(sb + p * kSlot + cta * 8192, &P.x, bars + (kBarX + p) * 8, p * 64, par, q0, b, (uint16_t)3);
      __syncwarp();
    }
#pragma unroll
    for (int u = 5; u < 36; u++) {
      if (unit_wait(u) != unit_wait(u - 1)) mbar_wait(bars + (kBarE + unit_wait(u)) * 8);
      if (u == 27) ticket = __shfl_sync(0xffffffffu, ticket, 0);
      if (elect_one()) {
        const uint32_t dst = sb + unit_slot(u) * kSlot, bar = bars + (kBarW + u) * 8;
        if (u < 12) tma_load_3d(dst, &P.w1, bar, 0, (u % 3) * 256 + (u / 3) * 64, 2 * cta);
        else if (u < 24) tma_load_3d(dst, &P.w2, bar, 0, ((u - 12) % 3) * 256 + ((2 * cta + (u - 12) / 3) & 3) * 64, 2 * cta);
        else if (u < 28) tma_load_3d(dst, &P.wf, bar, 0, ((2 * cta + (u - 24)) & 3) * 64, 2 * cta);
        else tma_load_3d(dst, &P.wo, bar, 0, ((2 * cta + (u - 28)) & 3) * 64, ((u - 28) >> 2) * 2);
        if (u == 27) {
          const unsigned int want = (ticket / kNumCtas + 1u) * 2u;
          const long long t0 = clock64();
          unsigned int v;
          do {
            asm volatile("ld.acquire.gpu.global.u32 %0, [%1];" : "=r"(v) : "l"(&g_ge_flag[b]) : "memory");
          } while ((int)(v - want) < 0 && clock64() - t0 < 4000000ll);
          asm volatile("fence.proxy.async;" ::: "memory");
          bulk_load(sb + kOffGE, reinterpret_cast<const char*>(g_ge) + b * kGEBytes, kGEBytes, bars + kBarGE * 8);
        }
      }
      __syncwarp();
      if (u == 11) TS(2, 2);
      if (u == 23) TS(2, 3);
      if (u == 27) TS(2, 4);
      if (u == 35) TS(2, 5);
    }
  } else {
    asm volatile("setmaxnreg.inc.sync.aligned.u32 232;");
    const int wg = warp >> 2, w = warp & 3;
    const int gq = lane >> 2, q = lane & 3;
    const uint32_t panel = 2 * cta + wg;
    const int ch = panel * 64 + w * 16 + gq;
    const uint32_t dA = desc_lo(sb + wg * 8192, 8192);
    const uint32_t dB = desc_lo(sb, 16);
    const uint32_t dBo = desc_lo(sb + cta * 2 * 8192, 16), dBp = desc_lo(sb + (cta ^ 1) * 2 * 8192, 16);
    const uint32_t dFo = desc_lo(sb + cta * 2 * 4096, 16), dFp = desc_lo(sb + (cta ^ 1) * 2 * 4096, 16);
    if (elect_one()) {
#pragma unroll
      for (int i = 0; i < 6; i++) init_bar(bars, 9 + warp * 6 + i);
      asm volatile("fence.mbarrier_init.release.cluster;" ::: "memory");
    }
    __syncwarp();
    cluster_sync_relaxed();
    if (w == 0) TS(wg, 0);

    if (ge_cta) {
      float ga[4];
      mbar_wait(bars + kBarG * 8);
      wg_fence();
#pragma unroll
      for (int i = 0; i < 4; i++) {
#pragma unroll
        for (int s = 0; s < 4; s++)
          wgmma_ss_n8(ga, desc_at(dA, (9 + i) * kSlot + s * 2048), desc_at(dB, kOffG + i * 1024 + s * 32), (i | s) != 0);
      }
      wg_commit();
      wg_wait<0>();
      if (lane == 0) mbar_arrive(bars + kBarP0 * 8);
      float* gp = g_ge + b * (kGEBytes / 4) + ((ch & 7) >> 1) * (kGEPitch / 4) + (ch >> 4) * 4 + (ch & 1);
      gp[(2 * q) * 4 * (kGEPitch / 4)] = ga[0];
      gp[(2 * q + 1) * 4 * (kGEPitch / 4)] = ga[1];
      gp[(2 * q) * 4 * (kGEPitch / 4) + 2] = ga[2];
      gp[(2 * q + 1) * 4 * (kGEPitch / 4) + 2] = ga[3];
      __syncwarp();
      if (lane == 0) mbar_arrive(bars + kBarGW * 8);
    }

    {
      float acc[32];
#pragma unroll
      for (int u = 0; u < 12; u++) {
        const int p = u / 3, tap = u % 3;
        if (tap == 0) mbar_wait(bars + (kBarX + p) * 8);
        mbar_wait(bars + (kBarW + u) * 8);
        if (u == 0 && w == 0) TS(wg, 1);
        wg_fence();
#pragma unroll
        for (int s = 0; s < 4; s++)
          wgmma_ss_n64(acc, desc_at(dA, unit_slot(u) * kSlot + s * 2048),
                       desc_at(dB, p * kSlot + (tap == 1 ? 8192 : (tap == 2 ? 128 : 0)) + s * 32), (u | s) != 0);
        wg_commit();
        if (u > 0) {
          wg_wait<1>();
          if (lane == 0) mbar_arrive(bars + (kBarE + u - 1) * 8);
        }
      }
      wg_wait<0>();
      if (lane == 0) mbar_arrive(bars + (kBarE + 11) * 8);
      if (w == 0) TS(wg, 2);
      const uint32_t hp = sb + kSlotH * kSlot + panel * 8192;
      const int mi = lane >> 3, l8 = lane & 7;
#pragma unroll
      for (int jb = 0; jb < 8; jb += 2) {
        uint32_t r[4];
#pragma unroll
        for (int t = 0; t < 2; t++) {
          r[2 * t + 0] = pack_bf16(gelu_tanh(acc[4 * (jb + t) + 0]), gelu_tanh(acc[4 * (jb + t) + 1]));
          r[2 * t + 1] = pack_bf16(gelu_tanh(acc[4 * (jb + t) + 2]), gelu_tanh(acc[4 * (jb + t) + 3]));
        }
        const int n = 8 * (jb + (mi >> 1)) + l8;
        const int row = n >> 1, chunk = 2 * w + (mi & 1);
        stsm_x4_trans(hp + (n & 1) * 4096 + row * 128 + ((chunk ^ (row & 7)) << 4), r[0], r[1], r[2], r[3]);
      }
      fence_async_smem();
      __syncwarp();
      if (lane == 0) mbar_arrive(bars + (kBarRH + wg) * 8);
      mbar_wait(bars + kBarRH * 8);
      mbar_wait(bars + (kBarRH + 1) * 8);
      if (w == 0) TS(wg, 3);
    }
    {
      float acc[16];
#pragma unroll
      for (int v = 0; v < 12; v++) {
        const int i = v / 3, tap = v % 3;
        if (v == 6) { mbar_wait_cluster(bars + kBarHX * 8); if (w == 0) TS(wg, 4); }
        mbar_wait(bars + (kBarW + 12 + v) * 8);
        wg_fence();
#pragma unroll
        for (int s = 0; s < 4; s++)
          wgmma_ss_n32(acc, desc_at(dA, unit_slot(12 + v) * kSlot + s * 2048),
                       desc_at(i < 2 ? dBo : dBp, kSlotH * kSlot + (i & 1) * 8192 + (tap == 1 ? 4096 : (tap == 2 ? 128 : 0)) + s * 32), (v | s) != 0);
        wg_commit();
        if (v > 0) {
          wg_wait<1>();
          if (lane == 0) mbar_arrive(bars + (kBarE + 12 + v - 1) * 8);
        }
      }
      wg_wait<0>();
      if (lane == 0) mbar_arrive(bars + (kBarE + 23) * 8);
      if (w == 0) TS(wg, 5);
      const uint32_t fp = sb + kSlotF * kSlot + panel * 4096;
      const int mi = lane >> 3, l8 = lane & 7;
#pragma unroll
      for (int jb = 0; jb < 4; jb += 2) {
        uint32_t r[4];
#pragma unroll
        for (int t = 0; t < 2; t++) {
          r[2 * t + 0] = pack_bf16(gelu_tanh(acc[4 * (jb + t) + 0]), gelu_tanh(acc[4 * (jb + t) + 1]));
          r[2 * t + 1] = pack_bf16(gelu_tanh(acc[4 * (jb + t) + 2]), gelu_tanh(acc[4 * (jb + t) + 3]));
        }
        const int n = 8 * (jb + (mi >> 1)) + l8;
        const int chunk = 2 * w + (mi & 1);
        stsm_x4_trans(fp + n * 128 + ((chunk ^ (n & 7)) << 4), r[0], r[1], r[2], r[3]);
      }
      fence_async_smem();
      __syncwarp();
      if (lane == 0) mbar_arrive(bars + (kBarRF + wg) * 8);
      mbar_wait(bars + kBarRF * 8);
      mbar_wait(bars + (kBarRF + 1) * 8);
      if (w == 0) TS(wg, 6);
    }
    {
      float acc[16];
#pragma unroll
      for (int i = 0; i < 4; i++) {
        if (i == 2) { mbar_wait_cluster(bars + kBarFX * 8); if (w == 0) TS(wg, 7); }
        mbar_wait(bars + (kBarW + 24 + i) * 8);
        wg_fence();
#pragma unroll
        for (int s = 0; s < 4; s++)
          wgmma_ss_n32(acc, desc_at(dA, unit_slot(24 + i) * kSlot + s * 2048),
                       desc_at(i < 2 ? dFo : dFp, kSlotF * kSlot + (i & 1) * 4096 + s * 32), (i | s) != 0);
        wg_commit();
        if (i > 0) {
          wg_wait<1>();
          if (lane == 0) mbar_arrive(bars + (kBarE + 24 + i - 1) * 8);
        }
      }
      wg_wait<0>();
      if (w == 0) TS(wg, 8);
      const uint32_t qk = gq >> 1;
      const uint32_t off0 = qk * 128 + (((2 * w) ^ (2 * qk)) << 4) + (gq & 1) * 8;
      const uint32_t off1 = qk * 128 + (((2 * w + 1) ^ (2 * qk)) << 4) + (gq & 1) * 8;
      const uint32_t own = sb + kSlotFE * kSlot + panel * 4096;
      const uint32_t stg = sb + kSlotH * kSlot + wg * 4096;
#pragma unroll
      for (int jb = 0; jb < 4; jb++) {
        const uint32_t base = (((uint32_t)(jb >> 1) == cta) ? own : stg) + (4 * (jb & 1) + q) * 512;
        sts64(base + off0, acc[4 * jb + 0], acc[4 * jb + 1]);
        sts64(base + off1, acc[4 * jb + 2], acc[4 * jb + 3]);
      }
      fence_async_smem();
      __syncwarp();
      if (lane == 0) { mbar_arrive(bars + (kBarRE + wg) * 8); mbar_arrive(bars + kBarFO * 8); }
      if (w == 0) TS(wg, 9);
    }
    const int rl0 = cta * 16 + wg * 8;
    mbar_wait(bars + kBarFO * 8);
    mbar_wait(bars + kBarGE * 8);
    if (wg == 1) asm volatile("bar.sync 4, 256;" ::: "memory");
    if (rl0 < rvalid) {
      if (w == 0) TS(wg, 10);
      const uint32_t fe_row = sb + kSlotFE * kSlot + ((4 * wg + w) * 4 + q) * 128;
      const uint32_t fe_h[2] = {fe_row + cta * 8192, fe_row + (cta ^ 1) * 8192};
      const uint32_t ge_h[2] = {sb + kOffGE + lane * kGEPitch + cta * 128, sb + kOffGE + lane * kGEPitch + (cta ^ 1) * 128};
      const int mi = lane >> 3, l8 = lane & 7;
      const uint32_t st = sb + (16 * w + (mi & 1) * 8 + l8) * 128;
      uint32_t A[64];
      float acc[2][32];
      {
        constexpr int PD = 3;
        float4 fa[PD], fb[PD], gg[PD];
#pragma unroll
        for (int kk = 0; kk < 16 + PD; kk++) {
          if (kk >= PD) {
            const int k = kk - PD, sl = k % PD;
            A[4 * k + 0] = tanh2_pack(fa[sl].x + gg[sl].x, fa[sl].z + gg[sl].y);
            A[4 * k + 1] = tanh2_pack(fa[sl].y + gg[sl].x, fa[sl].w + gg[sl].y);
            A[4 * k + 2] = tanh2_pack(fb[sl].x + gg[sl].z, fb[sl].z + gg[sl].w);
            A[4 * k + 3] = tanh2_pack(fb[sl].y + gg[sl].z, fb[sl].w + gg[sl].w);
          }
          if (kk < 16) {
            const int sl = kk % PD;
            if (kk == 8) mbar_wait_cluster(bars + kBarFE * 8);
            fa[sl] = lds128(fe_h[kk >> 3] + ((kk >> 2) & 1) * 4096 + ((((kk & 3) * 2) ^ (2 * q)) << 4));
            fb[sl] = lds128(fe_h[kk >> 3] + ((kk >> 2) & 1) * 4096 + ((((kk & 3) * 2 + 1) ^ (2 * q)) << 4));
            gg[sl] = lds128(ge_h[kk >> 3] + (kk & 7) * 16);
          }
        }
      }
      asm volatile("barrier.cluster.arrive.relaxed.aligned;" ::: "memory");
#pragma unroll
      for (int kk = 0; kk < 16; kk++) {
        if ((kk & 3) == 0) { mbar_wait(bars + (kBarW + 28 + (kk >> 2)) * 8); wg_fence(); }
        wgmma_rs_n64(acc[0], A[4 * kk], A[4 * kk + 1], A[4 * kk + 2], A[4 * kk + 3],
                     desc_at(dB, unit_slot(28 + (kk >> 2)) * kSlot + (kk & 3) * 2048), kk != 0);
        if (kk == ARRK) bar_arrive_pred(wg == 0);
      }
      wg_commit();
      wg_wait<0>();
#pragma unroll
      for (int jb = 0; jb < 8; jb += 2) {
        const uint32_t r0_ = pack_bf16(acc[0][4 * jb + 0], acc[0][4 * jb + 1]), r1_ = pack_bf16(acc[0][4 * jb + 2], acc[0][4 * jb + 3]);
        const uint32_t r2_ = pack_bf16(acc[0][4 * jb + 4], acc[0][4 * jb + 5]), r3_ = pack_bf16(acc[0][4 * jb + 6], acc[0][4 * jb + 7]);
        stsm_x4(st + (wg ? stage_off(1, 0) : stage_off(0, 0)) + (((jb + (mi >> 1)) ^ l8) << 4), r0_, r1_, r2_, r3_);
      }
      fence_async_smem();
      __syncwarp();
      mbar_arrive_pred(bars + (kBarPR + wg * 4) * 8, lane == 0);
      if (w == 0) TS(wg, 11);
#pragma unroll
      for (int j = 0; j < 4; j++) {
        const int jn = j + 1;
        if (jn == 2) {
#pragma unroll
          for (int i = 0; i < 4; i++) mbar_wait(bars + (kBarW + 32 + i) * 8);
        }
        if (j < 3) wg_fence();
        const uint32_t stj = st + (wg ? stage_off(1, j) : stage_off(0, j));
#pragma unroll
        for (int kk = 0; kk < 16; kk++) {
          if (j < 3)
            wgmma_rs_n64(acc[jn & 1], A[4 * kk], A[4 * kk + 1], A[4 * kk + 2], A[4 * kk + 3],
                         desc_at(dB, unit_slot(28 + (jn >> 1) * 4 + (kk >> 2)) * kSlot + (jn & 1) * 8192 + (kk & 3) * 2048), kk != 0);
          if (kk == 1 && j > 0) {
            if (j < 3) { wg_commit(); wg_wait<1>(); } else { wg_wait<0>(); }
          }
          if (j > 0 && kk >= 2 && kk < 10 && (kk & 1) == 0) {
            const int jb = kk - 2;
            const uint32_t r0_ = pack_bf16(acc[j & 1][4 * jb + 0], acc[j & 1][4 * jb + 1]), r1_ = pack_bf16(acc[j & 1][4 * jb + 2], acc[j & 1][4 * jb + 3]);
            const uint32_t r2_ = pack_bf16(acc[j & 1][4 * jb + 4], acc[j & 1][4 * jb + 5]), r3_ = pack_bf16(acc[j & 1][4 * jb + 6], acc[j & 1][4 * jb + 7]);
            stsm_x4(stj + (((jb + (mi >> 1)) ^ l8) << 4), r0_, r1_, r2_, r3_);
          }
          if (j > 0 && kk == 9) {
            fence_async_smem();
            __syncwarp();
            mbar_arrive_pred(bars + (kBarPR + wg * 4 + j) * 8, lane == 0);
          }
        }
        if (j < 3) wg_commit();
        if (j == 0 && w == 0) TS(wg, 12);
        if (j == 2 && w == 0) TS(wg, 13);
      }
      if (w == 0) TS(wg, 14);
    } else {
      if (wg == 0) asm volatile("bar.arrive 4, 256;" ::: "memory");
      mbar_wait_cluster(bars + kBarFE * 8);
      asm volatile("barrier.cluster.arrive.relaxed.aligned;" ::: "memory");
    }
    asm volatile("barrier.cluster.wait.aligned;" ::: "memory");
  }
}

typedef CUresult (*EncodeFn)(CUtensorMap*, CUtensorMapDataType, cuuint32_t, void*, const cuuint64_t*, const cuuint64_t*,
                             const cuuint32_t*, const cuuint32_t*, CUtensorMapInterleave, CUtensorMapSwizzle,
                             CUtensorMapL2promotion, CUtensorMapFloatOOBfill);

void make_map3(EncodeFn enc, CUtensorMap* tm, const void* ptr, uint64_t rows, uint32_t box_rows, uint32_t box_panels) {
  cuuint64_t gd[3] = {64, rows, 4};
  cuuint64_t gs[2] = {512, 128};
  cuuint32_t bd[3] = {64, box_rows, box_panels};
  cuuint32_t es[3] = {1, 1, 1};
  enc(tm, CU_TENSOR_MAP_DATA_TYPE_BFLOAT16, 3, const_cast<void*>(ptr), gd, gs, bd, es, CU_TENSOR_MAP_INTERLEAVE_NONE,
      CU_TENSOR_MAP_SWIZZLE_128B, CU_TENSOR_MAP_L2_PROMOTION_L2_256B, CU_TENSOR_MAP_FLOAT_OOB_FILL_NONE);
}

}

extern "C" void kernel_launch(void* const* d_in, const int* in_sizes, int n_in, void* d_out, int out_size) {
  static EncodeFn enc = nullptr;
  if (!enc) {
    cudaDriverEntryPointQueryResult qr;
    cudaGetDriverEntryPoint("cuTensorMapEncodeTiled", (void**)&enc, cudaEnableDefault, &qr);
    cudaFuncSetAttribute(rnnt_joint_kernel, cudaFuncAttributeMaxDynamicSharedMemorySize, kSmemBytes);
  }
  Params P;
  {
    cuuint64_t gd[4] = {256, 2, 2000, 2};
    cuuint64_t gs[3] = {512, 1024, 4000ull * 512};
    cuuint32_t bd[4] = {64, 1, 64, 1};
    cuuint32_t es[4] = {1, 1, 1, 1};
    enc(&P.x, CU_TENSOR_MAP_DATA_TYPE_BFLOAT16, 4, d_in[0], gd, gs, bd, es, CU_TENSOR_MAP_INTERLEAVE_NONE,
        CU_TENSOR_MAP_SWIZZLE_128B, XPROMO, CU_TENSOR_MAP_FLOAT_OOB_FILL_NONE);
  }
  P.xptr = d_in[0];
  make_map3(enc, &P.w1, d_in[1], 768, 64, 2);
  make_map3(enc, &P.w2, d_in[2], 768, 64, 2);
  make_map3(enc, &P.g, d_in[3], 16, 8, 4);
  make_map3(enc, &P.wf, d_in[4], 256, 64, 2);
  make_map3(enc, &P.wg, d_in[5], 256, 64, 2);
  make_map3(enc, &P.wo, d_in[6], 256, 64, 2);
  make_map3(enc, &P.out64, d_out, 16000, 64, 1);
  make_map3(enc, &P.out56, d_out, 16000, 56, 1);
  rnnt_joint_kernel<<<kNumCtas, kThreads, kSmemBytes>>>(P);
}
```

```cpp
#include <cuda_runtime.h>
#include <cuda_bf16.h>
#include <cuda.h>
#include <stdint.h>

#define ARRK 3
#define XBULK 0
#define SKEW1 3
#define SKEW2 3
#define XPREF 1
#define XFIRST 3
#define XSTEP 1
#define XPROMO CU_TENSOR_MAP_L2_PROMOTION_L2_128B
namespace {

constexpr int kT2 = 1000;
constexpr int kR = 31;
constexpr int kNumCtas = 132;
constexpr int kThreads = 384;
constexpr int kSlot = 16384;

constexpr int kSlotFE = 9, kSlotF = 10, kSlotH = 11;
constexpr int kOffG = 13 * kSlot;
constexpr int kOffGE = kOffG + 4096;
constexpr int kGEPitch = 272;
constexpr int kGEBytes = 32 * kGEPitch;
constexpr int kOffBar = kOffGE + kGEBytes;
constexpr int kBarX = 0;
constexpr int kBarW = 4;
constexpr int kBarE = 40;
constexpr int kBarHX = 67, kBarFX = 68, kBarFE = 69, kBarG = 70, kBarP0 = 71;
constexpr int kBarRH = 72, kBarRF = 74, kBarRE = 76;
constexpr int kBarPR = 78;
constexpr int kBarGW = 86;
constexpr int kBarFO = 87;
constexpr int kBarGE = 88;
constexpr int kNumBars = 89;
constexpr int kSmemBytes = kOffBar + kNumBars * 8 + 1024;

__device__ __align__(128) float g_ge[2 * kGEBytes / 4];
__device__ unsigned int g_ge_flag[2];
__device__ unsigned int g_cta_count;

#define TS(slot_, idx_) do {} while (0)
#define GT(idx_) do {} while (0)

__device__ __forceinline__ uint32_t smem_u32(const void* p) { return (uint32_t)__cvta_generic_to_shared(p); }
__device__ __forceinline__ void mbar_init(uint32_t a, uint32_t c) { asm volatile("mbarrier.init.shared.b64 [%0], %1;" ::"r"(a), "r"(c) : "memory"); }
__device__ __forceinline__ void mbar_expect(uint32_t a, uint32_t b) { asm volatile("mbarrier.arrive.expect_tx.shared.b64 _, [%0], %1;" ::"r"(a), "r"(b) : "memory"); }
__device__ __forceinline__ void mbar_arrive(uint32_t a) { asm volatile("mbarrier.arrive.shared.b64 _, [%0];" ::"r"(a) : "memory"); }
__device__ __forceinline__ void mbar_arrive_pred(uint32_t a, bool p) {
  asm volatile("{\n.reg .pred q;\nsetp.ne.u32 q, %1, 0;\n@q mbarrier.arrive.shared.b64 _, [%0];\n}\n" ::"r"(a), "r"((uint32_t)p) : "memory");
}
__device__ __forceinline__ void bar_arrive_pred(bool p) {
  asm volatile("{\n.reg .pred q;\nsetp.ne.u32 q, %0, 0;\n@q bar.arrive 4, 256;\n}\n" ::"r"((uint32_t)p) : "memory");
}
#define DEF_NAMED(ID) \
__device__ __forceinline__ void bar_arrive_pred##ID(bool p) { asm volatile("{\n.reg .pred q;\nsetp.ne.u32 q, %0, 0;\n@q bar.arrive " #ID ", 256;\n}\n" ::"r"((uint32_t)p) : "memory"); } \
__device__ __forceinline__ void bar_sync_pred##ID(bool p) { asm volatile("{\n.reg .pred q;\nsetp.ne.u32 q, %0, 0;\n@q bar.sync " #ID ", 256;\n}\n" ::"r"((uint32_t)p) : "memory"); }
DEF_NAMED(5)
DEF_NAMED(6)
__device__ __forceinline__ bool mbar_try(uint32_t a) {
  uint32_t ok;
  asm volatile("{\n.reg .pred p;\nmbarrier.try_wait.parity.shared.b64 p, [%1], 0;\nselp.u32 %0, 1, 0, p;\n}\n" : "=r"(ok) : "r"(a) : "memory");
  return ok != 0;
}
__device__ __forceinline__ bool mbar_test(uint32_t a) {
  uint32_t ok;
  asm volatile("{\n.reg .pred p;\nmbarrier.test_wait.parity.shared.b64 p, [%1], 0;\nselp.u32 %0, 1, 0, p;\n}\n" : "=r"(ok) : "r"(a) : "memory");
  return ok != 0;
}
__device__ __forceinline__ bool mbar_try_cluster(uint32_t a) {
  uint32_t ok;
  asm volatile("{\n.reg .pred p;\nmbarrier.try_wait.parity.acquire.cluster.shared.b64 p, [%1], 0;\nselp.u32 %0, 1, 0, p;\n}\n" : "=r"(ok) : "r"(a) : "memory");
  return ok != 0;
}
__device__ __forceinline__ void mbar_wait_slow(uint32_t a) {
  const long long t0 = clock64();
  while (!mbar_try(a)) { if (clock64() - t0 > 4000000ll) break; }
}
__device__ __forceinline__ void mbar_wait_cluster_slow(uint32_t a) {
  const long long t0 = clock64();
  while (!mbar_try_cluster(a)) { if (clock64() - t0 > 4000000ll) break; }
}
__device__ __forceinline__ void mbar_wait(uint32_t a) { if (!mbar_try(a)) mbar_wait_slow(a); }
__device__ __forceinline__ void mbar_wait_cluster(uint32_t a) { if (!mbar_try_cluster(a)) mbar_wait_cluster_slow(a); }
__device__ __forceinline__ uint32_t mapa(uint32_t a, uint32_t r) { uint32_t d; asm volatile("mapa.shared::cluster.u32 %0, %1, %2;" : "=r"(d) : "r"(a), "r"(r)); return d; }
__device__ __forceinline__ bool elect_one() { uint32_t p; asm volatile("{\n.reg .pred P;\nelect.sync _|P, 0xffffffff;\nselp.u32 %0, 1, 0, P;\n}\n" : "=r"(p)); return p != 0; }
__device__ __forceinline__ void fence_async_smem() { asm volatile("fence.proxy.async.shared::cta;" ::: "memory"); }
__device__ __forceinline__ void bar_consumers() { asm volatile("bar.sync 1, 256;" ::: "memory"); }
__device__ __forceinline__ void bar_wg(int wg) { asm volatile("bar.sync %0, 128;" ::"r"(2 + wg) : "memory"); }
__device__ __forceinline__ void cluster_sync_relaxed() { asm volatile("barrier.cluster.arrive.relaxed.aligned;\nbarrier.cluster.wait.aligned;" ::: "memory"); }
__device__ __forceinline__ void wg_fence() { asm volatile("wgmma.fence.sync.aligned;" ::: "memory"); }
__device__ __forceinline__ void wg_commit() { asm volatile("wgmma.commit_group.sync.aligned;" ::: "memory"); }
template <int N> __device__ __forceinline__ void wg_wait() { asm volatile("wgmma.wait_group.sync.aligned %0;" ::"n"(N) : "memory"); }

__device__ __forceinline__ void tma_load_3d(uint32_t dst, const CUtensorMap* tm, uint32_t bar, int c0, int c1, int c2) {
  asm volatile("cp.async.bulk.tensor.3d.shared::cluster.global.mbarrier::complete_tx::bytes [%0], [%1, {%3, %4, %5}], [%2];"
               ::"r"(dst), "l"(tm), "r"(bar), "r"(c0), "r"(c1), "r"(c2) : "memory");
}
__device__ __forceinline__ void tma_load_4d(uint32_t dst, const CUtensorMap* tm, uint32_t bar, int c0, int c1, int c2, int c3) {
  asm volatile("cp.async.bulk.tensor.4d.shared::cluster.global.mbarrier::complete_tx::bytes [%0], [%1, {%3, %4, %5, %6}], [%2];"
               ::"r"(dst), "l"(tm), "r"(bar), "r"(c0), "r"(c1), "r"(c2), "r"(c3) : "memory");
}
__device__ __forceinline__ void tma_load_4d_mc(uint32_t dst, const CUtensorMap* tm, uint32_t bar, int c0, int c1, int c2, int c3, uint16_t mask) {
  asm volatile("cp.async.bulk.tensor.4d.shared::cluster.global.mbarrier::complete_tx::bytes.multicast::cluster [%0], [%1, {%3, %4, %5, %6}], [%2], %7;"
               ::"r"(dst), "l"(tm), "r"(bar), "r"(c0), "r"(c1), "r"(c2), "r"(c3), "h"(mask) : "memory");
}
__device__ __forceinline__ void tma_store_3d(const CUtensorMap* tm, uint32_t src, int c0, int c1, int c2) {
  asm volatile("cp.async.bulk.tensor.3d.global.shared::cta.bulk_group [%0, {%2, %3, %4}], [%1];"
               ::"l"(tm), "r"(src), "r"(c0), "r"(c1), "r"(c2) : "memory");
}
__device__ __forceinline__ void bulk_load(uint32_t dst, const void* src, uint32_t bytes, uint32_t bar) {
  asm volatile("cp.async.bulk.shared::cluster.global.mbarrier::complete_tx::bytes [%0], [%1], %2, [%3];"
               ::"r"(dst), "l"(src), "r"(bytes), "r"(bar) : "memory");
}
__device__ __forceinline__ void dsmem_copy(uint32_t dst_remote, uint32_t src, uint32_t bytes, uint32_t bar_remote) {
  asm volatile("cp.async.bulk.shared::cluster.shared::cta.mbarrier::complete_tx::bytes [%0], [%1], %2, [%3];"
               ::"r"(dst_remote), "r"(src), "r"(bytes), "r"(bar_remote) : "memory");
}
__device__ __forceinline__ void stsm_x4_trans(uint32_t addr, uint32_t r0, uint32_t r1, uint32_t r2, uint32_t r3) {
  asm volatile("stmatrix.sync.aligned.m8n8.x4.trans.shared.b16 [%0], {%1, %2, %3, %4};" ::"r"(addr), "r"(r0), "r"(r1), "r"(r2), "r"(r3) : "memory");
}
__device__ __forceinline__ void stsm_x4(uint32_t addr, uint32_t r0, uint32_t r1, uint32_t r2, uint32_t r3) {
  asm volatile("stmatrix.sync.aligned.m8n8.x4.shared.b16 [%0], {%1, %2, %3, %4};" ::"r"(addr), "r"(r0), "r"(r1), "r"(r2), "r"(r3) : "memory");
}
__device__ __forceinline__ float2 lds64(uint32_t a) { float2 v; asm volatile("ld.shared.v2.f32 {%0, %1}, [%2];" : "=f"(v.x), "=f"(v.y) : "r"(a) : "memory"); return v; }
__device__ __forceinline__ float4 lds128(uint32_t a) { float4 v; asm volatile("ld.shared.v4.f32 {%0, %1, %2, %3}, [%4];" : "=f"(v.x), "=f"(v.y), "=f"(v.z), "=f"(v.w) : "r"(a) : "memory"); return v; }
__device__ __forceinline__ void sts64(uint32_t a, float x, float y) { asm volatile("st.shared.v2.f32 [%0], {%1, %2};" ::"r"(a), "f"(x), "f"(y) : "memory"); }
__device__ __forceinline__ float tanh_fast(float x) { float y; asm("tanh.approx.f32 %0, %1;" : "=f"(y) : "f"(x)); return y; }
__device__ __forceinline__ uint32_t tanh2_pack(float lo, float hi) {
  uint32_t r;
  asm volatile("{\n.reg .f32 a, b;\ntanh.approx.f32 a, %1;\ntanh.approx.f32 b, %2;\ncvt.rn.bf16x2.f32 %0, b, a;\n}\n" : "=r"(r) : "f"(lo), "f"(hi));
  return r;
}
__device__ __forceinline__ uint32_t pack_bf16(float lo, float hi) { uint32_t r; asm("cvt.rn.bf16x2.f32 %0, %1, %2;" : "=r"(r) : "f"(hi), "f"(lo)); return r; }
__device__ __forceinline__ float gelu_tanh(float x) {
  const float k0 = 0.7978845608028654f, k1 = 0.7978845608028654f * 0.044715f;
  float u = x * fmaf(x * x, k1, k0);
  float hx = 0.5f * x;
  return fmaf(hx, tanh_fast(u), hx);
}
__device__ __forceinline__ uint64_t make_desc(uint32_t addr, uint32_t lbo, uint32_t sbo) {
  return (uint64_t)((addr & 0x3FFFF) >> 4) | ((uint64_t)(lbo >> 4) << 16) | ((uint64_t)(sbo >> 4) << 32) | ((uint64_t)1 << 62);
}

__device__ __forceinline__ uint32_t desc_lo(uint32_t addr, uint32_t lbo) { return ((addr & 0x3FFFF) >> 4) | ((lbo >> 4) << 16); }
__device__ __forceinline__ uint64_t desc_at(uint32_t lo, uint32_t off) { return ((uint64_t)0x40000040u << 32) | (uint64_t)(lo + (off >> 4)); }

__device__ __forceinline__ void wgmma_ss_n64(float (&d)[32], uint64_t da, uint64_t db, int scale_d) {
  asm volatile("{\n.reg .pred p;\nsetp.ne.b32 p, %34, 0;\n"
    "wgmma.mma_async.sync.aligned.m64n64k16.f32.bf16.bf16 {%0, %1, %2, %3, %4, %5, %6, %7, %8, %9, %10, %11, %12, %13, %14, %15, %16, %17, %18, %19, %20, %21, %22, %23, %24, %25, %26, %27, %28, %29, %30, %31}, %32, %33, p, 1, 1, 1, 0;\n}\n"
    : "+f"(d[0]), "+f"(d[1]), "+f"(d[2]), "+f"(d[3]), "+f"(d[4]), "+f"(d[5]), "+f"(d[6]), "+f"(d[7]), "+f"(d[8]), "+f"(d[9]), "+f"(d[10]), "+f"(d[11]), "+f"(d[12]), "+f"(d[13]), "+f"(d[14]), "+f"(d[15]), "+f"(d[16]), "+f"(d[17]), "+f"(d[18]), "+f"(d[19]), "+f"(d[20]), "+f"(d[21]), "+f"(d[22]), "+f"(d[23]), "+f"(d[24]), "+f"(d[25]), "+f"(d[26]), "+f"(d[27]), "+f"(d[28]), "+f"(d[29]), "+f"(d[30]), "+f"(d[31])
    : "l"(da), "l"(db), "r"(scale_d));
}

__device__ __forceinline__ void wgmma_ss_n32(float (&d)[16], uint64_t da, uint64_t db, int scale_d) {
  asm volatile("{\n.reg .pred p;\nsetp.ne.b32 p, %18, 0;\n"
    "wgmma.mma_async.sync.aligned.m64n32k16.f32.bf16.bf16 {%0, %1, %2, %3, %4, %5, %6, %7, %8, %9, %10, %11, %12, %13, %14, %15}, %16, %17, p, 1, 1, 1, 0;\n}\n"
    : "+f"(d[0]), "+f"(d[1]), "+f"(d[2]), "+f"(d[3]), "+f"(d[4]), "+f"(d[5]), "+f"(d[6]), "+f"(d[7]), "+f"(d[8]), "+f"(d[9]), "+f"(d[10]), "+f"(d[11]), "+f"(d[12]), "+f"(d[13]), "+f"(d[14]), "+f"(d[15])
    : "l"(da), "l"(db), "r"(scale_d));
}

__device__ __forceinline__ void wgmma_ss_n8(float (&d)[4], uint64_t da, uint64_t db, int scale_d) {
  asm volatile("{\n.reg .pred p;\nsetp.ne.b32 p, %6, 0;\n"
    "wgmma.mma_async.sync.aligned.m64n8k16.f32.bf16.bf16 {%0, %1, %2, %3}, %4, %5, p, 1, 1, 1, 0;\n}\n"
    : "+f"(d[0]), "+f"(d[1]), "+f"(d[2]), "+f"(d[3])
    : "l"(da), "l"(db), "r"(scale_d));
}

__device__ __forceinline__ void wgmma_rs_n64(float (&d)[32], uint32_t a0, uint32_t a1, uint32_t a2, uint32_t a3, uint64_t db, int scale_d) {
  asm volatile("{\n.reg .pred p;\nsetp.ne.b32 p, %37, 0;\n"
    "wgmma.mma_async.sync.aligned.m64n64k16.f32.bf16.bf16 {%0, %1, %2, %3, %4, %5, %6, %7, %8, %9, %10, %11, %12, %13, %14, %15, %16, %17, %18, %19, %20, %21, %22, %23, %24, %25, %26, %27, %28, %29, %30, %31}, {%32, %33, %34, %35}, %36, p, 1, 1, 1;\n}\n"
    : "+f"(d[0]), "+f"(d[1]), "+f"(d[2]), "+f"(d[3]), "+f"(d[4]), "+f"(d[5]), "+f"(d[6]), "+f"(d[7]), "+f"(d[8]), "+f"(d[9]), "+f"(d[10]), "+f"(d[11]), "+f"(d[12]), "+f"(d[13]), "+f"(d[14]), "+f"(d[15]), "+f"(d[16]), "+f"(d[17]), "+f"(d[18]), "+f"(d[19]), "+f"(d[20]), "+f"(d[21]), "+f"(d[22]), "+f"(d[23]), "+f"(d[24]), "+f"(d[25]), "+f"(d[26]), "+f"(d[27]), "+f"(d[28]), "+f"(d[29]), "+f"(d[30]), "+f"(d[31])
    : "r"(a0), "r"(a1), "r"(a2), "r"(a3), "l"(db), "r"(scale_d));
}

__host__ __device__ constexpr int unit_slot(int u) {
  constexpr int t[36] = {4, 5, 6, 7, 8, 4, 5, 6, 0, 7, 8, 4,  1, 5, 6, 0, 2, 7, 8, 4, 3, 1, 5, 6,
                         0, 2, 7, 8,  4, 3, 1, 5, 6, 0, 2, 7};
  return t[u];
}
__host__ __device__ constexpr int unit_wait(int u) {
  constexpr int t[36] = {-1, -1, -1, -1, -1, 0, 1, 2, 2, 3, 4, 5,  5, 6, 7, 8, 8, 9, 10, 11, 11, 12, 13, 14,
                         15, 16, 17, 18,  19, 20, 21, 22, 23, 24, 25, 26};
  return t[u];
}

__device__ __forceinline__ uint32_t stage_off(int g, int j) {
  return g == 0 ? (j < 2 ? 8 * kSlot + j * 8192 : 10 * kSlot + (j - 2) * 8192)
                : (j < 2 ? 12 * kSlot + j * 8192 : (j == 2 ? 11 * kSlot + 8192 : 9 * kSlot));
}

struct Params {
  CUtensorMap x, w1, w2, wf, wg, wo, g, out64, out56;
  const void* xptr;
};

__device__ __forceinline__ void init_bar(uint32_t bars, int i) {
  const uint32_t a = bars + i * 8;
  const bool is_e = (i >= kBarE && i < kBarE + 27);
  mbar_init(a, is_e ? 8 : 1);
  if (!is_e) {
    uint32_t bytes = 16384;
    if (i == kBarFX) bytes = 8192;
    if (i == kBarFE) bytes = 8192;
    mbar_expect(a, bytes);
  }
}

__device__ __forceinline__ void store_pieces(const Params& P, uint32_t sb, uint32_t bars, int g, uint32_t cta, int b, int r0, int rvalid) {
  const int rl0 = cta * 16 + g * 8;
  if (rl0 >= rvalid) return;
  const CUtensorMap* omap = (rl0 + 8 <= rvalid) ? &P.out64 : &P.out56;
#pragma unroll
  for (int j = 0; j < 4; j++) {
    mbar_wait(bars + (kBarPR + g * 4 + j) * 8);
    if (elect_one()) {
      tma_store_3d(omap, sb + stage_off(g, j), 0, (b * kT2 + r0 + rl0) * 8, j);
      asm volatile("cp.async.bulk.commit_group;" ::: "memory");
    }
    __syncwarp();
    if (j == 0) TS(2, 12 + g);
    if (j == 3) TS(2, 14 + g);
  }
  if (elect_one()) asm volatile("cp.async.bulk.wait_group.read 0;" ::: "memory");
  __syncwarp();
  if (g == 1) { TS(2, 11); GT(1); }
}

__global__ void __cluster_dims__(2, 1, 1) __launch_bounds__(kThreads, 1)
rnnt_joint_kernel(const __grid_constant__ Params P) {
  extern __shared__ uint8_t smem_raw[];
  const uint32_t sb = (smem_u32(smem_raw) + 1023u) & ~1023u;
  const uint32_t bars = sb + kOffBar;
  const int warp = threadIdx.x >> 5, lane = threadIdx.x & 31;
  uint32_t cta;
  asm volatile("mov.u32 %0, %%cluster_ctarank;" : "=r"(cta));
  const uint32_t peer = cta ^ 1u;
  const int cl = blockIdx.x >> 1;
  const bool ge_cta = cl < 2;
  const int b = ge_cta ? cl : ((cl - 2) >> 5);
  const int r0 = ge_cta ? 32 * kR : ((cl - 2) & 31) * kR;
  const int rvalid = ge_cta ? kT2 - 32 * kR : kR;

  if (warp >= 8) {
    asm volatile("setmaxnreg.dec.sync.aligned.u32 40;");
    if (warp > 8) {
      if (warp == 11 && lane < 9) asm volatile("prefetch.tensormap [%0];" ::"l"(reinterpret_cast<const CUtensorMap*>(&P) + lane) : "memory");
      __syncwarp();
      if (elect_one()) {
#pragma unroll
        for (int i = 0; i < 5; i++) if (57 + (warp - 9) * 5 + i < kBarG) init_bar(bars, 57 + (warp - 9) * 5 + i);
#pragma unroll
        for (int i = 0; i < 5; i++) if (kBarRH + (warp - 9) * 5 + i < kBarGW) mbar_init(bars + (kBarRH + (warp - 9) * 5 + i) * 8, 4);
        if (warp == 11) { mbar_init(bars + kBarGW * 8, 8); mbar_init(bars + kBarFO * 8, 8); mbar_init(bars + kBarGE * 8, 1); mbar_expect(bars + kBarGE * 8, kGEBytes); }
        asm volatile("fence.mbarrier_init.release.cluster;" ::: "memory");
      }
      __syncwarp();
      cluster_sync_relaxed();
      if (warp == 10 && ge_cta) {
        mbar_wait(bars + kBarGW * 8);
        if (elect_one()) {
          __threadfence();
          asm volatile("red.release.gpu.global.add.u32 [%0], 1;" ::"l"(&g_ge_flag[b]) : "memory");
        }
        __syncwarp();
      }
      if (warp == 11) return;
      if (warp == 10) store_pieces(P, sb, bars, 1, cta, b, r0, rvalid);
      if (warp == 10) return;
#pragma unroll
      for (int g = 0; g < 2; g++) {
        mbar_wait(bars + (kBarRH + g) * 8);
        if (elect_one()) {
          const uint32_t src = sb + kSlotH * kSlot + (2 * cta + g) * 8192;
          dsmem_copy(mapa(src, peer), src, 8192, mapa(bars + kBarHX * 8, peer));
        }
        __syncwarp();
      }
#pragma unroll
      for (int g = 0; g < 2; g++) {
        mbar_wait(bars + (kBarRF + g) * 8);
        if (elect_one()) {
          const uint32_t src = sb + kSlotF * kSlot + (2 * cta + g) * 4096;
          dsmem_copy(mapa(src, peer), src, 4096, mapa(bars + kBarFX * 8, peer));
        }
        __syncwarp();
      }
#pragma unroll
      for (int g = 0; g < 2; g++) {
        mbar_wait(bars + (kBarRE + g) * 8);
        if (elect_one())
          dsmem_copy(mapa(sb + kSlotFE * kSlot + (2 * cta + g) * 4096, peer), sb + kSlotH * kSlot + g * 4096, 4096, mapa(bars + kBarFE * 8, peer));
        __syncwarp();
      }
      store_pieces(P, sb, bars, 0, cta, b, r0, rvalid);
      return;
    }
    TS(2, 0);
    GT(0);
    unsigned int ticket = 0;
    const int par = cta == 0 ? 1 : 0;
    const int q0 = cta == 0 ? 2 * r0 - 2 : 2 * r0 - 1;
    if (elect_one()) {
      mbar_init(bars + kBarX * 8, 1); mbar_expect(bars + kBarX * 8, 16384);
      mbar_init(bars + kBarW * 8, 1); mbar_expect(bars + kBarW * 8, 16384);
      fence_async_smem();
      tma_load_4d(sb, &P.x, bars + kBarX * 8, 0, 1, 2 * r0 - 2, b);
      tma_load_4d(sb + 8192, &P.x, bars + kBarX * 8, 0, 0, 2 * r0 - 1, b);
      tma_load_3d(sb + unit_slot(0) * kSlot, &P.w1, bars + kBarW * 8, 0, 0, 2 * cta);
      TS(2, 7);
#pragma unroll
      for (int i = 1; i < 9; i++) if (i != kBarW) { mbar_init(bars + i * 8, 1); mbar_expect(bars + i * 8, 16384); }
      if (ge_cta) { mbar_init(bars + kBarG * 8, 1); mbar_expect(bars + kBarG * 8, 4 * 16384 + 4096); mbar_init(bars + kBarP0 * 8, 8); }
      asm volatile("fence.mbarrier_init.release.cluster;" ::: "memory");
      fence_async_smem();
      TS(2, 8);
      if (ge_cta) {
        tma_load_3d(sb + kOffG, &P.g, bars + kBarG * 8, 0, b * 8, 0);
#pragma unroll
        for (int i = 0; i < 4; i++) tma_load_3d(sb + (9 + i) * kSlot, &P.wg, bars + kBarG * 8, 0, i * 64, 2 * cta);
      }
#pragma unroll
      for (int u = 1; u < 5; u++)
        tma_load_3d(sb + unit_slot(u) * kSlot, &P.w1, bars + (kBarW + u) * 8, 0, (u % 3) * 256 + (u / 3) * 64, 2 * cta);
      TS(2, 10);
    }
    __syncwarp();
    TS(2, 6);
    cluster_sync_relaxed();
    TS(2, 1);
    if (elect_one()) {
#pragma unroll
      for (int p = 1; p < XFIRST; p++)
        tma_load_4d_mc(sb + p * kSlot + cta * 8192, &P.x, bars + (kBarX + p) * 8, p * 64, par, q0, b, (uint16_t)3);
    }
    __syncwarp();
    if (lane == 0) ticket = atomicAdd(&g_cta_count, 1u);
#pragma unroll
    for (int p = XFIRST; p < 4; p++) {
      if (XSTEP == 1 || ((p - XFIRST) & 1) == 0) mbar_wait(bars + (kBarX + p - XFIRST) * 8);
      if (ge_cta && p == 3) mbar_wait(bars + kBarP0 * 8);
      if (elect_one())
        tma_load_4d_mc(sb + p * kSlot + cta * 8192, &P.x, bars + (kBarX + p) * 8, p * 64, par, q0, b, (uint16_t)3);
      __syncwarp();
    }
#pragma unroll
    for (int u = 5; u < 36; u++) {
      if (unit_wait(u) != unit_wait(u - 1)) mbar_wait(bars + (kBarE + unit_wait(u)) * 8);
      if (u == 27) ticket = __shfl_sync(0xffffffffu, ticket, 0);
      if (elect_one()) {
        const uint32_t dst = sb + unit_slot(u) * kSlot, bar = bars + (kBarW + u) * 8;
        if (u < 12) tma_load_3d(dst, &P.w1, bar, 0, (u % 3) * 256 + (u / 3) * 64, 2 * cta);
        else if (u < 24) tma_load_3d(dst, &P.w2, bar, 0, ((u - 12) % 3) * 256 + ((2 * cta + (u - 12) / 3) & 3) * 64, 2 * cta);
        else if (u < 28) tma_load_3d(dst, &P.wf, bar, 0, ((2 * cta + (u - 24)) & 3) * 64, 2 * cta);
        else tma_load_3d(dst, &P.wo, bar, 0, ((2 * cta + (u - 28)) & 3) * 64, ((u - 28) >> 2) * 2);
        if (u == 27) {
          const unsigned int want = (ticket / kNumCtas + 1u) * 2u;
          const long long t0 = clock64();
          unsigned int v;
          do {
            asm volatile("ld.acquire.gpu.global.u32 %0, [%1];" : "=r"(v) : "l"(&g_ge_flag[b]) : "memory");
          } while ((int)(v - want) < 0 && clock64() - t0 < 4000000ll);
          asm volatile("fence.proxy.async;" ::: "memory");
          bulk_load(sb + kOffGE, reinterpret_cast<const char*>(g_ge) + b * kGEBytes, kGEBytes, bars + kBarGE * 8);
        }
      }
      __syncwarp();
      if (u == 11) TS(2, 2);
      if (u == 23) TS(2, 3);
      if (u == 27) TS(2, 4);
      if (u == 35) TS(2, 5);
    }
  } else {
    asm volatile("setmaxnreg.inc.sync.aligned.u32 232;");
    const int wg = warp >> 2, w = warp & 3;
    const int gq = lane >> 2, q = lane & 3;
    const uint32_t panel = 2 * cta + wg;
    const int ch = panel * 64 + w * 16 + gq;
    const uint32_t dA = desc_lo(sb + wg * 8192, 8192);
    const uint32_t dB = desc_lo(sb, 16);
    const uint32_t dBo = desc_lo(sb + cta * 2 * 8192, 16), dBp = desc_lo(sb + (cta ^ 1) * 2 * 8192, 16);
    const uint32_t dFo = desc_lo(sb + cta * 2 * 4096, 16), dFp = desc_lo(sb + (cta ^ 1) * 2 * 4096, 16);
    if (elect_one()) {
#pragma unroll
      for (int i = 0; i < 6; i++) init_bar(bars, 9 + warp * 6 + i);
      asm volatile("fence.mbarrier_init.release.cluster;" ::: "memory");
    }
    __syncwarp();
    cluster_sync_relaxed();
    if (w == 0) TS(wg, 0);

    if (ge_cta) {
      float ga[4];
      mbar_wait(bars + kBarG * 8);
      wg_fence();
#pragma unroll
      for (int i = 0; i < 4; i++) {
#pragma unroll
        for (int s = 0; s < 4; s++)
          wgmma_ss_n8(ga, desc_at(dA, (9 + i) * kSlot + s * 2048), desc_at(dB, kOffG + i * 1024 + s * 32), (i | s) != 0);
      }
      wg_commit();
      wg_wait<0>();
      if (lane == 0) mbar_arrive(bars + kBarP0 * 8);
      float* gp = g_ge + b * (kGEBytes / 4) + ((ch & 7) >> 1) * (kGEPitch / 4) + (ch >> 4) * 4 + (ch & 1);
      gp[(2 * q) * 4 * (kGEPitch / 4)] = ga[0];
      gp[(2 * q + 1) * 4 * (kGEPitch / 4)] = ga[1];
      gp[(2 * q) * 4 * (kGEPitch / 4) + 2] = ga[2];
      gp[(2 * q + 1) * 4 * (kGEPitch / 4) + 2] = ga[3];
      __syncwarp();
      if (lane == 0) mbar_arrive(bars + kBarGW * 8);
    }

    {
      float acc[32];
#pragma unroll
      for (int u = 0; u < 12; u++) {
        const int p = u / 3, tap = u % 3;
        if (SKEW1 > 0 && u == 12 - SKEW1) bar_sync_pred5(wg == 1);
        if (tap == 0) mbar_wait(bars + (kBarX + p) * 8);
        mbar_wait(bars + (kBarW + u) * 8);
        if (u == 0 && w == 0) TS(wg, 1);
        wg_fence();
#pragma unroll
        for (int s = 0; s < 4; s++)
          wgmma_ss_n64(acc, desc_at(dA, unit_slot(u) * kSlot + s * 2048),
                       desc_at(dB, p * kSlot + (tap == 1 ? 8192 : (tap == 2 ? 128 : 0)) + s * 32), (u | s) != 0);
        wg_commit();
        if (SKEW1 > 0 && u == 11) bar_arrive_pred5(wg == 0);
        if (u > 0) {
          wg_wait<1>();
          if (lane == 0) mbar_arrive(bars + (kBarE + u - 1) * 8);
        }
      }
      wg_wait<0>();
      if (lane == 0) mbar_arrive(bars + (kBarE + 11) * 8);
      if (w == 0) TS(wg, 2);
      const uint32_t hp = sb + kSlotH * kSlot + panel * 8192;
      const int mi = lane >> 3, l8 = lane & 7;
#pragma unroll
      for (int jb = 0; jb < 8; jb += 2) {
        uint32_t r[4];
#pragma unroll
        for (int t = 0; t < 2; t++) {
          r[2 * t + 0] = pack_bf16(gelu_tanh(acc[4 * (jb + t) + 0]), gelu_tanh(acc[4 * (jb + t) + 1]));
          r[2 * t + 1] = pack_bf16(gelu_tanh(acc[4 * (jb + t) + 2]), gelu_tanh(acc[4 * (jb + t) + 3]));
        }
        const int n = 8 * (jb + (mi >> 1)) + l8;
        const int row = n >> 1, chunk = 2 * w + (mi & 1);
        stsm_x4_trans(hp + (n & 1) * 4096 + row * 128 + ((chunk ^ (row & 7)) << 4), r[0], r[1], r[2], r[3]);
      }
      fence_async_smem();
      __syncwarp();
      if (lane == 0) mbar_arrive(bars + (kBarRH + wg) * 8);
      if (w == 0) TS(wg, 3);
    }
    {
      float acc[16];
#pragma unroll
      for (int v = 0; v < 12; v++) {
        const int i = v / 3, tap = v % 3;
        if (SKEW2 > 0 && v == 12 - SKEW2) bar_sync_pred6(wg == 1);
        if (v == 0) mbar_wait(bars + kBarRH * 8);
        if (v == 3) mbar_wait(bars + (kBarRH + 1) * 8);
        if (v == 6) { mbar_wait_cluster(bars + kBarHX * 8); if (w == 0) TS(wg, 4); }
        mbar_wait(bars + (kBarW + 12 + v) * 8);
        wg_fence();
#pragma unroll
        for (int s = 0; s < 4; s++)
          wgmma_ss_n32(acc, desc_at(dA, unit_slot(12 + v) * kSlot + s * 2048),
                       desc_at(i < 2 ? dBo : dBp, kSlotH * kSlot + (i & 1) * 8192 + (tap == 1 ? 4096 : (tap == 2 ? 128 : 0)) + s * 32), (v | s) != 0);
        wg_commit();
        if (SKEW2 > 0 && v == 11) bar_arrive_pred6(wg == 0);
        if (v > 0) {
          wg_wait<1>();
          if (lane == 0) mbar_arrive(bars + (kBarE + 12 + v - 1) * 8);
        }
      }
      wg_wait<0>();
      if (lane == 0) mbar_arrive(bars + (kBarE + 23) * 8);
      if (w == 0) TS(wg, 5);
      const uint32_t fp = sb + kSlotF * kSlot + panel * 4096;
      const int mi = lane >> 3, l8 = lane & 7;
#pragma unroll
      for (int jb = 0; jb < 4; jb += 2) {
        uint32_t r[4];
#pragma unroll
        for (int t = 0; t < 2; t++) {
          r[2 * t + 0] = pack_bf16(gelu_tanh(acc[4 * (jb + t) + 0]), gelu_tanh(acc[4 * (jb + t) + 1]));
          r[2 * t + 1] = pack_bf16(gelu_tanh(acc[4 * (jb + t) + 2]), gelu_tanh(acc[4 * (jb + t) + 3]));
        }
        const int n = 8 * (jb + (mi >> 1)) + l8;
        const int chunk = 2 * w + (mi & 1);
        stsm_x4_trans(fp + n * 128 + ((chunk ^ (n & 7)) << 4), r[0], r[1], r[2], r[3]);
      }
      fence_async_smem();
      __syncwarp();
      if (lane == 0) mbar_arrive(bars + (kBarRF + wg) * 8);
      if (w == 0) TS(wg, 6);
    }
    {
      float acc[16];
#pragma unroll
      for (int i = 0; i < 4; i++) {
        if (i < 2) mbar_wait(bars + (kBarRF + i) * 8);
        if (i == 2) { mbar_wait_cluster(bars + kBarFX * 8); if (w == 0) TS(wg, 7); }
        mbar_wait(bars + (kBarW + 24 + i) * 8);
        wg_fence();
#pragma unroll
        for (int s = 0; s < 4; s++)
          wgmma_ss_n32(acc, desc_at(dA, unit_slot(24 + i) * kSlot + s * 2048),
                       desc_at(i < 2 ? dFo : dFp, kSlotF * kSlot + (i & 1) * 4096 + s * 32), (i | s) != 0);
        wg_commit();
        if (i > 0) {
          wg_wait<1>();
          if (lane == 0) mbar_arrive(bars + (kBarE + 24 + i - 1) * 8);
        }
      }
      wg_wait<0>();
      if (w == 0) TS(wg, 8);
      const uint32_t qk = gq >> 1;
      const uint32_t off0 = qk * 128 + (((2 * w) ^ (2 * qk)) << 4) + (gq & 1) * 8;
      const uint32_t off1 = qk * 128 + (((2 * w + 1) ^ (2 * qk)) << 4) + (gq & 1) * 8;
      const uint32_t own = sb + kSlotFE * kSlot + panel * 4096;
      const uint32_t stg = sb + kSlotH * kSlot + wg * 4096;
#pragma unroll
      for (int jb = 0; jb < 4; jb++) {
        const uint32_t base = (((uint32_t)(jb >> 1) == cta) ? own : stg) + (4 * (jb & 1) + q) * 512;
        sts64(base + off0, acc[4 * jb + 0], acc[4 * jb + 1]);
        sts64(base + off1, acc[4 * jb + 2], acc[4 * jb + 3]);
      }
      fence_async_smem();
      __syncwarp();
      if (lane == 0) { mbar_arrive(bars + (kBarRE + wg) * 8); mbar_arrive(bars + kBarFO * 8); }
      if (w == 0) TS(wg, 9);
    }
    const int rl0 = cta * 16 + wg * 8;
    mbar_wait(bars + kBarFO * 8);
    mbar_wait(bars + kBarGE * 8);
    if (wg == 1) asm volatile("bar.sync 4, 256;" ::: "memory");
    if (rl0 < rvalid) {
      if (w == 0) TS(wg, 10);
      const uint32_t fe_row = sb + kSlotFE * kSlot + ((4 * wg + w) * 4 + q) * 128;
      const uint32_t fe_h[2] = {fe_row + cta * 8192, fe_row + (cta ^ 1) * 8192};
      const uint32_t ge_h[2] = {sb + kOffGE + lane * kGEPitch + cta * 128, sb + kOffGE + lane * kGEPitch + (cta ^ 1) * 128};
      const int mi = lane >> 3, l8 = lane & 7;
      const uint32_t st = sb + (16 * w + (mi & 1) * 8 + l8) * 128;
      uint32_t A[64];
      float acc[2][32];
      {
        constexpr int PD = 3;
        float4 fa[PD], fb[PD], gg[PD];
#pragma unroll
        for (int kk = 0; kk < 16 + PD; kk++) {
          if (kk >= PD) {
            const int k = kk - PD, sl = k % PD;
            A[4 * k + 0] = tanh2_pack(fa[sl].x + gg[sl].x, fa[sl].z + gg[sl].y);
            A[4 * k + 1] = tanh2_pack(fa[sl].y + gg[sl].x, fa[sl].w + gg[sl].y);
            A[4 * k + 2] = tanh2_pack(fb[sl].x + gg[sl].z, fb[sl].z + gg[sl].w);
            A[4 * k + 3] = tanh2_pack(fb[sl].y + gg[sl].z, fb[sl].w + gg[sl].w);
          }
          if (kk < 16) {
            const int sl = kk % PD;
            if (kk == 8) mbar_wait_cluster(bars + kBarFE * 8);
            fa[sl] = lds128(fe_h[kk >> 3] + ((kk >> 2) & 1) * 4096 + ((((kk & 3) * 2) ^ (2 * q)) << 4));
            fb[sl] = lds128(fe_h[kk >> 3] + ((kk >> 2) & 1) * 4096 + ((((kk & 3) * 2 + 1) ^ (2 * q)) << 4));
            gg[sl] = lds128(ge_h[kk >> 3] + (kk & 7) * 16);
          }
        }
      }
      asm volatile("barrier.cluster.arrive.relaxed.aligned;" ::: "memory");
#pragma unroll
      for (int kk = 0; kk < 16; kk++) {
        if ((kk & 3) == 0) { mbar_wait(bars + (kBarW + 28 + (kk >> 2)) * 8); wg_fence(); }
        wgmma_rs_n64(acc[0], A[4 * kk], A[4 * kk + 1], A[4 * kk + 2], A[4 * kk + 3],
                     desc_at(dB, unit_slot(28 + (kk >> 2)) * kSlot + (kk & 3) * 2048), kk != 0);
        if (kk == ARRK) bar_arrive_pred(wg == 0);
      }
      wg_commit();
      wg_wait<0>();
#pragma unroll
      for (int jb = 0; jb < 8; jb += 2) {
        const uint32_t r0_ = pack_bf16(acc[0][4 * jb + 0], acc[0][4 * jb + 1]), r1_ = pack_bf16(acc[0][4 * jb + 2], acc[0][4 * jb + 3]);
        const uint32_t r2_ = pack_bf16(acc[0][4 * jb + 4], acc[0][4 * jb + 5]), r3_ = pack_bf16(acc[0][4 * jb + 6], acc[0][4 * jb + 7]);
        stsm_x4(st + (wg ? stage_off(1, 0) : stage_off(0, 0)) + (((jb + (mi >> 1)) ^ l8) << 4), r0_, r1_, r2_, r3_);
      }
      fence_async_smem();
      __syncwarp();
      mbar_arrive_pred(bars + (kBarPR + wg * 4) * 8, lane == 0);
      if (w == 0) TS(wg, 11);
#pragma unroll
      for (int j = 0; j < 4; j++) {
        const int jn = j + 1;
        if (jn == 2) {
#pragma unroll
          for (int i = 0; i < 4; i++) mbar_wait(bars + (kBarW + 32 + i) * 8);
        }
        if (j < 3) wg_fence();
        const uint32_t stj = st + (wg ? stage_off(1, j) : stage_off(0, j));
#pragma unroll
        for (int kk = 0; kk < 16; kk++) {
          if (j < 3)
            wgmma_rs_n64(acc[jn & 1], A[4 * kk], A[4 * kk + 1], A[4 * kk + 2], A[4 * kk + 3],
                         desc_at(dB, unit_slot(28 + (jn >> 1) * 4 + (kk >> 2)) * kSlot + (jn & 1) * 8192 + (kk & 3) * 2048), kk != 0);
          if (kk == 1 && j > 0) {
            if (j < 3) { wg_commit(); wg_wait<1>(); } else { wg_wait<0>(); }
          }
          if (j > 0 && kk >= 2 && kk < 10 && (kk & 1) == 0) {
            const int jb = kk - 2;
            const uint32_t r0_ = pack_bf16(acc[j & 1][4 * jb + 0], acc[j & 1][4 * jb + 1]), r1_ = pack_bf16(acc[j & 1][4 * jb + 2], acc[j & 1][4 * jb + 3]);
            const uint32_t r2_ = pack_bf16(acc[j & 1][4 * jb + 4], acc[j & 1][4 * jb + 5]), r3_ = pack_bf16(acc[j & 1][4 * jb + 6], acc[j & 1][4 * jb + 7]);
            stsm_x4(stj + (((jb + (mi >> 1)) ^ l8) << 4), r0_, r1_, r2_, r3_);
          }
          if (j > 0 && kk == 9) {
            fence_async_smem();
            __syncwarp();
            mbar_arrive_pred(bars + (kBarPR + wg * 4 + j) * 8, lane == 0);
          }
        }
        if (j < 3) wg_commit();
        if (j == 0 && w == 0) TS(wg, 12);
        if (j == 2 && w == 0) TS(wg, 13);
      }
      if (w == 0) TS(wg, 14);
    } else {
      if (wg == 0) asm volatile("bar.arrive 4, 256;" ::: "memory");
      mbar_wait_cluster(bars + kBarFE * 8);
      asm volatile("barrier.cluster.arrive.relaxed.aligned;" ::: "memory");
    }
    asm volatile("barrier.cluster.wait.aligned;" ::: "memory");
  }
}

typedef CUresult (*EncodeFn)(CUtensorMap*, CUtensorMapDataType, cuuint32_t, void*, const cuuint64_t*, const cuuint64_t*,
                             const cuuint32_t*, const cuuint32_t*, CUtensorMapInterleave, CUtensorMapSwizzle,
                             CUtensorMapL2promotion, CUtensorMapFloatOOBfill);

void make_map3(EncodeFn enc, CUtensorMap* tm, const void* ptr, uint64_t rows, uint32_t box_rows, uint32_t box_panels) {
  cuuint64_t gd[3] = {64, rows, 4};
  cuuint64_t gs[2] = {512, 128};
  cuuint32_t bd[3] = {64, box_rows, box_panels};
  cuuint32_t es[3] = {1, 1, 1};
  enc(tm, CU_TENSOR_MAP_DATA_TYPE_BFLOAT16, 3, const_cast<void*>(ptr), gd, gs, bd, es, CU_TENSOR_MAP_INTERLEAVE_NONE,
      CU_TENSOR_MAP_SWIZZLE_128B, CU_TENSOR_MAP_L2_PROMOTION_L2_256B, CU_TENSOR_MAP_FLOAT_OOB_FILL_NONE);
}

}

extern "C" void kernel_launch(void* const* d_in, const int* in_sizes, int n_in, void* d_out, int out_size) {
  static EncodeFn enc = nullptr;
  if (!enc) {
    cudaDriverEntryPointQueryResult qr;
    cudaGetDriverEntryPoint("cuTensorMapEncodeTiled", (void**)&enc, cudaEnableDefault, &qr);
    cudaFuncSetAttribute(rnnt_joint_kernel, cudaFuncAttributeMaxDynamicSharedMemorySize, kSmemBytes);
  }
  Params P;
  {
    cuuint64_t gd[4] = {256, 2, 2000, 2};
    cuuint64_t gs[3] = {512, 1024, 4000ull * 512};
    cuuint32_t bd[4] = {64, 1, 64, 1};
    cuuint32_t es[4] = {1, 1, 1, 1};
    enc(&P.x, CU_TENSOR_MAP_DATA_TYPE_BFLOAT16, 4, d_in[0], gd, gs, bd, es, CU_TENSOR_MAP_INTERLEAVE_NONE,
        CU_TENSOR_MAP_SWIZZLE_128B, XPROMO, CU_TENSOR_MAP_FLOAT_OOB_FILL_NONE);
  }
  P.xptr = d_in[0];
  make_map3(enc, &P.w1, d_in[1], 768, 64, 2);
  make_map3(enc, &P.w2, d_in[2], 768, 64, 2);
  make_map3(enc, &P.g, d_in[3], 16, 8, 4);
  make_map3(enc, &P.wf, d_in[4], 256, 64, 2);
  make_map3(enc, &P.wg, d_in[5], 256, 64, 2);
  make_map3(enc, &P.wo, d_in[6], 256, 64, 2);
  make_map3(enc, &P.out64, d_out, 16000, 64, 1);
  make_map3(enc, &P.out56, d_out, 16000, 56, 1);
  rnnt_joint_kernel<<<kNumCtas, kThreads, kSmemBytes>>>(P);
}
```

```cpp
#include <cuda_runtime.h>
#include <cuda_bf16.h>
#include <cuda.h>
#include <stdint.h>

#define ARRK 3
#define XBULK 0
#define SKEW1 2
#define SKEW2 2
#define TSPLIT 1
#define XPREF 1
#define XFIRST 3
#define XSTEP 1
#define XPROMO CU_TENSOR_MAP_L2_PROMOTION_L2_128B
namespace {

constexpr int kT2 = 1000;
constexpr int kR = 31;
constexpr int kNumCtas = 132;
constexpr int kThreads = 384;
constexpr int kSlot = 16384;

constexpr int kSlotFE = 9, kSlotF = 10, kSlotH = 11;
constexpr int kOffG = 13 * kSlot;
constexpr int kOffGE = kOffG + 4096;
constexpr int kGEPitch = 272;
constexpr int kGEBytes = 32 * kGEPitch;
constexpr int kOffBar = kOffGE + kGEBytes;
constexpr int kBarX = 0;
constexpr int kBarW = 4;
constexpr int kBarE = 40;
constexpr int kBarHX = 67, kBarFX = 68, kBarFE = 69, kBarG = 70, kBarP0 = 71;
constexpr int kBarRH = 72, kBarRF = 74, kBarRE = 76;
constexpr int kBarPR = 78;
constexpr int kBarGW = 86;
constexpr int kBarFO = 87;
constexpr int kBarGE = 88;
constexpr int kNumBars = 89;
constexpr int kSmemBytes = kOffBar + kNumBars * 8 + 1024;

__device__ __align__(128) float g_ge[2 * kGEBytes / 4];
__device__ unsigned int g_ge_flag[2];
__device__ unsigned int g_cta_count;

#define TS(slot_, idx_) do {} while (0)
#define GT(idx_) do {} while (0)
#define TS_DUMP(slot_, lo_, hi_) do {} while (0)
#define GT_DUMP(idx_) do {} while (0)

__device__ __forceinline__ uint32_t smem_u32(const void* p) { return (uint32_t)__cvta_generic_to_shared(p); }
__device__ __forceinline__ void mbar_init(uint32_t a, uint32_t c) { asm volatile("mbarrier.init.shared.b64 [%0], %1;" ::"r"(a), "r"(c) : "memory"); }
__device__ __forceinline__ void mbar_expect(uint32_t a, uint32_t b) { asm volatile("mbarrier.arrive.expect_tx.shared.b64 _, [%0], %1;" ::"r"(a), "r"(b) : "memory"); }
__device__ __forceinline__ void mbar_arrive(uint32_t a) { asm volatile("mbarrier.arrive.shared.b64 _, [%0];" ::"r"(a) : "memory"); }
__device__ __forceinline__ void mbar_arrive_pred(uint32_t a, bool p) {
  asm volatile("{\n.reg .pred q;\nsetp.ne.u32 q, %1, 0;\n@q mbarrier.arrive.shared.b64 _, [%0];\n}\n" ::"r"(a), "r"((uint32_t)p) : "memory");
}
__device__ __forceinline__ void bar_arrive_pred(bool p) {
  asm volatile("{\n.reg .pred q;\nsetp.ne.u32 q, %0, 0;\n@q bar.arrive 4, 256;\n}\n" ::"r"((uint32_t)p) : "memory");
}
#define DEF_NAMED(ID) \
__device__ __forceinline__ void bar_arrive_pred##ID(bool p) { asm volatile("{\n.reg .pred q;\nsetp.ne.u32 q, %0, 0;\n@q bar.arrive " #ID ", 256;\n}\n" ::"r"((uint32_t)p) : "memory"); } \
__device__ __forceinline__ void bar_sync_pred##ID(bool p) { asm volatile("{\n.reg .pred q;\nsetp.ne.u32 q, %0, 0;\n@q bar.sync " #ID ", 256;\n}\n" ::"r"((uint32_t)p) : "memory"); }
DEF_NAMED(4)
DEF_NAMED(5)
DEF_NAMED(6)
__device__ __forceinline__ bool mbar_try(uint32_t a) {
  uint32_t ok;
  asm volatile("{\n.reg .pred p;\nmbarrier.try_wait.parity.shared.b64 p, [%1], 0;\nselp.u32 %0, 1, 0, p;\n}\n" : "=r"(ok) : "r"(a) : "memory");
  return ok != 0;
}
__device__ __forceinline__ bool mbar_test(uint32_t a) {
  uint32_t ok;
  asm volatile("{\n.reg .pred p;\nmbarrier.test_wait.parity.shared.b64 p, [%1], 0;\nselp.u32 %0, 1, 0, p;\n}\n" : "=r"(ok) : "r"(a) : "memory");
  return ok != 0;
}
__device__ __forceinline__ bool mbar_try_cluster(uint32_t a) {
  uint32_t ok;
  asm volatile("{\n.reg .pred p;\nmbarrier.try_wait.parity.acquire.cluster.shared.b64 p, [%1], 0;\nselp.u32 %0, 1, 0, p;\n}\n" : "=r"(ok) : "r"(a) : "memory");
  return ok != 0;
}
__device__ __forceinline__ void mbar_wait_slow(uint32_t a) {
  const long long t0 = clock64();
  while (!mbar_try(a)) { if (clock64() - t0 > 4000000ll) break; }
}
__device__ __forceinline__ void mbar_wait_cluster_slow(uint32_t a) {
  const long long t0 = clock64();
  while (!mbar_try_cluster(a)) { if (clock64() - t0 > 4000000ll) break; }
}
__device__ __forceinline__ void mbar_wait(uint32_t a) { if (!mbar_try(a)) mbar_wait_slow(a); }
__device__ __forceinline__ void mbar_wait_cluster(uint32_t a) { if (!mbar_try_cluster(a)) mbar_wait_cluster_slow(a); }
__device__ __forceinline__ uint32_t mapa(uint32_t a, uint32_t r) { uint32_t d; asm volatile("mapa.shared::cluster.u32 %0, %1, %2;" : "=r"(d) : "r"(a), "r"(r)); return d; }
__device__ __forceinline__ bool elect_one() { uint32_t p; asm volatile("{\n.reg .pred P;\nelect.sync _|P, 0xffffffff;\nselp.u32 %0, 1, 0, P;\n}\n" : "=r"(p)); return p != 0; }
__device__ __forceinline__ void fence_async_smem() { asm volatile("fence.proxy.async.shared::cta;" ::: "memory"); }
__device__ __forceinline__ void bar_consumers() { asm volatile("bar.sync 1, 256;" ::: "memory"); }
__device__ __forceinline__ void bar_wg(int wg) { asm volatile("bar.sync %0, 128;" ::"r"(2 + wg) : "memory"); }
__device__ __forceinline__ void cluster_sync_relaxed() { asm volatile("barrier.cluster.arrive.relaxed.aligned;\nbarrier.cluster.wait.aligned;" ::: "memory"); }
__device__ __forceinline__ void wg_fence() { asm volatile("wgmma.fence.sync.aligned;" ::: "memory"); }
__device__ __forceinline__ void wg_commit() { asm volatile("wgmma.commit_group.sync.aligned;" ::: "memory"); }
template <int N> __device__ __forceinline__ void wg_wait() { asm volatile("wgmma.wait_group.sync.aligned %0;" ::"n"(N) : "memory"); }

__device__ __forceinline__ void tma_load_3d(uint32_t dst, const CUtensorMap* tm, uint32_t bar, int c0, int c1, int c2) {
  asm volatile("cp.async.bulk.tensor.3d.shared::cluster.global.mbarrier::complete_tx::bytes [%0], [%1, {%3, %4, %5}], [%2];"
               ::"r"(dst), "l"(tm), "r"(bar), "r"(c0), "r"(c1), "r"(c2) : "memory");
}
__device__ __forceinline__ void tma_load_4d(uint32_t dst, const CUtensorMap* tm, uint32_t bar, int c0, int c1, int c2, int c3) {
  asm volatile("cp.async.bulk.tensor.4d.shared::cluster.global.mbarrier::complete_tx::bytes [%0], [%1, {%3, %4, %5, %6}], [%2];"
               ::"r"(dst), "l"(tm), "r"(bar), "r"(c0), "r"(c1), "r"(c2), "r"(c3) : "memory");
}
__device__ __forceinline__ void tma_load_4d_mc(uint32_t dst, const CUtensorMap* tm, uint32_t bar, int c0, int c1, int c2, int c3, uint16_t mask) {
  asm volatile("cp.async.bulk.tensor.4d.shared::cluster.global.mbarrier::complete_tx::bytes.multicast::cluster [%0], [%1, {%3, %4, %5, %6}], [%2], %7;"
               ::"r"(dst), "l"(tm), "r"(bar), "r"(c0), "r"(c1), "r"(c2), "r"(c3), "h"(mask) : "memory");
}
__device__ __forceinline__ void tma_store_3d(const CUtensorMap* tm, uint32_t src, int c0, int c1, int c2) {
  asm volatile("cp.async.bulk.tensor.3d.global.shared::cta.bulk_group [%0, {%2, %3, %4}], [%1];"
               ::"l"(tm), "r"(src), "r"(c0), "r"(c1), "r"(c2) : "memory");
}
__device__ __forceinline__ void bulk_load(uint32_t dst, const void* src, uint32_t bytes, uint32_t bar) {
  asm volatile("cp.async.bulk.shared::cluster.global.mbarrier::complete_tx::bytes [%0], [%1], %2, [%3];"
               ::"r"(dst), "l"(src), "r"(bytes), "r"(bar) : "memory");
}
__device__ __forceinline__ void dsmem_copy(uint32_t dst_remote, uint32_t src, uint32_t bytes, uint32_t bar_remote) {
  asm volatile("cp.async.bulk.shared::cluster.shared::cta.mbarrier::complete_tx::bytes [%0], [%1], %2, [%3];"
               ::"r"(dst_remote), "r"(src), "r"(bytes), "r"(bar_remote) : "memory");
}
__device__ __forceinline__ void stsm_x4_trans(uint32_t addr, uint32_t r0, uint32_t r1, uint32_t r2, uint32_t r3) {
  asm volatile("stmatrix.sync.aligned.m8n8.x4.trans.shared.b16 [%0], {%1, %2, %3, %4};" ::"r"(addr), "r"(r0), "r"(r1), "r"(r2), "r"(r3) : "memory");
}
__device__ __forceinline__ void stsm_x4(uint32_t addr, uint32_t r0, uint32_t r1, uint32_t r2, uint32_t r3) {
  asm volatile("stmatrix.sync.aligned.m8n8.x4.shared.b16 [%0], {%1, %2, %3, %4};" ::"r"(addr), "r"(r0), "r"(r1), "r"(r2), "r"(r3) : "memory");
}
__device__ __forceinline__ float2 lds64(uint32_t a) { float2 v; asm volatile("ld.shared.v2.f32 {%0, %1}, [%2];" : "=f"(v.x), "=f"(v.y) : "r"(a) : "memory"); return v; }
__device__ __forceinline__ float4 lds128(uint32_t a) { float4 v; asm volatile("ld.shared.v4.f32 {%0, %1, %2, %3}, [%4];" : "=f"(v.x), "=f"(v.y), "=f"(v.z), "=f"(v.w) : "r"(a) : "memory"); return v; }
__device__ __forceinline__ void sts64(uint32_t a, float x, float y) { asm volatile("st.shared.v2.f32 [%0], {%1, %2};" ::"r"(a), "f"(x), "f"(y) : "memory"); }
__device__ __forceinline__ float tanh_fast(float x) { float y; asm("tanh.approx.f32 %0, %1;" : "=f"(y) : "f"(x)); return y; }
__device__ __forceinline__ uint32_t tanh2_pack(float lo, float hi) {
  uint32_t r;
  asm volatile("{\n.reg .f32 a, b;\ntanh.approx.f32 a, %1;\ntanh.approx.f32 b, %2;\ncvt.rn.bf16x2.f32 %0, b, a;\n}\n" : "=r"(r) : "f"(lo), "f"(hi));
  return r;
}
__device__ __forceinline__ uint32_t pack_bf16(float lo, float hi) { uint32_t r; asm("cvt.rn.bf16x2.f32 %0, %1, %2;" : "=r"(r) : "f"(hi), "f"(lo)); return r; }
__device__ __forceinline__ float gelu_tanh(float x) {
  const float k0 = 0.7978845608028654f, k1 = 0.7978845608028654f * 0.044715f;
  float u = x * fmaf(x * x, k1, k0);
  float hx = 0.5f * x;
  return fmaf(hx, tanh_fast(u), hx);
}
__device__ __forceinline__ uint64_t make_desc(uint32_t addr, uint32_t lbo, uint32_t sbo) {
  return (uint64_t)((addr & 0x3FFFF) >> 4) | ((uint64_t)(lbo >> 4) << 16) | ((uint64_t)(sbo >> 4) << 32) | ((uint64_t)1 << 62);
}

__device__ __forceinline__ uint32_t desc_lo(uint32_t addr, uint32_t lbo) { return ((addr & 0x3FFFF) >> 4) | ((lbo >> 4) << 16); }
__device__ __forceinline__ uint64_t desc_at(uint32_t lo, uint32_t off) { return ((uint64_t)0x40000040u << 32) | (uint64_t)(lo + (off >> 4)); }

__device__ __forceinline__ void wgmma_ss_n64(float (&d)[32], uint64_t da, uint64_t db, int scale_d) {
  asm volatile("{\n.reg .pred p;\nsetp.ne.b32 p, %34, 0;\n"
    "wgmma.mma_async.sync.aligned.m64n64k16.f32.bf16.bf16 {%0, %1, %2, %3, %4, %5, %6, %7, %8, %9, %10, %11, %12, %13, %14, %15, %16, %17, %18, %19, %20, %21, %22, %23, %24, %25, %26, %27, %28, %29, %30, %31}, %32, %33, p, 1, 1, 1, 0;\n}\n"
    : "+f"(d[0]), "+f"(d[1]), "+f"(d[2]), "+f"(d[3]), "+f"(d[4]), "+f"(d[5]), "+f"(d[6]), "+f"(d[7]), "+f"(d[8]), "+f"(d[9]), "+f"(d[10]), "+f"(d[11]), "+f"(d[12]), "+f"(d[13]), "+f"(d[14]), "+f"(d[15]), "+f"(d[16]), "+f"(d[17]), "+f"(d[18]), "+f"(d[19]), "+f"(d[20]), "+f"(d[21]), "+f"(d[22]), "+f"(d[23]), "+f"(d[24]), "+f"(d[25]), "+f"(d[26]), "+f"(d[27]), "+f"(d[28]), "+f"(d[29]), "+f"(d[30]), "+f"(d[31])
    : "l"(da), "l"(db), "r"(scale_d));
}

__device__ __forceinline__ void wgmma_ss_n32(float (&d)[16], uint64_t da, uint64_t db, int scale_d) {
  asm volatile("{\n.reg .pred p;\nsetp.ne.b32 p, %18, 0;\n"
    "wgmma.mma_async.sync.aligned.m64n32k16.f32.bf16.bf16 {%0, %1, %2, %3, %4, %5, %6, %7, %8, %9, %10, %11, %12, %13, %14, %15}, %16, %17, p, 1, 1, 1, 0;\n}\n"
    : "+f"(d[0]), "+f"(d[1]), "+f"(d[2]), "+f"(d[3]), "+f"(d[4]), "+f"(d[5]), "+f"(d[6]), "+f"(d[7]), "+f"(d[8]), "+f"(d[9]), "+f"(d[10]), "+f"(d[11]), "+f"(d[12]), "+f"(d[13]), "+f"(d[14]), "+f"(d[15])
    : "l"(da), "l"(db), "r"(scale_d));
}

__device__ __forceinline__ void wgmma_ss_n8(float (&d)[4], uint64_t da, uint64_t db, int scale_d) {
  asm volatile("{\n.reg .pred p;\nsetp.ne.b32 p, %6, 0;\n"
    "wgmma.mma_async.sync.aligned.m64n8k16.f32.bf16.bf16 {%0, %1, %2, %3}, %4, %5, p, 1, 1, 1, 0;\n}\n"
    : "+f"(d[0]), "+f"(d[1]), "+f"(d[2]), "+f"(d[3])
    : "l"(da), "l"(db), "r"(scale_d));
}

__device__ __forceinline__ void wgmma_rs_n64(float (&d)[32], uint32_t a0, uint32_t a1, uint32_t a2, uint32_t a3, uint64_t db, int scale_d) {
  asm volatile("{\n.reg .pred p;\nsetp.ne.b32 p, %37, 0;\n"
    "wgmma.mma_async.sync.aligned.m64n64k16.f32.bf16.bf16 {%0, %1, %2, %3, %4, %5, %6, %7, %8, %9, %10, %11, %12, %13, %14, %15, %16, %17, %18, %19, %20, %21, %22, %23, %24, %25, %26, %27, %28, %29, %30, %31}, {%32, %33, %34, %35}, %36, p, 1, 1, 1;\n}\n"
    : "+f"(d[0]), "+f"(d[1]), "+f"(d[2]), "+f"(d[3]), "+f"(d[4]), "+f"(d[5]), "+f"(d[6]), "+f"(d[7]), "+f"(d[8]), "+f"(d[9]), "+f"(d[10]), "+f"(d[11]), "+f"(d[12]), "+f"(d[13]), "+f"(d[14]), "+f"(d[15]), "+f"(d[16]), "+f"(d[17]), "+f"(d[18]), "+f"(d[19]), "+f"(d[20]), "+f"(d[21]), "+f"(d[22]), "+f"(d[23]), "+f"(d[24]), "+f"(d[25]), "+f"(d[26]), "+f"(d[27]), "+f"(d[28]), "+f"(d[29]), "+f"(d[30]), "+f"(d[31])
    : "r"(a0), "r"(a1), "r"(a2), "r"(a3), "l"(db), "r"(scale_d));
}

__host__ __device__ constexpr int unit_slot(int u) {
  constexpr int t[36] = {4, 5, 6, 7, 8, 4, 5, 6, 0, 7, 8, 4,  1, 5, 6, 0, 2, 7, 8, 4, 3, 1, 5, 6,
                         0, 2, 7, 8,  4, 3, 1, 5, 6, 0, 2, 7};
  return t[u];
}
__host__ __device__ constexpr int unit_wait(int u) {
  constexpr int t[36] = {-1, -1, -1, -1, -1, 0, 1, 2, 2, 3, 4, 5,  5, 6, 7, 8, 8, 9, 10, 11, 11, 12, 13, 14,
                         15, 16, 17, 18,  19, 20, 21, 22, 23, 24, 25, 26};
  return t[u];
}

__device__ __forceinline__ uint32_t stage_off(int g, int j) {
  return g == 0 ? (j < 2 ? 8 * kSlot + j * 8192 : 10 * kSlot + (j - 2) * 8192)
                : (j < 2 ? 12 * kSlot + j * 8192 : (j == 2 ? 11 * kSlot + 8192 : 9 * kSlot));
}

struct Params {
  CUtensorMap x, w1, w2, wf, wg, wo, g, out64, out56;
  const void* xptr;
};

__device__ __forceinline__ void init_bar(uint32_t bars, int i) {
  const uint32_t a = bars + i * 8;
  const bool is_e = (i >= kBarE && i < kBarE + 27);
  mbar_init(a, is_e ? 8 : 1);
  if (!is_e) {
    uint32_t bytes = 16384;
    if (i == kBarFX) bytes = 8192;
    if (i == kBarFE) bytes = 8192;
    mbar_expect(a, bytes);
  }
}

__device__ __forceinline__ void store_pieces(const Params& P, uint32_t sb, uint32_t bars, int g, uint32_t cta, int b, int r0, int rvalid) {
  const int rl0 = cta * 16 + g * 8;
  if (rl0 >= rvalid) return;
  const CUtensorMap* omap = (rl0 + 8 <= rvalid) ? &P.out64 : &P.out56;
#pragma unroll
  for (int j = 0; j < 4; j++) {
    mbar_wait(bars + (kBarPR + g * 4 + j) * 8);
    if (elect_one()) {
      tma_store_3d(omap, sb + stage_off(g, j), 0, (b * kT2 + r0 + rl0) * 8, j);
      asm volatile("cp.async.bulk.commit_group;" ::: "memory");
    }
    __syncwarp();
    if (j == 0) TS(2, 12 + g);
    if (j == 3) TS(2, 14 + g);
  }
  if (elect_one()) asm volatile("cp.async.bulk.wait_group.read 0;" ::: "memory");
  __syncwarp();
  if (g == 1) { TS(2, 11); GT(1); TS_DUMP(2, 11, 12); GT_DUMP(1); }
  TS_DUMP(2, 12 + g, 13 + g); TS_DUMP(2, 14 + g, 15 + g);
}

__global__ void __cluster_dims__(2, 1, 1) __launch_bounds__(kThreads, 1)
rnnt_joint_kernel(const __grid_constant__ Params P) {
  extern __shared__ uint8_t smem_raw[];
  const uint32_t sb = (smem_u32(smem_raw) + 1023u) & ~1023u;
  const uint32_t bars = sb + kOffBar;
  const int warp = threadIdx.x >> 5, lane = threadIdx.x & 31;
  uint32_t cta;
  asm volatile("mov.u32 %0, %%cluster_ctarank;" : "=r"(cta));
  const uint32_t peer = cta ^ 1u;
  const int cl = blockIdx.x >> 1;
  const bool ge_cta = cl < 2;
  const int b = ge_cta ? cl : ((cl - 2) >> 5);
  const int r0 = ge_cta ? 32 * kR : ((cl - 2) & 31) * kR;
  const int rvalid = ge_cta ? kT2 - 32 * kR : kR;

  if (warp >= 8) {
    asm volatile("setmaxnreg.dec.sync.aligned.u32 40;");
    if (warp > 8) {
      if (elect_one()) {
#pragma unroll
        for (int i = 0; i < 5; i++) if (57 + (warp - 9) * 5 + i < kBarG) init_bar(bars, 57 + (warp - 9) * 5 + i);
#pragma unroll
        for (int i = 0; i < 5; i++) if (kBarRH + (warp - 9) * 5 + i < kBarGW) mbar_init(bars + (kBarRH + (warp - 9) * 5 + i) * 8, 4);
        if (warp == 11) { mbar_init(bars + kBarGW * 8, 8); mbar_init(bars + kBarFO * 8, 8); mbar_init(bars + kBarGE * 8, 1); mbar_expect(bars + kBarGE * 8, kGEBytes); }
        asm volatile("fence.mbarrier_init.release.cluster;" ::: "memory");
      }
      __syncwarp();
      asm volatile("barrier.cluster.arrive.relaxed.aligned;" ::: "memory");
      if (warp == 11 && lane < 9) asm volatile("prefetch.tensormap [%0];" ::"l"(reinterpret_cast<const CUtensorMap*>(&P) + lane) : "memory");
      __syncwarp();
      asm volatile("barrier.cluster.wait.aligned;" ::: "memory");
      if (warp == 10 && ge_cta) {
        mbar_wait(bars + kBarGW * 8);
        if (elect_one()) {
          __threadfence();
          asm volatile("red.release.gpu.global.add.u32 [%0], 1;" ::"l"(&g_ge_flag[b]) : "memory");
        }
        __syncwarp();
      }
      if (warp == 11) return;
      if (warp == 10) store_pieces(P, sb, bars, 1, cta, b, r0, rvalid);
      if (warp == 10) return;
#pragma unroll
      for (int g = 0; g < 2; g++) {
        mbar_wait(bars + (kBarRH + g) * 8);
        if (elect_one()) {
          const uint32_t src = sb + kSlotH * kSlot + (2 * cta + g) * 8192;
          dsmem_copy(mapa(src, peer), src, 8192, mapa(bars + kBarHX * 8, peer));
        }
        __syncwarp();
      }
#pragma unroll
      for (int g = 0; g < 2; g++) {
        mbar_wait(bars + (kBarRF + g) * 8);
        if (elect_one()) {
          const uint32_t src = sb + kSlotF * kSlot + (2 * cta + g) * 4096;
          dsmem_copy(mapa(src, peer), src, 4096, mapa(bars + kBarFX * 8, peer));
        }
        __syncwarp();
      }
#pragma unroll
      for (int g = 0; g < 2; g++) {
        mbar_wait(bars + (kBarRE + g) * 8);
        if (elect_one())
          dsmem_copy(mapa(sb + kSlotFE * kSlot + (2 * cta + g) * 4096, peer), sb + kSlotH * kSlot + g * 4096, 4096, mapa(bars + kBarFE * 8, peer));
        __syncwarp();
      }
      store_pieces(P, sb, bars, 0, cta, b, r0, rvalid);
      return;
    }
    TS(2, 0);
    GT(0);
    unsigned int ticket = 0;
    const int par = cta == 0 ? 1 : 0;
    const int q0 = cta == 0 ? 2 * r0 - 2 : 2 * r0 - 1;
    if (elect_one()) {
      mbar_init(bars + kBarX * 8, 1); mbar_expect(bars + kBarX * 8, 16384);
      mbar_init(bars + kBarW * 8, 1); mbar_expect(bars + kBarW * 8, 16384);
      fence_async_smem();
      tma_load_4d(sb, &P.x, bars + kBarX * 8, 0, 1, 2 * r0 - 2, b);
      tma_load_4d(sb + 8192, &P.x, bars + kBarX * 8, 0, 0, 2 * r0 - 1, b);
      tma_load_3d(sb + unit_slot(0) * kSlot, &P.w1, bars + kBarW * 8, 0, 0, 2 * cta);
      TS(2, 7);
#pragma unroll
      for (int i = 1; i < 9; i++) if (i != kBarW) { mbar_init(bars + i * 8, 1); mbar_expect(bars + i * 8, 16384); }
      if (ge_cta) { mbar_init(bars + kBarG * 8, 1); mbar_expect(bars + kBarG * 8, 4 * 16384 + 4096); mbar_init(bars + kBarP0 * 8, 8); }
      asm volatile("fence.mbarrier_init.release.cluster;" ::: "memory");
      fence_async_smem();
      TS(2, 8);
      if (ge_cta) {
        tma_load_3d(sb + kOffG, &P.g, bars + kBarG * 8, 0, b * 8, 0);
#pragma unroll
        for (int i = 0; i < 4; i++) tma_load_3d(sb + (9 + i) * kSlot, &P.wg, bars + kBarG * 8, 0, i * 64, 2 * cta);
      }
#pragma unroll
      for (int u = 1; u < 5; u++)
        tma_load_3d(sb + unit_slot(u) * kSlot, &P.w1, bars + (kBarW + u) * 8, 0, (u % 3) * 256 + (u / 3) * 64, 2 * cta);
      TS(2, 10);
    }
    __syncwarp();
    TS(2, 6);
    cluster_sync_relaxed();
    TS(2, 1);
    if (elect_one()) {
#pragma unroll
      for (int p = 1; p < XFIRST; p++)
        tma_load_4d_mc(sb + p * kSlot + cta * 8192, &P.x, bars + (kBarX + p) * 8, p * 64, par, q0, b, (uint16_t)3);
    }
    __syncwarp();
    if (lane == 0) ticket = atomicAdd(&g_cta_count, 1u);
#pragma unroll
    for (int p = XFIRST; p < 4; p++) {
      if (XSTEP == 1 || ((p - XFIRST) & 1) == 0) mbar_wait(bars + (kBarX + p - XFIRST) * 8);
      if (ge_cta && p == 3) mbar_wait(bars + kBarP0 * 8);
      if (elect_one())
        tma_load_4d_mc(sb + p * kSlot + cta * 8192, &P.x, bars + (kBarX + p) * 8, p * 64, par, q0, b, (uint16_t)3);
      __syncwarp();
    }
#pragma unroll
    for (int u = 5; u < 36; u++) {
      if (unit_wait(u) != unit_wait(u - 1)) mbar_wait(bars + (kBarE + unit_wait(u)) * 8);
      if (u == 27) ticket = __shfl_sync(0xffffffffu, ticket, 0);
      if (elect_one()) {
        const uint32_t dst = sb + unit_slot(u) * kSlot, bar = bars + (kBarW + u) * 8;
        if (u < 12) tma_load_3d(dst, &P.w1, bar, 0, (u % 3) * 256 + (u / 3) * 64, 2 * cta);
        else if (u < 24) tma_load_3d(dst, &P.w2, bar, 0, ((u - 12) % 3) * 256 + ((2 * cta + (u - 12) / 3) & 3) * 64, 2 * cta);
        else if (u < 28) tma_load_3d(dst, &P.wf, bar, 0, ((2 * cta + (u - 24)) & 3) * 64, 2 * cta);
        else tma_load_3d(dst, &P.wo, bar, 0, ((2 * cta + (u - 28)) & 3) * 64, ((u - 28) >> 2) * 2);
        if (u == 27) {
          const unsigned int want = (ticket / kNumCtas + 1u) * 2u;
          const long long t0 = clock64();
          unsigned int v;
          do {
            asm volatile("ld.acquire.gpu.global.u32 %0, [%1];" : "=r"(v) : "l"(&g_ge_flag[b]) : "memory");
          } while ((int)(v - want) < 0 && clock64() - t0 < 4000000ll);
          asm volatile("fence.proxy.async;" ::: "memory");
          bulk_load(sb + kOffGE, reinterpret_cast<const char*>(g_ge) + b * kGEBytes, kGEBytes, bars + kBarGE * 8);
        }
      }
      __syncwarp();
      if (u == 11) TS(2, 2);
      if (u == 23) TS(2, 3);
      if (u == 27) TS(2, 4);
      if (u == 35) TS(2, 5);
    }
    TS_DUMP(2, 0, 11); GT_DUMP(0);
  } else {
    asm volatile("setmaxnreg.inc.sync.aligned.u32 232;");
    const int wg = warp >> 2, w = warp & 3;
    const int gq = lane >> 2, q = lane & 3;
    const uint32_t panel = 2 * cta + wg;
    const int ch = panel * 64 + w * 16 + gq;
    const uint32_t dA = desc_lo(sb + wg * 8192, 8192);
    const uint32_t dB = desc_lo(sb, 16);
    const uint32_t dBo = desc_lo(sb + cta * 2 * 8192, 16), dBp = desc_lo(sb + (cta ^ 1) * 2 * 8192, 16);
    const uint32_t dFo = desc_lo(sb + cta * 2 * 4096, 16), dFp = desc_lo(sb + (cta ^ 1) * 2 * 4096, 16);
    if (elect_one()) {
#pragma unroll
      for (int i = 0; i < 6; i++) init_bar(bars, 9 + warp * 6 + i);
      asm volatile("fence.mbarrier_init.release.cluster;" ::: "memory");
    }
    __syncwarp();
    cluster_sync_relaxed();
    if (w == 0) TS(wg, 0);

    if (ge_cta) {
      float ga[4];
      mbar_wait(bars + kBarG * 8);
      wg_fence();
#pragma unroll
      for (int i = 0; i < 4; i++) {
#pragma unroll
        for (int s = 0; s < 4; s++)
          wgmma_ss_n8(ga, desc_at(dA, (9 + i) * kSlot + s * 2048), desc_at(dB, kOffG + i * 1024 + s * 32), (i | s) != 0);
      }
      wg_commit();
      wg_wait<0>();
      if (lane == 0) mbar_arrive(bars + kBarP0 * 8);
      float* gp = g_ge + b * (kGEBytes / 4) + ((ch & 7) >> 1) * (kGEPitch / 4) + (ch >> 4) * 4 + (ch & 1);
      gp[(2 * q) * 4 * (kGEPitch / 4)] = ga[0];
      gp[(2 * q + 1) * 4 * (kGEPitch / 4)] = ga[1];
      gp[(2 * q) * 4 * (kGEPitch / 4) + 2] = ga[2];
      gp[(2 * q + 1) * 4 * (kGEPitch / 4) + 2] = ga[3];
      __syncwarp();
      if (lane == 0) mbar_arrive(bars + kBarGW * 8);
    }

    {
      float acc[32];
#pragma unroll
      for (int u = 0; u < 12; u++) {
        const int p = u / 3, tap = u % 3;
        if (SKEW1 > 0 && u == 12 - SKEW1) bar_sync_pred5(wg == 1);
        if (tap == 0) mbar_wait(bars + (kBarX + p) * 8);
        mbar_wait(bars + (kBarW + u) * 8);
        if (u == 0 && w == 0) TS(wg, 1);
        wg_fence();
#pragma unroll
        for (int s = 0; s < 4; s++)
          wgmma_ss_n64(acc, desc_at(dA, unit_slot(u) * kSlot + s * 2048),
                       desc_at(dB, p * kSlot + (tap == 1 ? 8192 : (tap == 2 ? 128 : 0)) + s * 32), (u | s) != 0);
        wg_commit();
        if (SKEW1 > 0 && u == 11) bar_arrive_pred5(wg == 0);
        if (u > 0) {
          wg_wait<1>();
          if (lane == 0) mbar_arrive(bars + (kBarE + u - 1) * 8);
        }
      }
      wg_wait<0>();
      if (lane == 0) mbar_arrive(bars + (kBarE + 11) * 8);
      if (w == 0) TS(wg, 2);
      const uint32_t hp = sb + kSlotH * kSlot + panel * 8192;
      const int mi = lane >> 3, l8 = lane & 7;
#pragma unroll
      for (int jb = 0; jb < 8; jb += 2) {
        uint32_t r[4];
#pragma unroll
        for (int t = 0; t < 2; t++) {
          r[2 * t + 0] = pack_bf16(gelu_tanh(acc[4 * (jb + t) + 0]), gelu_tanh(acc[4 * (jb + t) + 1]));
          r[2 * t + 1] = pack_bf16(gelu_tanh(acc[4 * (jb + t) + 2]), gelu_tanh(acc[4 * (jb + t) + 3]));
        }
        const int n = 8 * (jb + (mi >> 1)) + l8;
        const int row = n >> 1, chunk = 2 * w + (mi & 1);
        stsm_x4_trans(hp + (n & 1) * 4096 + row * 128 + ((chunk ^ (row & 7)) << 4), r[0], r[1], r[2], r[3]);
      }
      __syncwarp();
      if (w == 0) TS(wg, 15);
      fence_async_smem();
      __syncwarp();
      if (lane == 0) mbar_arrive(bars + (kBarRH + wg) * 8);
      if (w == 0) TS(wg, 3);
    }
    {
      float acc[16];
#pragma unroll
      for (int v = 0; v < 12; v++) {
        const int i = v / 3, tap = v % 3;
        if (SKEW2 > 0 && v == 12 - SKEW2) bar_sync_pred6(wg == 1);
        if (v == 0) mbar_wait(bars + kBarRH * 8);
        if (v == 3) mbar_wait(bars + (kBarRH + 1) * 8);
        if (v == 6) { mbar_wait_cluster(bars + kBarHX * 8); if (w == 0) TS(wg, 4); }
        mbar_wait(bars + (kBarW + 12 + v) * 8);
        wg_fence();
#pragma unroll
        for (int s = 0; s < 4; s++)
          wgmma_ss_n32(acc, desc_at(dA, unit_slot(12 + v) * kSlot + s * 2048),
                       desc_at(i < 2 ? dBo : dBp, kSlotH * kSlot + (i & 1) * 8192 + (tap == 1 ? 4096 : (tap == 2 ? 128 : 0)) + s * 32), (v | s) != 0);
        wg_commit();
        if (SKEW2 > 0 && v == 11) bar_arrive_pred6(wg == 0);
        if (v > 0) {
          wg_wait<1>();
          if (lane == 0) mbar_arrive(bars + (kBarE + 12 + v - 1) * 8);
        }
      }
      wg_wait<0>();
      if (lane == 0) mbar_arrive(bars + (kBarE + 23) * 8);
      if (w == 0) TS(wg, 5);
      const uint32_t fp = sb + kSlotF * kSlot + panel * 4096;
      const int mi = lane >> 3, l8 = lane & 7;
#pragma unroll
      for (int jb = 0; jb < 4; jb += 2) {
        uint32_t r[4];
#pragma unroll
        for (int t = 0; t < 2; t++) {
          r[2 * t + 0] = pack_bf16(gelu_tanh(acc[4 * (jb + t) + 0]), gelu_tanh(acc[4 * (jb + t) + 1]));
          r[2 * t + 1] = pack_bf16(gelu_tanh(acc[4 * (jb + t) + 2]), gelu_tanh(acc[4 * (jb + t) + 3]));
        }
        const int n = 8 * (jb + (mi >> 1)) + l8;
        const int chunk = 2 * w + (mi & 1);
        stsm_x4_trans(fp + n * 128 + ((chunk ^ (n & 7)) << 4), r[0], r[1], r[2], r[3]);
      }
      fence_async_smem();
      __syncwarp();
      if (lane == 0) mbar_arrive(bars + (kBarRF + wg) * 8);
      if (w == 0) TS(wg, 6);
    }
    {
      float acc[16];
#pragma unroll
      for (int i = 0; i < 4; i++) {
        if (i < 2) mbar_wait(bars + (kBarRF + i) * 8);
        if (i == 2) { mbar_wait_cluster(bars + kBarFX * 8); if (w == 0) TS(wg, 7); }
        mbar_wait(bars + (kBarW + 24 + i) * 8);
        wg_fence();
#pragma unroll
        for (int s = 0; s < 4; s++)
          wgmma_ss_n32(acc, desc_at(dA, unit_slot(24 + i) * kSlot + s * 2048),
                       desc_at(i < 2 ? dFo : dFp, kSlotF * kSlot + (i & 1) * 4096 + s * 32), (i | s) != 0);
        wg_commit();
        if (i > 0) {
          wg_wait<1>();
          if (lane == 0) mbar_arrive(bars + (kBarE + 24 + i - 1) * 8);
        }
      }
      wg_wait<0>();
      if (w == 0) TS(wg, 8);
      const uint32_t qk = gq >> 1;
      const uint32_t off0 = qk * 128 + (((2 * w) ^ (2 * qk)) << 4) + (gq & 1) * 8;
      const uint32_t off1 = qk * 128 + (((2 * w + 1) ^ (2 * qk)) << 4) + (gq & 1) * 8;
      const uint32_t own = sb + kSlotFE * kSlot + panel * 4096;
      const uint32_t stg = sb + kSlotH * kSlot + wg * 4096;
#pragma unroll
      for (int jb = 0; jb < 4; jb++) {
        const uint32_t base = (((uint32_t)(jb >> 1) == cta) ? own : stg) + (4 * (jb & 1) + q) * 512;
        sts64(base + off0, acc[4 * jb + 0], acc[4 * jb + 1]);
        sts64(base + off1, acc[4 * jb + 2], acc[4 * jb + 3]);
      }
      fence_async_smem();
      __syncwarp();
      if (lane == 0) { mbar_arrive(bars + (kBarRE + wg) * 8); mbar_arrive(bars + kBarFO * 8); }
      if (w == 0) TS(wg, 9);
    }
    const int rl0 = cta * 16 + wg * 8;
    mbar_wait(bars + kBarFO * 8);
    mbar_wait(bars + kBarGE * 8);
    if (!TSPLIT && wg == 1) asm volatile("bar.sync 4, 256;" ::: "memory");
    if (rl0 < rvalid) {
      if (w == 0) TS(wg, 10);
      const uint32_t fe_row = sb + kSlotFE * kSlot + ((4 * wg + w) * 4 + q) * 128;
      const uint32_t fe_h[2] = {fe_row + cta * 8192, fe_row + (cta ^ 1) * 8192};
      const uint32_t ge_h[2] = {sb + kOffGE + lane * kGEPitch + cta * 128, sb + kOffGE + lane * kGEPitch + (cta ^ 1) * 128};
      const int mi = lane >> 3, l8 = lane & 7;
      const uint32_t st = sb + (16 * w + (mi & 1) * 8 + l8) * 128;
      uint32_t A[64];
      float acc[2][32];
      {
        constexpr int PD = 3;
        float4 fa[PD], fb[PD], gg[PD];
#pragma unroll
        for (int kk = 0; kk < 16 + PD; kk++) {
          if (kk >= PD) {
            const int k = kk - PD, sl = k % PD;
            A[4 * k + 0] = tanh2_pack(fa[sl].x + gg[sl].x, fa[sl].z + gg[sl].y);
            A[4 * k + 1] = tanh2_pack(fa[sl].y + gg[sl].x, fa[sl].w + gg[sl].y);
            A[4 * k + 2] = tanh2_pack(fb[sl].x + gg[sl].z, fb[sl].z + gg[sl].w);
            A[4 * k + 3] = tanh2_pack(fb[sl].y + gg[sl].z, fb[sl].w + gg[sl].w);
          }
          if (kk < 16) {
            const int sl = kk % PD;
            if (kk == 8) {
              if (TSPLIT) bar_sync_pred4(wg == 1);
              mbar_wait_cluster(bars + kBarFE * 8);
            }
            fa[sl] = lds128(fe_h[kk >> 3] + ((kk >> 2) & 1) * 4096 + ((((kk & 3) * 2) ^ (2 * q)) << 4));
            fb[sl] = lds128(fe_h[kk >> 3] + ((kk >> 2) & 1) * 4096 + ((((kk & 3) * 2 + 1) ^ (2 * q)) << 4));
            gg[sl] = lds128(ge_h[kk >> 3] + (kk & 7) * 16);
          }
        }
      }
      asm volatile("barrier.cluster.arrive.relaxed.aligned;" ::: "memory");
#pragma unroll
      for (int kk = 0; kk < 16; kk++) {
        if ((kk & 3) == 0) { mbar_wait(bars + (kBarW + 28 + (kk >> 2)) * 8); wg_fence(); }
        wgmma_rs_n64(acc[0], A[4 * kk], A[4 * kk + 1], A[4 * kk + 2], A[4 * kk + 3],
                     desc_at(dB, unit_slot(28 + (kk >> 2)) * kSlot + (kk & 3) * 2048), kk != 0);
        if (kk == ARRK) bar_arrive_pred(wg == 0);
      }
      wg_commit();
      wg_wait<0>();
#pragma unroll
      for (int jb = 0; jb < 8; jb += 2) {
        const uint32_t r0_ = pack_bf16(acc[0][4 * jb + 0], acc[0][4 * jb + 1]), r1_ = pack_bf16(acc[0][4 * jb + 2], acc[0][4 * jb + 3]);
        const uint32_t r2_ = pack_bf16(acc[0][4 * jb + 4], acc[0][4 * jb + 5]), r3_ = pack_bf16(acc[0][4 * jb + 6], acc[0][4 * jb + 7]);
        stsm_x4(st + (wg ? stage_off(1, 0) : stage_off(0, 0)) + (((jb + (mi >> 1)) ^ l8) << 4), r0_, r1_, r2_, r3_);
      }
      fence_async_smem();
      __syncwarp();
      mbar_arrive_pred(bars + (kBarPR + wg * 4) * 8, lane == 0);
      if (w == 0) TS(wg, 11);
#pragma unroll
      for (int j = 0; j < 4; j++) {
        const int jn = j + 1;
        if (jn == 2) {
#pragma unroll
          for (int i = 0; i < 4; i++) mbar_wait(bars + (kBarW + 32 + i) * 8);
        }
        if (j < 3) wg_fence();
        const uint32_t stj = st + (wg ? stage_off(1, j) : stage_off(0, j));
#pragma unroll
        for (int kk = 0; kk < 16; kk++) {
          if (j < 3)
            wgmma_rs_n64(acc[jn & 1], A[4 * kk], A[4 * kk + 1], A[4 * kk + 2], A[4 * kk + 3],
                         desc_at(dB, unit_slot(28 + (jn >> 1) * 4 + (kk >> 2)) * kSlot + (jn & 1) * 8192 + (kk & 3) * 2048), kk != 0);
          if (kk == 1 && j > 0) {
            if (j < 3) { wg_commit(); wg_wait<1>(); } else { wg_wait<0>(); }
          }
          if (j > 0 && kk >= 2 && kk < 10 && (kk & 1) == 0) {
            const int jb = kk - 2;
            const uint32_t r0_ = pack_bf16(acc[j & 1][4 * jb + 0], acc[j & 1][4 * jb + 1]), r1_ = pack_bf16(acc[j & 1][4 * jb + 2], acc[j & 1][4 * jb + 3]);
            const uint32_t r2_ = pack_bf16(acc[j & 1][4 * jb + 4], acc[j & 1][4 * jb + 5]), r3_ = pack_bf16(acc[j & 1][4 * jb + 6], acc[j & 1][4 * jb + 7]);
            stsm_x4(stj + (((jb + (mi >> 1)) ^ l8) << 4), r0_, r1_, r2_, r3_);
          }
          if (j > 0 && kk == 9) {
            fence_async_smem();
            __syncwarp();
            mbar_arrive_pred(bars + (kBarPR + wg * 4 + j) * 8, lane == 0);
          }
        }
        if (j < 3) wg_commit();
        if (j == 0 && w == 0) TS(wg, 12);
        if (j == 2 && w == 0) TS(wg, 13);
      }
      if (w == 0) TS(wg, 14);
    } else {
      if (wg == 0) asm volatile("bar.arrive 4, 256;" ::: "memory");
      if (TSPLIT && wg == 1) asm volatile("bar.sync 4, 256;" ::: "memory");
      mbar_wait_cluster(bars + kBarFE * 8);
      asm volatile("barrier.cluster.arrive.relaxed.aligned;" ::: "memory");
    }
    asm volatile("barrier.cluster.wait.aligned;" ::: "memory");
    if (w == 0) TS_DUMP(wg, 0, 16);
  }
}

typedef CUresult (*EncodeFn)(CUtensorMap*, CUtensorMapDataType, cuuint32_t, void*, const cuuint64_t*, const cuuint64_t*,
                             const cuuint32_t*, const cuuint32_t*, CUtensorMapInterleave, CUtensorMapSwizzle,
                             CUtensorMapL2promotion, CUtensorMapFloatOOBfill);

void make_map3(EncodeFn enc, CUtensorMap* tm, const void* ptr, uint64_t rows, uint32_t box_rows, uint32_t box_panels) {
  cuuint64_t gd[3] = {64, rows, 4};
  cuuint64_t gs[2] = {512, 128};
  cuuint32_t bd[3] = {64, box_rows, box_panels};
  cuuint32_t es[3] = {1, 1, 1};
  enc(tm, CU_TENSOR_MAP_DATA_TYPE_BFLOAT16, 3, const_cast<void*>(ptr), gd, gs, bd, es, CU_TENSOR_MAP_INTERLEAVE_NONE,
      CU_TENSOR_MAP_SWIZZLE_128B, CU_TENSOR_MAP_L2_PROMOTION_L2_256B, CU_TENSOR_MAP_FLOAT_OOB_FILL_NONE);
}

}

extern "C" void kernel_launch(void* const* d_in, const int* in_sizes, int n_in, void* d_out, int out_size) {
  static EncodeFn enc = nullptr;
  if (!enc) {
    cudaDriverEntryPointQueryResult qr;
    cudaGetDriverEntryPoint("cuTensorMapEncodeTiled", (void**)&enc, cudaEnableDefault, &qr);
    cudaFuncSetAttribute(rnnt_joint_kernel, cudaFuncAttributeMaxDynamicSharedMemorySize, kSmemBytes);
  }
  Params P;
  {
    cuuint64_t gd[4] = {256, 2, 2000, 2};
    cuuint64_t gs[3] = {512, 1024, 4000ull * 512};
    cuuint32_t bd[4] = {64, 1, 64, 1};
    cuuint32_t es[4] = {1, 1, 1, 1};
    enc(&P.x, CU_TENSOR_MAP_DATA_TYPE_BFLOAT16, 4, d_in[0], gd, gs, bd, es, CU_TENSOR_MAP_INTERLEAVE_NONE,
        CU_TENSOR_MAP_SWIZZLE_128B, XPROMO, CU_TENSOR_MAP_FLOAT_OOB_FILL_NONE);
  }
  P.xptr = d_in[0];
  make_map3(enc, &P.w1, d_in[1], 768, 64, 2);
  make_map3(enc, &P.w2, d_in[2], 768, 64, 2);
  make_map3(enc, &P.g, d_in[3], 16, 8, 4);
  make_map3(enc, &P.wf, d_in[4], 256, 64, 2);
  make_map3(enc, &P.wg, d_in[5], 256, 64, 2);
  make_map3(enc, &P.wo, d_in[6], 256, 64, 2);
  make_map3(enc, &P.out64, d_out, 16000, 64, 1);
  make_map3(enc, &P.out56, d_out, 16000, 56, 1);
  rnnt_joint_kernel<<<kNumCtas, kThreads, kSmemBytes>>>(P);
}
```

```cpp
#include <cuda_runtime.h>
#include <cuda_bf16.h>
#include <cuda.h>
#include <stdint.h>

#define ARRK 3
#define XBULK 0
#define SKEW1 2
#define SKEW2 2
#define TSPLIT 0
#define XPREF 1
#define XFIRST 3
#define XSTEP 1
#define XPROMO CU_TENSOR_MAP_L2_PROMOTION_L2_128B
namespace {

constexpr int kT2 = 1000;
constexpr int kR = 31;
constexpr int kNumCtas = 132;
constexpr int kThreads = 384;
constexpr int kSlot = 16384;

constexpr int kSlotFE = 9, kSlotF = 10, kSlotH = 11;
constexpr int kOffG = 13 * kSlot;
constexpr int kOffGE = kOffG + 4096;
constexpr int kGEPitch = 272;
constexpr int kGEBytes = 32 * kGEPitch;
constexpr int kOffBar = kOffGE + kGEBytes;
constexpr int kBarX = 0;
constexpr int kBarW = 4;
constexpr int kBarE = 40;
constexpr int kBarHX = 67, kBarFX = 68, kBarFE = 69, kBarG = 70, kBarP0 = 71;
constexpr int kBarRH = 72, kBarRF = 74, kBarRE = 76;
constexpr int kBarPR = 78;
constexpr int kBarGW = 86;
constexpr int kBarFO = 87;
constexpr int kBarGE = 88;
constexpr int kNumBars = 89;
constexpr int kSmemBytes = kOffBar + kNumBars * 8 + 1024;

__device__ __align__(128) float g_ge[2 * kGEBytes / 4];
__device__ unsigned int g_ge_flag[2];
__device__ unsigned int g_cta_count;

#define TS(slot_, idx_) do {} while (0)
#define GT(idx_) do {} while (0)
#define TS_DUMP(slot_, lo_, hi_) do {} while (0)
#define GT_DUMP(idx_) do {} while (0)

__device__ __forceinline__ uint32_t smem_u32(const void* p) { return (uint32_t)__cvta_generic_to_shared(p); }
__device__ __forceinline__ void mbar_init(uint32_t a, uint32_t c) { asm volatile("mbarrier.init.shared.b64 [%0], %1;" ::"r"(a), "r"(c) : "memory"); }
__device__ __forceinline__ void mbar_expect(uint32_t a, uint32_t b) { asm volatile("mbarrier.arrive.expect_tx.shared.b64 _, [%0], %1;" ::"r"(a), "r"(b) : "memory"); }
__device__ __forceinline__ void mbar_arrive(uint32_t a) { asm volatile("mbarrier.arrive.shared.b64 _, [%0];" ::"r"(a) : "memory"); }
__device__ __forceinline__ void mbar_arrive_pred(uint32_t a, bool p) {
  asm volatile("{\n.reg .pred q;\nsetp.ne.u32 q, %1, 0;\n@q mbarrier.arrive.shared.b64 _, [%0];\n}\n" ::"r"(a), "r"((uint32_t)p) : "memory");
}
__device__ __forceinline__ void bar_arrive_pred(bool p) {
  asm volatile("{\n.reg .pred q;\nsetp.ne.u32 q, %0, 0;\n@q bar.arrive 4, 256;\n}\n" ::"r"((uint32_t)p) : "memory");
}
#define DEF_NAMED(ID) \
__device__ __forceinline__ void bar_arrive_pred##ID(bool p) { asm volatile("{\n.reg .pred q;\nsetp.ne.u32 q, %0, 0;\n@q bar.arrive " #ID ", 256;\n}\n" ::"r"((uint32_t)p) : "memory"); } \
__device__ __forceinline__ void bar_sync_pred##ID(bool p) { asm volatile("{\n.reg .pred q;\nsetp.ne.u32 q, %0, 0;\n@q bar.sync " #ID ", 256;\n}\n" ::"r"((uint32_t)p) : "memory"); }
DEF_NAMED(4)
DEF_NAMED(5)
DEF_NAMED(6)
__device__ __forceinline__ bool mbar_try(uint32_t a) {
  uint32_t ok;
  asm volatile("{\n.reg .pred p;\nmbarrier.try_wait.parity.shared.b64 p, [%1], 0;\nselp.u32 %0, 1, 0, p;\n}\n" : "=r"(ok) : "r"(a) : "memory");
  return ok != 0;
}
__device__ __forceinline__ bool mbar_test(uint32_t a) {
  uint32_t ok;
  asm volatile("{\n.reg .pred p;\nmbarrier.test_wait.parity.shared.b64 p, [%1], 0;\nselp.u32 %0, 1, 0, p;\n}\n" : "=r"(ok) : "r"(a) : "memory");
  return ok != 0;
}
__device__ __forceinline__ bool mbar_try_cluster(uint32_t a) {
  uint32_t ok;
  asm volatile("{\n.reg .pred p;\nmbarrier.try_wait.parity.acquire.cluster.shared.b64 p, [%1], 0;\nselp.u32 %0, 1, 0, p;\n}\n" : "=r"(ok) : "r"(a) : "memory");
  return ok != 0;
}
__device__ __forceinline__ void mbar_wait_slow(uint32_t a) {
  const long long t0 = clock64();
  while (!mbar_try(a)) { if (clock64() - t0 > 4000000ll) break; }
}
__device__ __forceinline__ void mbar_wait_cluster_slow(uint32_t a) {
  const long long t0 = clock64();
  while (!mbar_try_cluster(a)) { if (clock64() - t0 > 4000000ll) break; }
}
__device__ __forceinline__ void mbar_wait(uint32_t a) { if (!mbar_try(a)) mbar_wait_slow(a); }
__device__ __forceinline__ void mbar_wait_cluster(uint32_t a) { if (!mbar_try_cluster(a)) mbar_wait_cluster_slow(a); }
__device__ __forceinline__ uint32_t mapa(uint32_t a, uint32_t r) { uint32_t d; asm volatile("mapa.shared::cluster.u32 %0, %1, %2;" : "=r"(d) : "r"(a), "r"(r)); return d; }
__device__ __forceinline__ bool elect_one() { uint32_t p; asm volatile("{\n.reg .pred P;\nelect.sync _|P, 0xffffffff;\nselp.u32 %0, 1, 0, P;\n}\n" : "=r"(p)); return p != 0; }
__device__ __forceinline__ void fence_async_smem() { asm volatile("fence.proxy.async.shared::cta;" ::: "memory"); }
__device__ __forceinline__ void bar_consumers() { asm volatile("bar.sync 1, 256;" ::: "memory"); }
__device__ __forceinline__ void bar_wg(int wg) { asm volatile("bar.sync %0, 128;" ::"r"(2 + wg) : "memory"); }
__device__ __forceinline__ void cluster_sync_relaxed() { asm volatile("barrier.cluster.arrive.relaxed.aligned;\nbarrier.cluster.wait.aligned;" ::: "memory"); }
__device__ __forceinline__ void wg_fence() { asm volatile("wgmma.fence.sync.aligned;" ::: "memory"); }
__device__ __forceinline__ void wg_commit() { asm volatile("wgmma.commit_group.sync.aligned;" ::: "memory"); }
template <int N> __device__ __forceinline__ void wg_wait() { asm volatile("wgmma.wait_group.sync.aligned %0;" ::"n"(N) : "memory"); }

__device__ __forceinline__ void tma_load_3d(uint32_t dst, const CUtensorMap* tm, uint32_t bar, int c0, int c1, int c2) {
  asm volatile("cp.async.bulk.tensor.3d.shared::cluster.global.mbarrier::complete_tx::bytes [%0], [%1, {%3, %4, %5}], [%2];"
               ::"r"(dst), "l"(tm), "r"(bar), "r"(c0), "r"(c1), "r"(c2) : "memory");
}
__device__ __forceinline__ void tma_load_4d(uint32_t dst, const CUtensorMap* tm, uint32_t bar, int c0, int c1, int c2, int c3) {
  asm volatile("cp.async.bulk.tensor.4d.shared::cluster.global.mbarrier::complete_tx::bytes [%0], [%1, {%3, %4, %5, %6}], [%2];"
               ::"r"(dst), "l"(tm), "r"(bar), "r"(c0), "r"(c1), "r"(c2), "r"(c3) : "memory");
}
__device__ __forceinline__ void tma_load_4d_mc(uint32_t dst, const CUtensorMap* tm, uint32_t bar, int c0, int c1, int c2, int c3, uint16_t mask) {
  asm volatile("cp.async.bulk.tensor.4d.shared::cluster.global.mbarrier::complete_tx::bytes.multicast::cluster [%0], [%1, {%3, %4, %5, %6}], [%2], %7;"
               ::"r"(dst), "l"(tm), "r"(bar), "r"(c0), "r"(c1), "r"(c2), "r"(c3), "h"(mask) : "memory");
}
__device__ __forceinline__ void tma_store_3d(const CUtensorMap* tm, uint32_t src, int c0, int c1, int c2) {
  asm volatile("cp.async.bulk.tensor.3d.global.shared::cta.bulk_group [%0, {%2, %3, %4}], [%1];"
               ::"l"(tm), "r"(src), "r"(c0), "r"(c1), "r"(c2) : "memory");
}
__device__ __forceinline__ void bulk_load(uint32_t dst, const void* src, uint32_t bytes, uint32_t bar) {
  asm volatile("cp.async.bulk.shared::cluster.global.mbarrier::complete_tx::bytes [%0], [%1], %2, [%3];"
               ::"r"(dst), "l"(src), "r"(bytes), "r"(bar) : "memory");
}
__device__ __forceinline__ void dsmem_copy(uint32_t dst_remote, uint32_t src, uint32_t bytes, uint32_t bar_remote) {
  asm volatile("cp.async.bulk.shared::cluster.shared::cta.mbarrier::complete_tx::bytes [%0], [%1], %2, [%3];"
               ::"r"(dst_remote), "r"(src), "r"(bytes), "r"(bar_remote) : "memory");
}
__device__ __forceinline__ void stsm_x4_trans(uint32_t addr, uint32_t r0, uint32_t r1, uint32_t r2, uint32_t r3) {
  asm volatile("stmatrix.sync.aligned.m8n8.x4.trans.shared.b16 [%0], {%1, %2, %3, %4};" ::"r"(addr), "r"(r0), "r"(r1), "r"(r2), "r"(r3) : "memory");
}
__device__ __forceinline__ void stsm_x4(uint32_t addr, uint32_t r0, uint32_t r1, uint32_t r2, uint32_t r3) {
  asm volatile("stmatrix.sync.aligned.m8n8.x4.shared.b16 [%0], {%1, %2, %3, %4};" ::"r"(addr), "r"(r0), "r"(r1), "r"(r2), "r"(r3) : "memory");
}
__device__ __forceinline__ float2 lds64(uint32_t a) { float2 v; asm volatile("ld.shared.v2.f32 {%0, %1}, [%2];" : "=f"(v.x), "=f"(v.y) : "r"(a) : "memory"); return v; }
__device__ __forceinline__ float4 lds128(uint32_t a) { float4 v; asm volatile("ld.shared.v4.f32 {%0, %1, %2, %3}, [%4];" : "=f"(v.x), "=f"(v.y), "=f"(v.z), "=f"(v.w) : "r"(a) : "memory"); return v; }
__device__ __forceinline__ void sts64(uint32_t a, float x, float y) { asm volatile("st.shared.v2.f32 [%0], {%1, %2};" ::"r"(a), "f"(x), "f"(y) : "memory"); }
__device__ __forceinline__ float tanh_fast(float x) { float y; asm("tanh.approx.f32 %0, %1;" : "=f"(y) : "f"(x)); return y; }
__device__ __forceinline__ uint32_t tanh2_pack(float lo, float hi) {
  uint32_t r;
  asm volatile("{\n.reg .f32 a, b;\ntanh.approx.f32 a, %1;\ntanh.approx.f32 b, %2;\ncvt.rn.bf16x2.f32 %0, b, a;\n}\n" : "=r"(r) : "f"(lo), "f"(hi));
  return r;
}
__device__ __forceinline__ uint32_t pack_bf16(float lo, float hi) { uint32_t r; asm("cvt.rn.bf16x2.f32 %0, %1, %2;" : "=r"(r) : "f"(hi), "f"(lo)); return r; }
__device__ __forceinline__ float gelu_tanh(float x) {
  const float k0 = 0.7978845608028654f, k1 = 0.7978845608028654f * 0.044715f;
  float u = x * fmaf(x * x, k1, k0);
  float hx = 0.5f * x;
  return fmaf(hx, tanh_fast(u), hx);
}
__device__ __forceinline__ uint64_t make_desc(uint32_t addr, uint32_t lbo, uint32_t sbo) {
  return (uint64_t)((addr & 0x3FFFF) >> 4) | ((uint64_t)(lbo >> 4) << 16) | ((uint64_t)(sbo >> 4) << 32) | ((uint64_t)1 << 62);
}

__device__ __forceinline__ uint32_t desc_lo(uint32_t addr, uint32_t lbo) { return ((addr & 0x3FFFF) >> 4) | ((lbo >> 4) << 16); }
__device__ __forceinline__ uint64_t desc_at(uint32_t lo, uint32_t off) { return ((uint64_t)0x40000040u << 32) | (uint64_t)(lo + (off >> 4)); }

__device__ __forceinline__ void wgmma_ss_n64(float (&d)[32], uint64_t da, uint64_t db, int scale_d) {
  asm volatile("{\n.reg .pred p;\nsetp.ne.b32 p, %34, 0;\n"
    "wgmma.mma_async.sync.aligned.m64n64k16.f32.bf16.bf16 {%0, %1, %2, %3, %4, %5, %6, %7, %8, %9, %10, %11, %12, %13, %14, %15, %16, %17, %18, %19, %20, %21, %22, %23, %24, %25, %26, %27, %28, %29, %30, %31}, %32, %33, p, 1, 1, 1, 0;\n}\n"
    : "+f"(d[0]), "+f"(d[1]), "+f"(d[2]), "+f"(d[3]), "+f"(d[4]), "+f"(d[5]), "+f"(d[6]), "+f"(d[7]), "+f"(d[8]), "+f"(d[9]), "+f"(d[10]), "+f"(d[11]), "+f"(d[12]), "+f"(d[13]), "+f"(d[14]), "+f"(d[15]), "+f"(d[16]), "+f"(d[17]), "+f"(d[18]), "+f"(d[19]), "+f"(d[20]), "+f"(d[21]), "+f"(d[22]), "+f"(d[23]), "+f"(d[24]), "+f"(d[25]), "+f"(d[26]), "+f"(d[27]), "+f"(d[28]), "+f"(d[29]), "+f"(d[30]), "+f"(d[31])
    : "l"(da), "l"(db), "r"(scale_d));
}

__device__ __forceinline__ void wgmma_ss_n32(float (&d)[16], uint64_t da, uint64_t db, int scale_d) {
  asm volatile("{\n.reg .pred p;\nsetp.ne.b32 p, %18, 0;\n"
    "wgmma.mma_async.sync.aligned.m64n32k16.f32.bf16.bf16 {%0, %1, %2, %3, %4, %5, %6, %7, %8, %9, %10, %11, %12, %13, %14, %15}, %16, %17, p, 1, 1, 1, 0;\n}\n"
    : "+f"(d[0]), "+f"(d[1]), "+f"(d[2]), "+f"(d[3]), "+f"(d[4]), "+f"(d[5]), "+f"(d[6]), "+f"(d[7]), "+f"(d[8]), "+f"(d[9]), "+f"(d[10]), "+f"(d[11]), "+f"(d[12]), "+f"(d[13]), "+f"(d[14]), "+f"(d[15])
    : "l"(da), "l"(db), "r"(scale_d));
}

__device__ __forceinline__ void wgmma_ss_n8(float (&d)[4], uint64_t da, uint64_t db, int scale_d) {
  asm volatile("{\n.reg .pred p;\nsetp.ne.b32 p, %6, 0;\n"
    "wgmma.mma_async.sync.aligned.m64n8k16.f32.bf16.bf16 {%0, %1, %2, %3}, %4, %5, p, 1, 1, 1, 0;\n}\n"
    : "+f"(d[0]), "+f"(d[1]), "+f"(d[2]), "+f"(d[3])
    : "l"(da), "l"(db), "r"(scale_d));
}

__device__ __forceinline__ void wgmma_rs_n64(float (&d)[32], uint32_t a0, uint32_t a1, uint32_t a2, uint32_t a3, uint64_t db, int scale_d) {
  asm volatile("{\n.reg .pred p;\nsetp.ne.b32 p, %37, 0;\n"
    "wgmma.mma_async.sync.aligned.m64n64k16.f32.bf16.bf16 {%0, %1, %2, %3, %4, %5, %6, %7, %8, %9, %10, %11, %12, %13, %14, %15, %16, %17, %18, %19, %20, %21, %22, %23, %24, %25, %26, %27, %28, %29, %30, %31}, {%32, %33, %34, %35}, %36, p, 1, 1, 1;\n}\n"
    : "+f"(d[0]), "+f"(d[1]), "+f"(d[2]), "+f"(d[3]), "+f"(d[4]), "+f"(d[5]), "+f"(d[6]), "+f"(d[7]), "+f"(d[8]), "+f"(d[9]), "+f"(d[10]), "+f"(d[11]), "+f"(d[12]), "+f"(d[13]), "+f"(d[14]), "+f"(d[15]), "+f"(d[16]), "+f"(d[17]), "+f"(d[18]), "+f"(d[19]), "+f"(d[20]), "+f"(d[21]), "+f"(d[22]), "+f"(d[23]), "+f"(d[24]), "+f"(d[25]), "+f"(d[26]), "+f"(d[27]), "+f"(d[28]), "+f"(d[29]), "+f"(d[30]), "+f"(d[31])
    : "r"(a0), "r"(a1), "r"(a2), "r"(a3), "l"(db), "r"(scale_d));
}

__host__ __device__ constexpr int unit_slot(int u) {
  constexpr int t[36] = {4, 5, 6, 7, 8, 4, 5, 6, 0, 7, 8, 4,  1, 5, 6, 0, 2, 7, 8, 4, 3, 1, 5, 6,
                         0, 2, 7, 8,  4, 3, 1, 5, 6, 0, 2, 7};
  return t[u];
}
__host__ __device__ constexpr int unit_wait(int u) {
  constexpr int t[36] = {-1, -1, -1, -1, -1, 0, 1, 2, 2, 3, 4, 5,  5, 6, 7, 8, 8, 9, 10, 11, 11, 12, 13, 14,
                         15, 16, 17, 18,  19, 20, 21, 22, 23, 24, 25, 26};
  return t[u];
}

__device__ __forceinline__ uint32_t stage_off(int g, int j) {
  return g == 0 ? (j < 2 ? 8 * kSlot + j * 8192 : 10 * kSlot + (j - 2) * 8192)
                : (j < 2 ? 12 * kSlot + j * 8192 : (j == 2 ? 11 * kSlot + 8192 : 9 * kSlot));
}

struct Params {
  CUtensorMap x, w1, w2, wf, wg, wo, g, out64, out56;
  const void* xptr;
};

__device__ __forceinline__ void init_bar(uint32_t bars, int i) {
  const uint32_t a = bars + i * 8;
  const bool is_e = (i >= kBarE && i < kBarE + 27);
  mbar_init(a, is_e ? 8 : 1);
  if (!is_e) {
    uint32_t bytes = 16384;
    if (i == kBarFX) bytes = 8192;
    if (i == kBarFE) bytes = 8192;
    mbar_expect(a, bytes);
  }
}

__device__ __forceinline__ void store_pieces(const Params& P, uint32_t sb, uint32_t bars, int g, uint32_t cta, int b, int r0, int rvalid) {
  const int rl0 = cta * 16 + g * 8;
  if (rl0 >= rvalid) return;
  const CUtensorMap* omap = (rl0 + 8 <= rvalid) ? &P.out64 : &P.out56;
#pragma unroll
  for (int j = 0; j < 4; j++) {
    mbar_wait(bars + (kBarPR + g * 4 + j) * 8);
    if (elect_one()) {
      tma_store_3d(omap, sb + stage_off(g, j), 0, (b * kT2 + r0 + rl0) * 8, j);
      asm volatile("cp.async.bulk.commit_group;" ::: "memory");
    }
    __syncwarp();
    if (j == 0) TS(2, 12 + g);
    if (j == 3) TS(2, 14 + g);
  }
  if (elect_one()) asm volatile("cp.async.bulk.wait_group.read 0;" ::: "memory");
  __syncwarp();
  if (g == 1) { TS(2, 11); GT(1); TS_DUMP(2, 11, 12); GT_DUMP(1); }
  TS_DUMP(2, 12 + g, 13 + g); TS_DUMP(2, 14 + g, 15 + g);
}

__global__ void __cluster_dims__(2, 1, 1) __launch_bounds__(kThreads, 1)
rnnt_joint_kernel(const __grid_constant__ Params P) {
  extern __shared__ uint8_t smem_raw[];
  const uint32_t sb = (smem_u32(smem_raw) + 1023u) & ~1023u;
  const uint32_t bars = sb + kOffBar;
  const int warp = threadIdx.x >> 5, lane = threadIdx.x & 31;
  uint32_t cta;
  asm volatile("mov.u32 %0, %%cluster_ctarank;" : "=r"(cta));
  const uint32_t peer = cta ^ 1u;
  const int cl = blockIdx.x >> 1;
  const bool ge_cta = cl < 2;
  const int b = ge_cta ? cl : ((cl - 2) >> 5);
  const int r0 = ge_cta ? 32 * kR : ((cl - 2) & 31) * kR;
  const int rvalid = ge_cta ? kT2 - 32 * kR : kR;

  if (warp >= 8) {
    asm volatile("setmaxnreg.dec.sync.aligned.u32 40;");
    if (warp > 8) {
      if (elect_one()) {
#pragma unroll
        for (int i = 0; i < 5; i++) if (57 + (warp - 9) * 5 + i < kBarG) init_bar(bars, 57 + (warp - 9) * 5 + i);
#pragma unroll
        for (int i = 0; i < 5; i++) if (kBarRH + (warp - 9) * 5 + i < kBarGW) mbar_init(bars + (kBarRH + (warp - 9) * 5 + i) * 8, 4);
        if (warp == 11) { mbar_init(bars + kBarGW * 8, 8); mbar_init(bars + kBarFO * 8, 8); mbar_init(bars + kBarGE * 8, 1); mbar_expect(bars + kBarGE * 8, kGEBytes); }
        asm volatile("fence.mbarrier_init.release.cluster;" ::: "memory");
      }
      __syncwarp();
      asm volatile("barrier.cluster.arrive.relaxed.aligned;" ::: "memory");
      if (warp == 11 && lane < 9) asm volatile("prefetch.tensormap [%0];" ::"l"(reinterpret_cast<const CUtensorMap*>(&P) + lane) : "memory");
      __syncwarp();
      asm volatile("barrier.cluster.wait.aligned;" ::: "memory");
      if (warp == 10 && ge_cta) {
        mbar_wait(bars + kBarGW * 8);
        if (elect_one()) {
          __threadfence();
          asm volatile("red.release.gpu.global.add.u32 [%0], 1;" ::"l"(&g_ge_flag[b]) : "memory");
        }
        __syncwarp();
      }
      if (warp == 11) {
        if (elect_one()) {
          const unsigned int ticket = atomicAdd(&g_cta_count, 1u);
          const unsigned int want = (ticket / kNumCtas + 1u) * 2u;
          const long long t0 = clock64();
          unsigned int v;
          do {
            __nanosleep(200);
            asm volatile("ld.acquire.gpu.global.u32 %0, [%1];" : "=r"(v) : "l"(&g_ge_flag[b]) : "memory");
          } while ((int)(v - want) < 0 && clock64() - t0 < 4000000ll);
          asm volatile("fence.proxy.async;" ::: "memory");
          bulk_load(sb + kOffGE, reinterpret_cast<const char*>(g_ge) + b * kGEBytes, kGEBytes, bars + kBarGE * 8);
        }
        __syncwarp();
        return;
      }
      if (warp == 10) store_pieces(P, sb, bars, 1, cta, b, r0, rvalid);
      if (warp == 10) return;
#pragma unroll
      for (int g = 0; g < 2; g++) {
        mbar_wait(bars + (kBarRH + g) * 8);
        if (elect_one()) {
          const uint32_t src = sb + kSlotH * kSlot + (2 * cta + g) * 8192;
          dsmem_copy(mapa(src, peer), src, 8192, mapa(bars + kBarHX * 8, peer));
        }
        __syncwarp();
      }
#pragma unroll
      for (int g = 0; g < 2; g++) {
        mbar_wait(bars + (kBarRF + g) * 8);
        if (elect_one()) {
          const uint32_t src = sb + kSlotF * kSlot + (2 * cta + g) * 4096;
          dsmem_copy(mapa(src, peer), src, 4096, mapa(bars + kBarFX * 8, peer));
        }
        __syncwarp();
      }
#pragma unroll
      for (int g = 0; g < 2; g++) {
        mbar_wait(bars + (kBarRE + g) * 8);
        if (elect_one())
          dsmem_copy(mapa(sb + kSlotFE * kSlot + (2 * cta + g) * 4096, peer), sb + kSlotH * kSlot + g * 4096, 4096, mapa(bars + kBarFE * 8, peer));
        __syncwarp();
      }
      store_pieces(P, sb, bars, 0, cta, b, r0, rvalid);
      return;
    }
    TS(2, 0);
    GT(0);
    const int par = cta == 0 ? 1 : 0;
    const int q0 = cta == 0 ? 2 * r0 - 2 : 2 * r0 - 1;
    if (elect_one()) {
      mbar_init(bars + kBarX * 8, 1); mbar_expect(bars + kBarX * 8, 16384);
      mbar_init(bars + kBarW * 8, 1); mbar_expect(bars + kBarW * 8, 16384);
      fence_async_smem();
      tma_load_4d(sb, &P.x, bars + kBarX * 8, 0, 1, 2 * r0 - 2, b);
      tma_load_4d(sb + 8192, &P.x, bars + kBarX * 8, 0, 0, 2 * r0 - 1, b);
      tma_load_3d(sb + unit_slot(0) * kSlot, &P.w1, bars + kBarW * 8, 0, 0, 2 * cta);
      TS(2, 7);
#pragma unroll
      for (int i = 1; i < 9; i++) if (i != kBarW) { mbar_init(bars + i * 8, 1); mbar_expect(bars + i * 8, 16384); }
      if (ge_cta) { mbar_init(bars + kBarG * 8, 1); mbar_expect(bars + kBarG * 8, 4 * 16384 + 4096); mbar_init(bars + kBarP0 * 8, 8); }
      asm volatile("fence.mbarrier_init.release.cluster;" ::: "memory");
      fence_async_smem();
      TS(2, 8);
      if (ge_cta) {
        tma_load_3d(sb + kOffG, &P.g, bars + kBarG * 8, 0, b * 8, 0);
#pragma unroll
        for (int i = 0; i < 4; i++) tma_load_3d(sb + (9 + i) * kSlot, &P.wg, bars + kBarG * 8, 0, i * 64, 2 * cta);
      }
#pragma unroll
      for (int u = 1; u < 5; u++)
        tma_load_3d(sb + unit_slot(u) * kSlot, &P.w1, bars + (kBarW + u) * 8, 0, (u % 3) * 256 + (u / 3) * 64, 2 * cta);
      TS(2, 10);
    }
    __syncwarp();
    TS(2, 6);
    cluster_sync_relaxed();
    TS(2, 1);
    if (elect_one()) {
#pragma unroll
      for (int p = 1; p < XFIRST; p++)
        tma_load_4d_mc(sb + p * kSlot + cta * 8192, &P.x, bars + (kBarX + p) * 8, p * 64, par, q0, b, (uint16_t)3);
    }
    __syncwarp();
#pragma unroll
    for (int p = XFIRST; p < 4; p++) {
      if (XSTEP == 1 || ((p - XFIRST) & 1) == 0) mbar_wait(bars + (kBarX + p - XFIRST) * 8);
      if (ge_cta && p == 3) mbar_wait(bars + kBarP0 * 8);
      if (elect_one())
        tma_load_4d_mc(sb + p * kSlot + cta * 8192, &P.x, bars + (kBarX + p) * 8, p * 64, par, q0, b, (uint16_t)3);
      __syncwarp();
    }
#pragma unroll
    for (int u = 5; u < 36; u++) {
      if (unit_wait(u) != unit_wait(u - 1)) mbar_wait(bars + (kBarE + unit_wait(u)) * 8);
      if (elect_one()) {
        const uint32_t dst = sb + unit_slot(u) * kSlot, bar = bars + (kBarW + u) * 8;
        if (u < 12) tma_load_3d(dst, &P.w1, bar, 0, (u % 3) * 256 + (u / 3) * 64, 2 * cta);
        else if (u < 24) tma_load_3d(dst, &P.w2, bar, 0, ((u - 12) % 3) * 256 + ((2 * cta + (u - 12) / 3) & 3) * 64, 2 * cta);
        else if (u < 28) tma_load_3d(dst, &P.wf, bar, 0, ((2 * cta + (u - 24)) & 3) * 64, 2 * cta);
        else tma_load_3d(dst, &P.wo, bar, 0, ((2 * cta + (u - 28)) & 3) * 64, ((u - 28) >> 2) * 2);
      }
      __syncwarp();
      if (u == 11) TS(2, 2);
      if (u == 23) TS(2, 3);
      if (u == 27) TS(2, 4);
      if (u == 35) TS(2, 5);
    }
    TS_DUMP(2, 0, 11); GT_DUMP(0);
  } else {
    asm volatile("setmaxnreg.inc.sync.aligned.u32 232;");
    const int wg = warp >> 2, w = warp & 3;
    const int gq = lane >> 2, q = lane & 3;
    const uint32_t panel = 2 * cta + wg;
    const int ch = panel * 64 + w * 16 + gq;
    const uint32_t dA = desc_lo(sb + wg * 8192, 8192);
    const uint32_t dB = desc_lo(sb, 16);
    const uint32_t dBo = desc_lo(sb + cta * 2 * 8192, 16), dBp = desc_lo(sb + (cta ^ 1) * 2 * 8192, 16);
    const uint32_t dFo = desc_lo(sb + cta * 2 * 4096, 16), dFp = desc_lo(sb + (cta ^ 1) * 2 * 4096, 16);
    if (elect_one()) {
#pragma unroll
      for (int i = 0; i < 6; i++) init_bar(bars, 9 + warp * 6 + i);
      asm volatile("fence.mbarrier_init.release.cluster;" ::: "memory");
    }
    __syncwarp();
    cluster_sync_relaxed();
    if (w == 0) TS(wg, 0);

    if (ge_cta) {
      float ga[4];
      mbar_wait(bars + kBarG * 8);
      wg_fence();
#pragma unroll
      for (int i = 0; i < 4; i++) {
#pragma unroll
        for (int s = 0; s < 4; s++)
          wgmma_ss_n8(ga, desc_at(dA, (9 + i) * kSlot + s * 2048), desc_at(dB, kOffG + i * 1024 + s * 32), (i | s) != 0);
      }
      wg_commit();
      wg_wait<0>();
      if (lane == 0) mbar_arrive(bars + kBarP0 * 8);
      float* gp = g_ge + b * (kGEBytes / 4) + ((ch & 7) >> 1) * (kGEPitch / 4) + (ch >> 4) * 4 + (ch & 1);
      gp[(2 * q) * 4 * (kGEPitch / 4)] = ga[0];
      gp[(2 * q + 1) * 4 * (kGEPitch / 4)] = ga[1];
      gp[(2 * q) * 4 * (kGEPitch / 4) + 2] = ga[2];
      gp[(2 * q + 1) * 4 * (kGEPitch / 4) + 2] = ga[3];
      __syncwarp();
      if (lane == 0) mbar_arrive(bars + kBarGW * 8);
    }

    {
      float acc[32];
#pragma unroll
      for (int u = 0; u < 12; u++) {
        const int p = u / 3, tap = u % 3;
        if (SKEW1 > 0 && u == 12 - SKEW1) bar_sync_pred5(wg == 1);
        if (tap == 0) mbar_wait(bars + (kBarX + p) * 8);
        mbar_wait(bars + (kBarW + u) * 8);
        if (u == 0 && w == 0) TS(wg, 1);
        wg_fence();
#pragma unroll
        for (int s = 0; s < 4; s++)
          wgmma_ss_n64(acc, desc_at(dA, unit_slot(u) * kSlot + s * 2048),
                       desc_at(dB, p * kSlot + (tap == 1 ? 8192 : (tap == 2 ? 128 : 0)) + s * 32), (u | s) != 0);
        wg_commit();
        if (SKEW1 > 0 && u == 11) bar_arrive_pred5(wg == 0);
        if (u > 0) {
          wg_wait<1>();
          if (lane == 0) mbar_arrive(bars + (kBarE + u - 1) * 8);
        }
      }
      wg_wait<0>();
      if (lane == 0) mbar_arrive(bars + (kBarE + 11) * 8);
      if (w == 0) TS(wg, 2);
      const uint32_t hp = sb + kSlotH * kSlot + panel * 8192;
      const int mi = lane >> 3, l8 = lane & 7;
#pragma unroll
      for (int jb = 0; jb < 8; jb += 2) {
        uint32_t r[4];
#pragma unroll
        for (int t = 0; t < 2; t++) {
          r[2 * t + 0] = pack_bf16(gelu_tanh(acc[4 * (jb + t) + 0]), gelu_tanh(acc[4 * (jb + t) + 1]));
          r[2 * t + 1] = pack_bf16(gelu_tanh(acc[4 * (jb + t) + 2]), gelu_tanh(acc[4 * (jb + t) + 3]));
        }
        const int n = 8 * (jb + (mi >> 1)) + l8;
        const int row = n >> 1, chunk = 2 * w + (mi & 1);
        stsm_x4_trans(hp + (n & 1) * 4096 + row * 128 + ((chunk ^ (row & 7)) << 4), r[0], r[1], r[2], r[3]);
      }
      __syncwarp();
      if (w == 0) TS(wg, 15);
      fence_async_smem();
      __syncwarp();
      if (lane == 0) mbar_arrive(bars + (kBarRH + wg) * 8);
      if (w == 0) TS(wg, 3);
    }
    {
      float acc[16];
#pragma unroll
      for (int v = 0; v < 12; v++) {
        const int i = v / 3, tap = v % 3;
        if (SKEW2 > 0 && v == 12 - SKEW2) bar_sync_pred6(wg == 1);
        if (v == 0) mbar_wait(bars + kBarRH * 8);
        if (v == 3) mbar_wait(bars + (kBarRH + 1) * 8);
        if (v == 6) { mbar_wait_cluster(bars + kBarHX * 8); if (w == 0) TS(wg, 4); }
        mbar_wait(bars + (kBarW + 12 + v) * 8);
        wg_fence();
#pragma unroll
        for (int s = 0; s < 4; s++)
          wgmma_ss_n32(acc, desc_at(dA, unit_slot(12 + v) * kSlot + s * 2048),
                       desc_at(i < 2 ? dBo : dBp, kSlotH * kSlot + (i & 1) * 8192 + (tap == 1 ? 4096 : (tap == 2 ? 128 : 0)) + s * 32), (v | s) != 0);
        wg_commit();
        if (SKEW2 > 0 && v == 11) bar_arrive_pred6(wg == 0);
        if (v > 0) {
          wg_wait<1>();
          if (lane == 0) mbar_arrive(bars + (kBarE + 12 + v - 1) * 8);
        }
      }
      wg_wait<0>();
      if (lane == 0) mbar_arrive(bars + (kBarE + 23) * 8);
      if (w == 0) TS(wg, 5);
      const uint32_t fp = sb + kSlotF * kSlot + panel * 4096;
      const int mi = lane >> 3, l8 = lane & 7;
#pragma unroll
      for (int jb = 0; jb < 4; jb += 2) {
        uint32_t r[4];
#pragma unroll
        for (int t = 0; t < 2; t++) {
          r[2 * t + 0] = pack_bf16(gelu_tanh(acc[4 * (jb + t) + 0]), gelu_tanh(acc[4 * (jb + t) + 1]));
          r[2 * t + 1] = pack_bf16(gelu_tanh(acc[4 * (jb + t) + 2]), gelu_tanh(acc[4 * (jb + t) + 3]));
        }
        const int n = 8 * (jb + (mi >> 1)) + l8;
        const int chunk = 2 * w + (mi & 1);
        stsm_x4_trans(fp + n * 128 + ((chunk ^ (n & 7)) << 4), r[0], r[1], r[2], r[3]);
      }
      fence_async_smem();
      __syncwarp();
      if (lane == 0) mbar_arrive(bars + (kBarRF + wg) * 8);
      if (w == 0) TS(wg, 6);
    }
    {
      float acc[16];
#pragma unroll
      for (int i = 0; i < 4; i++) {
        if (i < 2) mbar_wait(bars + (kBarRF + i) * 8);
        if (i == 2) { mbar_wait_cluster(bars + kBarFX * 8); if (w == 0) TS(wg, 7); }
        mbar_wait(bars + (kBarW + 24 + i) * 8);
        wg_fence();
#pragma unroll
        for (int s = 0; s < 4; s++)
          wgmma_ss_n32(acc, desc_at(dA, unit_slot(24 + i) * kSlot + s * 2048),
                       desc_at(i < 2 ? dFo : dFp, kSlotF * kSlot + (i & 1) * 4096 + s * 32), (i | s) != 0);
        wg_commit();
        if (i > 0) {
          wg_wait<1>();
          if (lane == 0) mbar_arrive(bars + (kBarE + 24 + i - 1) * 8);
        }
      }
      wg_wait<0>();
      if (w == 0) TS(wg, 8);
      const uint32_t qk = gq >> 1;
      const uint32_t off0 = qk * 128 + (((2 * w) ^ (2 * qk)) << 4) + (gq & 1) * 8;
      const uint32_t off1 = qk * 128 + (((2 * w + 1) ^ (2 * qk)) << 4) + (gq & 1) * 8;
      const uint32_t own = sb + kSlotFE * kSlot + panel * 4096;
      const uint32_t stg = sb + kSlotH * kSlot + wg * 4096;
#pragma unroll
      for (int jb = 0; jb < 4; jb++) {
        const uint32_t base = (((uint32_t)(jb >> 1) == cta) ? own : stg) + (4 * (jb & 1) + q) * 512;
        sts64(base + off0, acc[4 * jb + 0], acc[4 * jb + 1]);
        sts64(base + off1, acc[4 * jb + 2], acc[4 * jb + 3]);
      }
      fence_async_smem();
      __syncwarp();
      if (lane == 0) { mbar_arrive(bars + (kBarRE + wg) * 8); mbar_arrive(bars + kBarFO * 8); }
      if (w == 0) TS(wg, 9);
    }
    const int rl0 = cta * 16 + wg * 8;
    mbar_wait(bars + kBarFO * 8);
    mbar_wait(bars + kBarGE * 8);
    if (!TSPLIT && wg == 1) asm volatile("bar.sync 4, 256;" ::: "memory");
    if (rl0 < rvalid) {
      if (w == 0) TS(wg, 10);
      const uint32_t fe_row = sb + kSlotFE * kSlot + ((4 * wg + w) * 4 + q) * 128;
      const uint32_t fe_h[2] = {fe_row + cta * 8192, fe_row + (cta ^ 1) * 8192};
      const uint32_t ge_h[2] = {sb + kOffGE + lane * kGEPitch + cta * 128, sb + kOffGE + lane * kGEPitch + (cta ^ 1) * 128};
      const int mi = lane >> 3, l8 = lane & 7;
      const uint32_t st = sb + (16 * w + (mi & 1) * 8 + l8) * 128;
      uint32_t A[64];
      float acc[2][32];
      {
        constexpr int PD = 3;
        float4 fa[PD], fb[PD], gg[PD];
#pragma unroll
        for (int kk = 0; kk < 16 + PD; kk++) {
          if (kk >= PD) {
            const int k = kk - PD, sl = k % PD;
            A[4 * k + 0] = tanh2_pack(fa[sl].x + gg[sl].x, fa[sl].z + gg[sl].y);
            A[4 * k + 1] = tanh2_pack(fa[sl].y + gg[sl].x, fa[sl].w + gg[sl].y);
            A[4 * k + 2] = tanh2_pack(fb[sl].x + gg[sl].z, fb[sl].z + gg[sl].w);
            A[4 * k + 3] = tanh2_pack(fb[sl].y + gg[sl].z, fb[sl].w + gg[sl].w);
          }
          if (kk < 16) {
            const int sl = kk % PD;
            if (kk == 8) {
              if (TSPLIT) bar_sync_pred4(wg == 1);
              mbar_wait_cluster(bars + kBarFE * 8);
            }
            fa[sl] = lds128(fe_h[kk >> 3] + ((kk >> 2) & 1) * 4096 + ((((kk & 3) * 2) ^ (2 * q)) << 4));
            fb[sl] = lds128(fe_h[kk >> 3] + ((kk >> 2) & 1) * 4096 + ((((kk & 3) * 2 + 1) ^ (2 * q)) << 4));
            gg[sl] = lds128(ge_h[kk >> 3] + (kk & 7) * 16);
          }
        }
      }
      asm volatile("barrier.cluster.arrive.relaxed.aligned;" ::: "memory");
#pragma unroll
      for (int kk = 0; kk < 16; kk++) {
        if ((kk & 3) == 0) { mbar_wait(bars + (kBarW + 28 + (kk >> 2)) * 8); wg_fence(); }
        wgmma_rs_n64(acc[0], A[4 * kk], A[4 * kk + 1], A[4 * kk + 2], A[4 * kk + 3],
                     desc_at(dB, unit_slot(28 + (kk >> 2)) * kSlot + (kk & 3) * 2048), kk != 0);
        if (kk == ARRK) bar_arrive_pred(wg == 0);
      }
      wg_commit();
      wg_wait<0>();
#pragma unroll
      for (int jb = 0; jb < 8; jb += 2) {
        const uint32_t r0_ = pack_bf16(acc[0][4 * jb + 0], acc[0][4 * jb + 1]), r1_ = pack_bf16(acc[0][4 * jb + 2], acc[0][4 * jb + 3]);
        const uint32_t r2_ = pack_bf16(acc[0][4 * jb + 4], acc[0][4 * jb + 5]), r3_ = pack_bf16(acc[0][4 * jb + 6], acc[0][4 * jb + 7]);
        stsm_x4(st + (wg ? stage_off(1, 0) : stage_off(0, 0)) + (((jb + (mi >> 1)) ^ l8) << 4), r0_, r1_, r2_, r3_);
      }
      fence_async_smem();
      __syncwarp();
      mbar_arrive_pred(bars + (kBarPR + wg * 4) * 8, lane == 0);
      if (w == 0) TS(wg, 11);
#pragma unroll
      for (int j = 0; j < 4; j++) {
        const int jn = j + 1;
        if (jn == 2) {
#pragma unroll
          for (int i = 0; i < 4; i++) mbar_wait(bars + (kBarW + 32 + i) * 8);
        }
        if (j < 3) wg_fence();
        const uint32_t stj = st + (wg ? stage_off(1, j) : stage_off(0, j));
#pragma unroll
        for (int kk = 0; kk < 16; kk++) {
          if (j < 3)
            wgmma_rs_n64(acc[jn & 1], A[4 * kk], A[4 * kk + 1], A[4 * kk + 2], A[4 * kk + 3],
                         desc_at(dB, unit_slot(28 + (jn >> 1) * 4 + (kk >> 2)) * kSlot + (jn & 1) * 8192 + (kk & 3) * 2048), kk != 0);
          if (kk == 1 && j > 0) {
            if (j < 3) { wg_commit(); wg_wait<1>(); } else { wg_wait<0>(); }
          }
          if (j > 0 && kk >= 2 && kk < 10 && (kk & 1) == 0) {
            const int jb = kk - 2;
            const uint32_t r0_ = pack_bf16(acc[j & 1][4 * jb + 0], acc[j & 1][4 * jb + 1]), r1_ = pack_bf16(acc[j & 1][4 * jb + 2], acc[j & 1][4 * jb + 3]);
            const uint32_t r2_ = pack_bf16(acc[j & 1][4 * jb + 4], acc[j & 1][4 * jb + 5]), r3_ = pack_bf16(acc[j & 1][4 * jb + 6], acc[j & 1][4 * jb + 7]);
            stsm_x4(stj + (((jb + (mi >> 1)) ^ l8) << 4), r0_, r1_, r2_, r3_);
          }
          if (j > 0 && kk == 9) {
            fence_async_smem();
            __syncwarp();
            mbar_arrive_pred(bars + (kBarPR + wg * 4 + j) * 8, lane == 0);
          }
        }
        if (j < 3) wg_commit();
        if (j == 0 && w == 0) TS(wg, 12);
        if (j == 2 && w == 0) TS(wg, 13);
      }
      if (w == 0) TS(wg, 14);
    } else {
      if (wg == 0) asm volatile("bar.arrive 4, 256;" ::: "memory");
      if (TSPLIT && wg == 1) asm volatile("bar.sync 4, 256;" ::: "memory");
      mbar_wait_cluster(bars + kBarFE * 8);
      asm volatile("barrier.cluster.arrive.relaxed.aligned;" ::: "memory");
    }
    asm volatile("barrier.cluster.wait.aligned;" ::: "memory");
    if (w == 0) TS_DUMP(wg, 0, 16);
  }
}

typedef CUresult (*EncodeFn)(CUtensorMap*, CUtensorMapDataType, cuuint32_t, void*, const cuuint64_t*, const cuuint64_t*,
                             const cuuint32_t*, const cuuint32_t*, CUtensorMapInterleave, CUtensorMapSwizzle,
                             CUtensorMapL2promotion, CUtensorMapFloatOOBfill);

void make_map3(EncodeFn enc, CUtensorMap* tm, const void* ptr, uint64_t rows, uint32_t box_rows, uint32_t box_panels) {
  cuuint64_t gd[3] = {64, rows, 4};
  cuuint64_t gs[2] = {512, 128};
  cuuint32_t bd[3] = {64, box_rows, box_panels};
  cuuint32_t es[3] = {1, 1, 1};
  enc(tm, CU_TENSOR_MAP_DATA_TYPE_BFLOAT16, 3, const_cast<void*>(ptr), gd, gs, bd, es, CU_TENSOR_MAP_INTERLEAVE_NONE,
      CU_TENSOR_MAP_SWIZZLE_128B, CU_TENSOR_MAP_L2_PROMOTION_L2_256B, CU_TENSOR_MAP_FLOAT_OOB_FILL_NONE);
}

}

extern "C" void kernel_launch(void* const* d_in, const int* in_sizes, int n_in, void* d_out, int out_size) {
  static EncodeFn enc = nullptr;
  if (!enc) {
    cudaDriverEntryPointQueryResult qr;
    cudaGetDriverEntryPoint("cuTensorMapEncodeTiled", (void**)&enc, cudaEnableDefault, &qr);
    cudaFuncSetAttribute(rnnt_joint_kernel, cudaFuncAttributeMaxDynamicSharedMemorySize, kSmemBytes);
  }
  Params P;
  {
    cuuint64_t gd[4] = {256, 2, 2000, 2};
    cuuint64_t gs[3] = {512, 1024, 4000ull * 512};
    cuuint32_t bd[4] = {64, 1, 64, 1};
    cuuint32_t es[4] = {1, 1, 1, 1};
    enc(&P.x, CU_TENSOR_MAP_DATA_TYPE_BFLOAT16, 4, d_in[0], gd, gs, bd, es, CU_TENSOR_MAP_INTERLEAVE_NONE,
        CU_TENSOR_MAP_SWIZZLE_128B, XPROMO, CU_TENSOR_MAP_FLOAT_OOB_FILL_NONE);
  }
  P.xptr = d_in[0];
  make_map3(enc, &P.w1, d_in[1], 768, 64, 2);
  make_map3(enc, &P.w2, d_in[2], 768, 64, 2);
  make_map3(enc, &P.g, d_in[3], 16, 8, 4);
  make_map3(enc, &P.wf, d_in[4], 256, 64, 2);
  make_map3(enc, &P.wg, d_in[5], 256, 64, 2);
  make_map3(enc, &P.wo, d_in[6], 256, 64, 2);
  make_map3(enc, &P.out64, d_out, 16000, 64, 1);
  make_map3(enc, &P.out56, d_out, 16000, 56, 1);
  rnnt_joint_kernel<<<kNumCtas, kThreads, kSmemBytes>>>(P);
}
```

```cpp
#include <cuda_runtime.h>
#include <cuda_bf16.h>
#include <cuda.h>
#include <stdint.h>

#define ARRK 3
#define XBULK 0
#define SKEW1 2
#define SKEW2 2
#define TSPLIT 0
#define WOGATE 1
#define XPREF 1
#define XFIRST 3
#define XSTEP 1
#define XPROMO CU_TENSOR_MAP_L2_PROMOTION_L2_128B
namespace {

constexpr int kT2 = 1000;
constexpr int kR = 31;
constexpr int kNumCtas = 132;
constexpr int kThreads = 384;
constexpr int kSlot = 16384;

constexpr int kSlotFE = 9, kSlotF = 10, kSlotH = 11;
constexpr int kOffG = 13 * kSlot;
constexpr int kOffGE = kOffG + 4096;
constexpr int kGEPitch = 272;
constexpr int kGEBytes = 32 * kGEPitch;
constexpr int kOffBar = kOffGE + kGEBytes;
constexpr int kBarX = 0;
constexpr int kBarW = 4;
constexpr int kBarE = 40;
constexpr int kBarHX = 67, kBarFX = 68, kBarFE = 69, kBarG = 70, kBarP0 = 71;
constexpr int kBarRH = 72, kBarRF = 74, kBarRE = 76;
constexpr int kBarPR = 78;
constexpr int kBarGW = 86;
constexpr int kBarFO = 87;
constexpr int kBarGE = 88;
constexpr int kNumBars = 89;
constexpr int kSmemBytes = kOffBar + kNumBars * 8 + 1024;

__device__ __align__(128) float g_ge[2 * kGEBytes / 4];
__device__ unsigned int g_ge_flag[2];
__device__ unsigned int g_cta_count;

#define TS(slot_, idx_) do {} while (0)
#define GT(idx_) do {} while (0)
#define TS_DUMP(slot_, lo_, hi_) do {} while (0)
#define GT_DUMP(idx_) do {} while (0)

__device__ __forceinline__ uint32_t smem_u32(const void* p) { return (uint32_t)__cvta_generic_to_shared(p); }
__device__ __forceinline__ void mbar_init(uint32_t a, uint32_t c) { asm volatile("mbarrier.init.shared.b64 [%0], %1;" ::"r"(a), "r"(c) : "memory"); }
__device__ __forceinline__ void mbar_expect(uint32_t a, uint32_t b) { asm volatile("mbarrier.arrive.expect_tx.shared.b64 _, [%0], %1;" ::"r"(a), "r"(b) : "memory"); }
__device__ __forceinline__ void mbar_arrive(uint32_t a) { asm volatile("mbarrier.arrive.shared.b64 _, [%0];" ::"r"(a) : "memory"); }
__device__ __forceinline__ void mbar_arrive_pred(uint32_t a, bool p) {
  asm volatile("{\n.reg .pred q;\nsetp.ne.u32 q, %1, 0;\n@q mbarrier.arrive.shared.b64 _, [%0];\n}\n" ::"r"(a), "r"((uint32_t)p) : "memory");
}
__device__ __forceinline__ void bar_arrive_pred(bool p) {
  asm volatile("{\n.reg .pred q;\nsetp.ne.u32 q, %0, 0;\n@q bar.arrive 4, 256;\n}\n" ::"r"((uint32_t)p) : "memory");
}
#define DEF_NAMED(ID) \
__device__ __forceinline__ void bar_arrive_pred##ID(bool p) { asm volatile("{\n.reg .pred q;\nsetp.ne.u32 q, %0, 0;\n@q bar.arrive " #ID ", 256;\n}\n" ::"r"((uint32_t)p) : "memory"); } \
__device__ __forceinline__ void bar_sync_pred##ID(bool p) { asm volatile("{\n.reg .pred q;\nsetp.ne.u32 q, %0, 0;\n@q bar.sync " #ID ", 256;\n}\n" ::"r"((uint32_t)p) : "memory"); }
DEF_NAMED(4)
DEF_NAMED(5)
DEF_NAMED(6)
__device__ __forceinline__ bool mbar_try(uint32_t a) {
  uint32_t ok;
  asm volatile("{\n.reg .pred p;\nmbarrier.try_wait.parity.shared.b64 p, [%1], 0;\nselp.u32 %0, 1, 0, p;\n}\n" : "=r"(ok) : "r"(a) : "memory");
  return ok != 0;
}
__device__ __forceinline__ bool mbar_test(uint32_t a) {
  uint32_t ok;
  asm volatile("{\n.reg .pred p;\nmbarrier.test_wait.parity.shared.b64 p, [%1], 0;\nselp.u32 %0, 1, 0, p;\n}\n" : "=r"(ok) : "r"(a) : "memory");
  return ok != 0;
}
__device__ __forceinline__ bool mbar_try_cluster(uint32_t a) {
  uint32_t ok;
  asm volatile("{\n.reg .pred p;\nmbarrier.try_wait.parity.acquire.cluster.shared.b64 p, [%1], 0;\nselp.u32 %0, 1, 0, p;\n}\n" : "=r"(ok) : "r"(a) : "memory");
  return ok != 0;
}
__device__ __forceinline__ void mbar_wait_slow(uint32_t a) {
  const long long t0 = clock64();
  while (!mbar_try(a)) { if (clock64() - t0 > 4000000ll) break; }
}
__device__ __forceinline__ void mbar_wait_cluster_slow(uint32_t a) {
  const long long t0 = clock64();
  while (!mbar_try_cluster(a)) { if (clock64() - t0 > 4000000ll) break; }
}
__device__ __forceinline__ void mbar_wait(uint32_t a) { if (!mbar_try(a)) mbar_wait_slow(a); }
__device__ __forceinline__ void mbar_wait_cluster(uint32_t a) { if (!mbar_try_cluster(a)) mbar_wait_cluster_slow(a); }
__device__ __forceinline__ uint32_t mapa(uint32_t a, uint32_t r) { uint32_t d; asm volatile("mapa.shared::cluster.u32 %0, %1, %2;" : "=r"(d) : "r"(a), "r"(r)); return d; }
__device__ __forceinline__ bool elect_one() { uint32_t p; asm volatile("{\n.reg .pred P;\nelect.sync _|P, 0xffffffff;\nselp.u32 %0, 1, 0, P;\n}\n" : "=r"(p)); return p != 0; }
__device__ __forceinline__ void fence_async_smem() { asm volatile("fence.proxy.async.shared::cta;" ::: "memory"); }
__device__ __forceinline__ void bar_consumers() { asm volatile("bar.sync 1, 256;" ::: "memory"); }
__device__ __forceinline__ void bar_wg(int wg) { asm volatile("bar.sync %0, 128;" ::"r"(2 + wg) : "memory"); }
__device__ __forceinline__ void cluster_sync_relaxed() { asm volatile("barrier.cluster.arrive.relaxed.aligned;\nbarrier.cluster.wait.aligned;" ::: "memory"); }
__device__ __forceinline__ void wg_fence() { asm volatile("wgmma.fence.sync.aligned;" ::: "memory"); }
__device__ __forceinline__ void wg_commit() { asm volatile("wgmma.commit_group.sync.aligned;" ::: "memory"); }
template <int N> __device__ __forceinline__ void wg_wait() { asm volatile("wgmma.wait_group.sync.aligned %0;" ::"n"(N) : "memory"); }

__device__ __forceinline__ void tma_load_3d(uint32_t dst, const CUtensorMap* tm, uint32_t bar, int c0, int c1, int c2) {
  asm volatile("cp.async.bulk.tensor.3d.shared::cluster.global.mbarrier::complete_tx::bytes [%0], [%1, {%3, %4, %5}], [%2];"
               ::"r"(dst), "l"(tm), "r"(bar), "r"(c0), "r"(c1), "r"(c2) : "memory");
}
__device__ __forceinline__ void tma_load_4d(uint32_t dst, const CUtensorMap* tm, uint32_t bar, int c0, int c1, int c2, int c3) {
  asm volatile("cp.async.bulk.tensor.4d.shared::cluster.global.mbarrier::complete_tx::bytes [%0], [%1, {%3, %4, %5, %6}], [%2];"
               ::"r"(dst), "l"(tm), "r"(bar), "r"(c0), "r"(c1), "r"(c2), "r"(c3) : "memory");
}
__device__ __forceinline__ void tma_load_4d_mc(uint32_t dst, const CUtensorMap* tm, uint32_t bar, int c0, int c1, int c2, int c3, uint16_t mask) {
  asm volatile("cp.async.bulk.tensor.4d.shared::cluster.global.mbarrier::complete_tx::bytes.multicast::cluster [%0], [%1, {%3, %4, %5, %6}], [%2], %7;"
               ::"r"(dst), "l"(tm), "r"(bar), "r"(c0), "r"(c1), "r"(c2), "r"(c3), "h"(mask) : "memory");
}
__device__ __forceinline__ void tma_store_3d(const CUtensorMap* tm, uint32_t src, int c0, int c1, int c2) {
  asm volatile("cp.async.bulk.tensor.3d.global.shared::cta.bulk_group [%0, {%2, %3, %4}], [%1];"
               ::"l"(tm), "r"(src), "r"(c0), "r"(c1), "r"(c2) : "memory");
}
__device__ __forceinline__ void bulk_load(uint32_t dst, const void* src, uint32_t bytes, uint32_t bar) {
  asm volatile("cp.async.bulk.shared::cluster.global.mbarrier::complete_tx::bytes [%0], [%1], %2, [%3];"
               ::"r"(dst), "l"(src), "r"(bytes), "r"(bar) : "memory");
}
__device__ __forceinline__ void dsmem_copy(uint32_t dst_remote, uint32_t src, uint32_t bytes, uint32_t bar_remote) {
  asm volatile("cp.async.bulk.shared::cluster.shared::cta.mbarrier::complete_tx::bytes [%0], [%1], %2, [%3];"
               ::"r"(dst_remote), "r"(src), "r"(bytes), "r"(bar_remote) : "memory");
}
__device__ __forceinline__ void stsm_x4_trans(uint32_t addr, uint32_t r0, uint32_t r1, uint32_t r2, uint32_t r3) {
  asm volatile("stmatrix.sync.aligned.m8n8.x4.trans.shared.b16 [%0], {%1, %2, %3, %4};" ::"r"(addr), "r"(r0), "r"(r1), "r"(r2), "r"(r3) : "memory");
}
__device__ __forceinline__ void stsm_x4(uint32_t addr, uint32_t r0, uint32_t r1, uint32_t r2, uint32_t r3) {
  asm volatile("stmatrix.sync.aligned.m8n8.x4.shared.b16 [%0], {%1, %2, %3, %4};" ::"r"(addr), "r"(r0), "r"(r1), "r"(r2), "r"(r3) : "memory");
}
__device__ __forceinline__ float2 lds64(uint32_t a) { float2 v; asm volatile("ld.shared.v2.f32 {%0, %1}, [%2];" : "=f"(v.x), "=f"(v.y) : "r"(a) : "memory"); return v; }
__device__ __forceinline__ float4 lds128(uint32_t a) { float4 v; asm volatile("ld.shared.v4.f32 {%0, %1, %2, %3}, [%4];" : "=f"(v.x), "=f"(v.y), "=f"(v.z), "=f"(v.w) : "r"(a) : "memory"); return v; }
__device__ __forceinline__ void sts64(uint32_t a, float x, float y) { asm volatile("st.shared.v2.f32 [%0], {%1, %2};" ::"r"(a), "f"(x), "f"(y) : "memory"); }
__device__ __forceinline__ float tanh_fast(float x) { float y; asm("tanh.approx.f32 %0, %1;" : "=f"(y) : "f"(x)); return y; }
__device__ __forceinline__ uint32_t tanh2_pack(float lo, float hi) {
  uint32_t r;
  asm volatile("{\n.reg .f32 a, b;\ntanh.approx.f32 a, %1;\ntanh.approx.f32 b, %2;\ncvt.rn.bf16x2.f32 %0, b, a;\n}\n" : "=r"(r) : "f"(lo), "f"(hi));
  return r;
}
__device__ __forceinline__ uint32_t pack_bf16(float lo, float hi) { uint32_t r; asm("cvt.rn.bf16x2.f32 %0, %1, %2;" : "=r"(r) : "f"(hi), "f"(lo)); return r; }
__device__ __forceinline__ float gelu_tanh(float x) {
  const float k0 = 0.7978845608028654f, k1 = 0.7978845608028654f * 0.044715f;
  float u = x * fmaf(x * x, k1, k0);
  float hx = 0.5f * x;
  return fmaf(hx, tanh_fast(u), hx);
}
__device__ __forceinline__ uint64_t make_desc(uint32_t addr, uint32_t lbo, uint32_t sbo) {
  return (uint64_t)((addr & 0x3FFFF) >> 4) | ((uint64_t)(lbo >> 4) << 16) | ((uint64_t)(sbo >> 4) << 32) | ((uint64_t)1 << 62);
}

__device__ __forceinline__ uint32_t desc_lo(uint32_t addr, uint32_t lbo) { return ((addr & 0x3FFFF) >> 4) | ((lbo >> 4) << 16); }
__device__ __forceinline__ uint64_t desc_at(uint32_t lo, uint32_t off) { return ((uint64_t)0x40000040u << 32) | (uint64_t)(lo + (off >> 4)); }

__device__ __forceinline__ void wgmma_ss_n64(float (&d)[32], uint64_t da, uint64_t db, int scale_d) {
  asm volatile("{\n.reg .pred p;\nsetp.ne.b32 p, %34, 0;\n"
    "wgmma.mma_async.sync.aligned.m64n64k16.f32.bf16.bf16 {%0, %1, %2, %3, %4, %5, %6, %7, %8, %9, %10, %11, %12, %13, %14, %15, %16, %17, %18, %19, %20, %21, %22, %23, %24, %25, %26, %27, %28, %29, %30, %31}, %32, %33, p, 1, 1, 1, 0;\n}\n"
    : "+f"(d[0]), "+f"(d[1]), "+f"(d[2]), "+f"(d[3]), "+f"(d[4]), "+f"(d[5]), "+f"(d[6]), "+f"(d[7]), "+f"(d[8]), "+f"(d[9]), "+f"(d[10]), "+f"(d[11]), "+f"(d[12]), "+f"(d[13]), "+f"(d[14]), "+f"(d[15]), "+f"(d[16]), "+f"(d[17]), "+f"(d[18]), "+f"(d[19]), "+f"(d[20]), "+f"(d[21]), "+f"(d[22]), "+f"(d[23]), "+f"(d[24]), "+f"(d[25]), "+f"(d[26]), "+f"(d[27]), "+f"(d[28]), "+f"(d[29]), "+f"(d[30]), "+f"(d[31])
    : "l"(da), "l"(db), "r"(scale_d));
}

__device__ __forceinline__ void wgmma_ss_n32(float (&d)[16], uint64_t da, uint64_t db, int scale_d) {
  asm volatile("{\n.reg .pred p;\nsetp.ne.b32 p, %18, 0;\n"
    "wgmma.mma_async.sync.aligned.m64n32k16.f32.bf16.bf16 {%0, %1, %2, %3, %4, %5, %6, %7, %8, %9, %10, %11, %12, %13, %14, %15}, %16, %17, p, 1, 1, 1, 0;\n}\n"
    : "+f"(d[0]), "+f"(d[1]), "+f"(d[2]), "+f"(d[3]), "+f"(d[4]), "+f"(d[5]), "+f"(d[6]), "+f"(d[7]), "+f"(d[8]), "+f"(d[9]), "+f"(d[10]), "+f"(d[11]), "+f"(d[12]), "+f"(d[13]), "+f"(d[14]), "+f"(d[15])
    : "l"(da), "l"(db), "r"(scale_d));
}

__device__ __forceinline__ void wgmma_ss_n8(float (&d)[4], uint64_t da, uint64_t db, int scale_d) {
  asm volatile("{\n.reg .pred p;\nsetp.ne.b32 p, %6, 0;\n"
    "wgmma.mma_async.sync.aligned.m64n8k16.f32.bf16.bf16 {%0, %1, %2, %3}, %4, %5, p, 1, 1, 1, 0;\n}\n"
    : "+f"(d[0]), "+f"(d[1]), "+f"(d[2]), "+f"(d[3])
    : "l"(da), "l"(db), "r"(scale_d));
}

__device__ __forceinline__ void wgmma_rs_n64(float (&d)[32], uint32_t a0, uint32_t a1, uint32_t a2, uint32_t a3, uint64_t db, int scale_d) {
  asm volatile("{\n.reg .pred p;\nsetp.ne.b32 p, %37, 0;\n"
    "wgmma.mma_async.sync.aligned.m64n64k16.f32.bf16.bf16 {%0, %1, %2, %3, %4, %5, %6, %7, %8, %9, %10, %11, %12, %13, %14, %15, %16, %17, %18, %19, %20, %21, %22, %23, %24, %25, %26, %27, %28, %29, %30, %31}, {%32, %33, %34, %35}, %36, p, 1, 1, 1;\n}\n"
    : "+f"(d[0]), "+f"(d[1]), "+f"(d[2]), "+f"(d[3]), "+f"(d[4]), "+f"(d[5]), "+f"(d[6]), "+f"(d[7]), "+f"(d[8]), "+f"(d[9]), "+f"(d[10]), "+f"(d[11]), "+f"(d[12]), "+f"(d[13]), "+f"(d[14]), "+f"(d[15]), "+f"(d[16]), "+f"(d[17]), "+f"(d[18]), "+f"(d[19]), "+f"(d[20]), "+f"(d[21]), "+f"(d[22]), "+f"(d[23]), "+f"(d[24]), "+f"(d[25]), "+f"(d[26]), "+f"(d[27]), "+f"(d[28]), "+f"(d[29]), "+f"(d[30]), "+f"(d[31])
    : "r"(a0), "r"(a1), "r"(a2), "r"(a3), "l"(db), "r"(scale_d));
}

__host__ __device__ constexpr int unit_slot(int u) {
  constexpr int t[36] = {4, 5, 6, 7, 8, 4, 5, 6, 0, 7, 8, 4,  1, 5, 6, 0, 2, 7, 8, 4, 3, 1, 5, 6,
                         0, 2, 7, 8,  4, 3, 1, 5, 6, 0, 2, 7};
  return t[u];
}
__host__ __device__ constexpr int unit_wait(int u) {
  constexpr int t[36] = {-1, -1, -1, -1, -1, 0, 1, 2, 2, 3, 4, 5,  5, 6, 7, 8, 8, 9, 10, 11, 11, 12, 13, 14,
                         15, 16, 17, 18,  19, 20, 21, 22, 23, 24, 25, 26};
  return t[u];
}

__device__ __forceinline__ uint32_t stage_off(int g, int j) {
  return g == 0 ? (j < 2 ? 8 * kSlot + j * 8192 : 10 * kSlot + (j - 2) * 8192)
                : (j < 2 ? 12 * kSlot + j * 8192 : (j == 2 ? 11 * kSlot + 8192 : 9 * kSlot));
}

struct Params {
  CUtensorMap x, w1, w2, wf, wg, wo, g, out64, out56;
  const void* xptr;
};

__device__ __forceinline__ void init_bar(uint32_t bars, int i) {
  const uint32_t a = bars + i * 8;
  const bool is_e = (i >= kBarE && i < kBarE + 27);
  mbar_init(a, is_e ? 8 : 1);
  if (!is_e) {
    uint32_t bytes = 16384;
    if (i == kBarFX) bytes = 8192;
    if (i == kBarFE) bytes = 8192;
    mbar_expect(a, bytes);
  }
}

__device__ __forceinline__ void store_pieces(const Params& P, uint32_t sb, uint32_t bars, int g, uint32_t cta, int b, int r0, int rvalid) {
  const int rl0 = cta * 16 + g * 8;
  if (rl0 >= rvalid) return;
  const CUtensorMap* omap = (rl0 + 8 <= rvalid) ? &P.out64 : &P.out56;
#pragma unroll
  for (int j = 0; j < 4; j++) {
    mbar_wait(bars + (kBarPR + g * 4 + j) * 8);
    if (elect_one()) {
      tma_store_3d(omap, sb + stage_off(g, j), 0, (b * kT2 + r0 + rl0) * 8, j);
      asm volatile("cp.async.bulk.commit_group;" ::: "memory");
    }
    __syncwarp();
    if (j == 0) TS(2, 12 + g);
    if (j == 3) TS(2, 14 + g);
  }
  if (elect_one()) asm volatile("cp.async.bulk.wait_group.read 0;" ::: "memory");
  __syncwarp();
  if (g == 1) { TS(2, 11); GT(1); TS_DUMP(2, 11, 12); GT_DUMP(1); }
  TS_DUMP(2, 12 + g, 13 + g); TS_DUMP(2, 14 + g, 15 + g);
}

__global__ void __cluster_dims__(2, 1, 1) __launch_bounds__(kThreads, 1)
rnnt_joint_kernel(const __grid_constant__ Params P) {
  extern __shared__ uint8_t smem_raw[];
  const uint32_t sb = (smem_u32(smem_raw) + 1023u) & ~1023u;
  const uint32_t bars = sb + kOffBar;
  const int warp = threadIdx.x >> 5, lane = threadIdx.x & 31;
  uint32_t cta;
  asm volatile("mov.u32 %0, %%cluster_ctarank;" : "=r"(cta));
  const uint32_t peer = cta ^ 1u;
  const int cl = blockIdx.x >> 1;
  const bool ge_cta = cl < 2;
  const int b = ge_cta ? cl : ((cl - 2) >> 5);
  const int r0 = ge_cta ? 32 * kR : ((cl - 2) & 31) * kR;
  const int rvalid = ge_cta ? kT2 - 32 * kR : kR;

  if (warp >= 8) {
    asm volatile("setmaxnreg.dec.sync.aligned.u32 40;");
    if (warp > 8) {
      if (elect_one()) {
#pragma unroll
        for (int i = 0; i < 5; i++) if (57 + (warp - 9) * 5 + i < kBarG) init_bar(bars, 57 + (warp - 9) * 5 + i);
#pragma unroll
        for (int i = 0; i < 5; i++) if (kBarRH + (warp - 9) * 5 + i < kBarGW) mbar_init(bars + (kBarRH + (warp - 9) * 5 + i) * 8, 4);
        if (warp == 11) { mbar_init(bars + kBarGW * 8, 8); mbar_init(bars + kBarFO * 8, 8); mbar_init(bars + kBarGE * 8, 1); mbar_expect(bars + kBarGE * 8, kGEBytes); }
        asm volatile("fence.mbarrier_init.release.cluster;" ::: "memory");
      }
      __syncwarp();
      asm volatile("barrier.cluster.arrive.relaxed.aligned;" ::: "memory");
      if (warp == 11 && lane < 9) asm volatile("prefetch.tensormap [%0];" ::"l"(reinterpret_cast<const CUtensorMap*>(&P) + lane) : "memory");
      __syncwarp();
      asm volatile("barrier.cluster.wait.aligned;" ::: "memory");
      if (warp == 10 && ge_cta) {
        mbar_wait(bars + kBarGW * 8);
        if (elect_one()) {
          __threadfence();
          asm volatile("red.release.gpu.global.add.u32 [%0], 1;" ::"l"(&g_ge_flag[b]) : "memory");
        }
        __syncwarp();
      }
      if (warp == 11) {
        if (elect_one()) {
          const unsigned int ticket = atomicAdd(&g_cta_count, 1u);
          const unsigned int want = (ticket / kNumCtas + 1u) * 2u;
          const long long t0 = clock64();
          unsigned int v;
          do {
            __nanosleep(200);
            asm volatile("ld.acquire.gpu.global.u32 %0, [%1];" : "=r"(v) : "l"(&g_ge_flag[b]) : "memory");
          } while ((int)(v - want) < 0 && clock64() - t0 < 4000000ll);
          asm volatile("fence.proxy.async;" ::: "memory");
          bulk_load(sb + kOffGE, reinterpret_cast<const char*>(g_ge) + b * kGEBytes, kGEBytes, bars + kBarGE * 8);
        }
        __syncwarp();
        return;
      }
      if (warp == 10) store_pieces(P, sb, bars, 1, cta, b, r0, rvalid);
      if (warp == 10) return;
#pragma unroll
      for (int g = 0; g < 2; g++) {
        mbar_wait(bars + (kBarRH + g) * 8);
        if (elect_one()) {
          const uint32_t src = sb + kSlotH * kSlot + (2 * cta + g) * 8192;
          dsmem_copy(mapa(src, peer), src, 8192, mapa(bars + kBarHX * 8, peer));
        }
        __syncwarp();
      }
#pragma unroll
      for (int g = 0; g < 2; g++) {
        mbar_wait(bars + (kBarRF + g) * 8);
        if (elect_one()) {
          const uint32_t src = sb + kSlotF * kSlot + (2 * cta + g) * 4096;
          dsmem_copy(mapa(src, peer), src, 4096, mapa(bars + kBarFX * 8, peer));
        }
        __syncwarp();
      }
#pragma unroll
      for (int g = 0; g < 2; g++) {
        mbar_wait(bars + (kBarRE + g) * 8);
        if (elect_one())
          dsmem_copy(mapa(sb + kSlotFE * kSlot + (2 * cta + g) * 4096, peer), sb + kSlotH * kSlot + g * 4096, 4096, mapa(bars + kBarFE * 8, peer));
        __syncwarp();
      }
      store_pieces(P, sb, bars, 0, cta, b, r0, rvalid);
      return;
    }
    TS(2, 0);
    GT(0);
    const int par = cta == 0 ? 1 : 0;
    const int q0 = cta == 0 ? 2 * r0 - 2 : 2 * r0 - 1;
    if (elect_one()) {
      mbar_init(bars + kBarX * 8, 1); mbar_expect(bars + kBarX * 8, 16384);
      mbar_init(bars + kBarW * 8, 1); mbar_expect(bars + kBarW * 8, 16384);
      fence_async_smem();
      tma_load_4d(sb, &P.x, bars + kBarX * 8, 0, 1, 2 * r0 - 2, b);
      tma_load_4d(sb + 8192, &P.x, bars + kBarX * 8, 0, 0, 2 * r0 - 1, b);
      tma_load_3d(sb + unit_slot(0) * kSlot, &P.w1, bars + kBarW * 8, 0, 0, 2 * cta);
      TS(2, 7);
#pragma unroll
      for (int i = 1; i < 9; i++) if (i != kBarW) { mbar_init(bars + i * 8, 1); mbar_expect(bars + i * 8, 16384); }
      if (ge_cta) { mbar_init(bars + kBarG * 8, 1); mbar_expect(bars + kBarG * 8, 4 * 16384 + 4096); mbar_init(bars + kBarP0 * 8, 8); }
      asm volatile("fence.mbarrier_init.release.cluster;" ::: "memory");
      fence_async_smem();
      TS(2, 8);
      if (ge_cta) {
        tma_load_3d(sb + kOffG, &P.g, bars + kBarG * 8, 0, b * 8, 0);
#pragma unroll
        for (int i = 0; i < 4; i++) tma_load_3d(sb + (9 + i) * kSlot, &P.wg, bars + kBarG * 8, 0, i * 64, 2 * cta);
      }
#pragma unroll
      for (int u = 1; u < 5; u++)
        tma_load_3d(sb + unit_slot(u) * kSlot, &P.w1, bars + (kBarW + u) * 8, 0, (u % 3) * 256 + (u / 3) * 64, 2 * cta);
      TS(2, 10);
    }
    __syncwarp();
    TS(2, 6);
    cluster_sync_relaxed();
    TS(2, 1);
    if (elect_one()) {
#pragma unroll
      for (int p = 1; p < XFIRST; p++)
        tma_load_4d_mc(sb + p * kSlot + cta * 8192, &P.x, bars + (kBarX + p) * 8, p * 64, par, q0, b, (uint16_t)3);
    }
    __syncwarp();
#pragma unroll
    for (int p = XFIRST; p < 4; p++) {
      if (XSTEP == 1 || ((p - XFIRST) & 1) == 0) mbar_wait(bars + (kBarX + p - XFIRST) * 8);
      if (ge_cta && p == 3) mbar_wait(bars + kBarP0 * 8);
      if (elect_one())
        tma_load_4d_mc(sb + p * kSlot + cta * 8192, &P.x, bars + (kBarX + p) * 8, p * 64, par, q0, b, (uint16_t)3);
      __syncwarp();
    }
#pragma unroll
    for (int u = 5; u < 36; u++) {
      if (unit_wait(u) != unit_wait(u - 1)) mbar_wait(bars + (kBarE + unit_wait(u)) * 8);
      if (WOGATE >= 1 && u == 28) mbar_wait(bars + kBarFX * 8);
      if (WOGATE >= 2 && u == 32) mbar_wait(bars + kBarFE * 8);
      if (elect_one()) {
        const uint32_t dst = sb + unit_slot(u) * kSlot, bar = bars + (kBarW + u) * 8;
        if (u < 12) tma_load_3d(dst, &P.w1, bar, 0, (u % 3) * 256 + (u / 3) * 64, 2 * cta);
        else if (u < 24) tma_load_3d(dst, &P.w2, bar, 0, ((u - 12) % 3) * 256 + ((2 * cta + (u - 12) / 3) & 3) * 64, 2 * cta);
        else if (u < 28) tma_load_3d(dst, &P.wf, bar, 0, ((2 * cta + (u - 24)) & 3) * 64, 2 * cta);
        else tma_load_3d(dst, &P.wo, bar, 0, ((2 * cta + (u - 28)) & 3) * 64, ((u - 28) >> 2) * 2);
      }
      __syncwarp();
      if (u == 11) TS(2, 2);
      if (u == 23) TS(2, 3);
      if (u == 27) TS(2, 4);
      if (u == 35) TS(2, 5);
    }
    TS_DUMP(2, 0, 11); GT_DUMP(0);
  } else {
    asm volatile("setmaxnreg.inc.sync.aligned.u32 232;");
    const int wg = warp >> 2, w = warp & 3;
    const int gq = lane >> 2, q = lane & 3;
    const uint32_t panel = 2 * cta + wg;
    const int ch = panel * 64 + w * 16 + gq;
    const uint32_t dA = desc_lo(sb + wg * 8192, 8192);
    const uint32_t dB = desc_lo(sb, 16);
    const uint32_t dBo = desc_lo(sb + cta * 2 * 8192, 16), dBp = desc_lo(sb + (cta ^ 1) * 2 * 8192, 16);
    const uint32_t dFo = desc_lo(sb + cta * 2 * 4096, 16), dFp = desc_lo(sb + (cta ^ 1) * 2 * 4096, 16);
    if (elect_one()) {
#pragma unroll
      for (int i = 0; i < 6; i++) init_bar(bars, 9 + warp * 6 + i);
      asm volatile("fence.mbarrier_init.release.cluster;" ::: "memory");
    }
    __syncwarp();
    cluster_sync_relaxed();
    if (w == 0) TS(wg, 0);

    if (ge_cta) {
      float ga[4];
      mbar_wait(bars + kBarG * 8);
      wg_fence();
#pragma unroll
      for (int i = 0; i < 4; i++) {
#pragma unroll
        for (int s = 0; s < 4; s++)
          wgmma_ss_n8(ga, desc_at(dA, (9 + i) * kSlot + s * 2048), desc_at(dB, kOffG + i * 1024 + s * 32), (i | s) != 0);
      }
      wg_commit();
      wg_wait<0>();
      if (lane == 0) mbar_arrive(bars + kBarP0 * 8);
      float* gp = g_ge + b * (kGEBytes / 4) + ((ch & 7) >> 1) * (kGEPitch / 4) + (ch >> 4) * 4 + (ch & 1);
      gp[(2 * q) * 4 * (kGEPitch / 4)] = ga[0];
      gp[(2 * q + 1) * 4 * (kGEPitch / 4)] = ga[1];
      gp[(2 * q) * 4 * (kGEPitch / 4) + 2] = ga[2];
      gp[(2 * q + 1) * 4 * (kGEPitch / 4) + 2] = ga[3];
      __syncwarp();
      if (lane == 0) mbar_arrive(bars + kBarGW * 8);
    }

    {
      float acc[32];
#pragma unroll
      for (int u = 0; u < 12; u++) {
        const int p = u / 3, tap = u % 3;
        if (SKEW1 > 0 && u == 12 - SKEW1) bar_sync_pred5(wg == 1);
        if (tap == 0) mbar_wait(bars + (kBarX + p) * 8);
        mbar_wait(bars + (kBarW + u) * 8);
        if (u == 0 && w == 0) TS(wg, 1);
        wg_fence();
#pragma unroll
        for (int s = 0; s < 4; s++)
          wgmma_ss_n64(acc, desc_at(dA, unit_slot(u) * kSlot + s * 2048),
                       desc_at(dB, p * kSlot + (tap == 1 ? 8192 : (tap == 2 ? 128 : 0)) + s * 32), (u | s) != 0);
        wg_commit();
        if (SKEW1 > 0 && u == 11) bar_arrive_pred5(wg == 0);
        if (u > 0) {
          wg_wait<1>();
          if (lane == 0) mbar_arrive(bars + (kBarE + u - 1) * 8);
        }
      }
      wg_wait<0>();
      if (lane == 0) mbar_arrive(bars + (kBarE + 11) * 8);
      if (w == 0) TS(wg, 2);
      const uint32_t hp = sb + kSlotH * kSlot + panel * 8192;
      const int mi = lane >> 3, l8 = lane & 7;
#pragma unroll
      for (int jb = 0; jb < 8; jb += 2) {
        uint32_t r[4];
#pragma unroll
        for (int t = 0; t < 2; t++) {
          r[2 * t + 0] = pack_bf16(gelu_tanh(acc[4 * (jb + t) + 0]), gelu_tanh(acc[4 * (jb + t) + 1]));
          r[2 * t + 1] = pack_bf16(gelu_tanh(acc[4 * (jb + t) + 2]), gelu_tanh(acc[4 * (jb + t) + 3]));
        }
        const int n = 8 * (jb + (mi >> 1)) + l8;
        const int row = n >> 1, chunk = 2 * w + (mi & 1);
        stsm_x4_trans(hp + (n & 1) * 4096 + row * 128 + ((chunk ^ (row & 7)) << 4), r[0], r[1], r[2], r[3]);
      }
      __syncwarp();
      if (w == 0) TS(wg, 15);
      fence_async_smem();
      __syncwarp();
      if (lane == 0) mbar_arrive(bars + (kBarRH + wg) * 8);
      if (w == 0) TS(wg, 3);
    }
    {
      float acc[16];
#pragma unroll
      for (int v = 0; v < 12; v++) {
        const int i = v / 3, tap = v % 3;
        if (SKEW2 > 0 && v == 12 - SKEW2) bar_sync_pred6(wg == 1);
        if (v == 0) mbar_wait(bars + kBarRH * 8);
        if (v == 3) mbar_wait(bars + (kBarRH + 1) * 8);
        if (v == 6) { mbar_wait_cluster(bars + kBarHX * 8); if (w == 0) TS(wg, 4); }
        mbar_wait(bars + (kBarW + 12 + v) * 8);
        wg_fence();
#pragma unroll
        for (int s = 0; s < 4; s++)
          wgmma_ss_n32(acc, desc_at(dA, unit_slot(12 + v) * kSlot + s * 2048),
                       desc_at(i < 2 ? dBo : dBp, kSlotH * kSlot + (i & 1) * 8192 + (tap == 1 ? 4096 : (tap == 2 ? 128 : 0)) + s * 32), (v | s) != 0);
        wg_commit();
        if (SKEW2 > 0 && v == 11) bar_arrive_pred6(wg == 0);
        if (v > 0) {
          wg_wait<1>();
          if (lane == 0) mbar_arrive(bars + (kBarE + 12 + v - 1) * 8);
        }
      }
      wg_wait<0>();
      if (lane == 0) mbar_arrive(bars + (kBarE + 23) * 8);
      if (w == 0) TS(wg, 5);
      const uint32_t fp = sb + kSlotF * kSlot + panel * 4096;
      const int mi = lane >> 3, l8 = lane & 7;
#pragma unroll
      for (int jb = 0; jb < 4; jb += 2) {
        uint32_t r[4];
#pragma unroll
        for (int t = 0; t < 2; t++) {
          r[2 * t + 0] = pack_bf16(gelu_tanh(acc[4 * (jb + t) + 0]), gelu_tanh(acc[4 * (jb + t) + 1]));
          r[2 * t + 1] = pack_bf16(gelu_tanh(acc[4 * (jb + t) + 2]), gelu_tanh(acc[4 * (jb + t) + 3]));
        }
        const int n = 8 * (jb + (mi >> 1)) + l8;
        const int chunk = 2 * w + (mi & 1);
        stsm_x4_trans(fp + n * 128 + ((chunk ^ (n & 7)) << 4), r[0], r[1], r[2], r[3]);
      }
      fence_async_smem();
      __syncwarp();
      if (lane == 0) mbar_arrive(bars + (kBarRF + wg) * 8);
      if (w == 0) TS(wg, 6);
    }
    {
      float acc[16];
#pragma unroll
      for (int i = 0; i < 4; i++) {
        if (i < 2) mbar_wait(bars + (kBarRF + i) * 8);
        if (i == 2) { mbar_wait_cluster(bars + kBarFX * 8); if (w == 0) TS(wg, 7); }
        mbar_wait(bars + (kBarW + 24 + i) * 8);
        wg_fence();
#pragma unroll
        for (int s = 0; s < 4; s++)
          wgmma_ss_n32(acc, desc_at(dA, unit_slot(24 + i) * kSlot + s * 2048),
                       desc_at(i < 2 ? dFo : dFp, kSlotF * kSlot + (i & 1) * 4096 + s * 32), (i | s) != 0);
        wg_commit();
        if (i > 0) {
          wg_wait<1>();
          if (lane == 0) mbar_arrive(bars + (kBarE + 24 + i - 1) * 8);
        }
      }
      wg_wait<0>();
      if (w == 0) TS(wg, 8);
      const uint32_t qk = gq >> 1;
      const uint32_t off0 = qk * 128 + (((2 * w) ^ (2 * qk)) << 4) + (gq & 1) * 8;
      const uint32_t off1 = qk * 128 + (((2 * w + 1) ^ (2 * qk)) << 4) + (gq & 1) * 8;
      const uint32_t own = sb + kSlotFE * kSlot + panel * 4096;
      const uint32_t stg = sb + kSlotH * kSlot + wg * 4096;
#pragma unroll
      for (int jb = 0; jb < 4; jb++) {
        const uint32_t base = (((uint32_t)(jb >> 1) == cta) ? own : stg) + (4 * (jb & 1) + q) * 512;
        sts64(base + off0, acc[4 * jb + 0], acc[4 * jb + 1]);
        sts64(base + off1, acc[4 * jb + 2], acc[4 * jb + 3]);
      }
      fence_async_smem();
      __syncwarp();
      if (lane == 0) { mbar_arrive(bars + (kBarRE + wg) * 8); mbar_arrive(bars + kBarFO * 8); }
      if (w == 0) TS(wg, 9);
    }
    const int rl0 = cta * 16 + wg * 8;
    mbar_wait(bars + kBarFO * 8);
    mbar_wait(bars + kBarGE * 8);
    if (rl0 < rvalid) {
      if (w == 0) TS(wg, 10);
      const uint32_t fe_row = sb + kSlotFE * kSlot + ((4 * wg + w) * 4 + q) * 128;
      const uint32_t fe_h[2] = {fe_row + cta * 8192, fe_row + (cta ^ 1) * 8192};
      const uint32_t ge_h[2] = {sb + kOffGE + lane * kGEPitch + cta * 128, sb + kOffGE + lane * kGEPitch + (cta ^ 1) * 128};
      const int mi = lane >> 3, l8 = lane & 7;
      const uint32_t st = sb + (16 * w + (mi & 1) * 8 + l8) * 128;
      uint32_t A[64];
      float acc[2][32];
      if (wg == 0) {
        constexpr int PD = 3;
        float4 fa[PD], fb[PD], gg[PD];
#pragma unroll
        for (int kk = 0; kk < 16 + PD; kk++) {
          if (kk >= PD) {
            const int k = kk - PD, sl = k % PD;
            A[4 * k + 0] = tanh2_pack(fa[sl].x + gg[sl].x, fa[sl].z + gg[sl].y);
            A[4 * k + 1] = tanh2_pack(fa[sl].y + gg[sl].x, fa[sl].w + gg[sl].y);
            A[4 * k + 2] = tanh2_pack(fb[sl].x + gg[sl].z, fb[sl].z + gg[sl].w);
            A[4 * k + 3] = tanh2_pack(fb[sl].y + gg[sl].z, fb[sl].w + gg[sl].w);
          }
          if (kk < 16) {
            const int sl = kk % PD;
            if (kk == 8) {
              mbar_wait_cluster(bars + kBarFE * 8);
            }
            fa[sl] = lds128(fe_h[kk >> 3] + ((kk >> 2) & 1) * 4096 + ((((kk & 3) * 2) ^ (2 * q)) << 4));
            fb[sl] = lds128(fe_h[kk >> 3] + ((kk >> 2) & 1) * 4096 + ((((kk & 3) * 2 + 1) ^ (2 * q)) << 4));
            gg[sl] = lds128(ge_h[kk >> 3] + (kk & 7) * 16);
          }
        }
      } else {
        float sm_[128];
#pragma unroll
        for (int kk = 0; kk < 16; kk++) {
          if (kk == 8) mbar_wait_cluster(bars + kBarFE * 8);
          const float4 fa = lds128(fe_h[kk >> 3] + ((kk >> 2) & 1) * 4096 + ((((kk & 3) * 2) ^ (2 * q)) << 4));
          const float4 fb = lds128(fe_h[kk >> 3] + ((kk >> 2) & 1) * 4096 + ((((kk & 3) * 2 + 1) ^ (2 * q)) << 4));
          const float4 gg = lds128(ge_h[kk >> 3] + (kk & 7) * 16);
          sm_[8 * kk + 0] = fa.x + gg.x; sm_[8 * kk + 1] = fa.z + gg.y; sm_[8 * kk + 2] = fa.y + gg.x; sm_[8 * kk + 3] = fa.w + gg.y;
          sm_[8 * kk + 4] = fb.x + gg.z; sm_[8 * kk + 5] = fb.z + gg.w; sm_[8 * kk + 6] = fb.y + gg.z; sm_[8 * kk + 7] = fb.w + gg.w;
        }
#pragma unroll
        for (int i = 0; i < 128; i++) asm volatile("" : "+f"(sm_[i]));
        asm volatile("bar.sync 4, 256;" ::: "memory");
#pragma unroll
        for (int i = 0; i < 64; i++) A[i] = tanh2_pack(sm_[2 * i], sm_[2 * i + 1]);
      }
      asm volatile("barrier.cluster.arrive.relaxed.aligned;" ::: "memory");
#pragma unroll
      for (int kk = 0; kk < 16; kk++) {
        if ((kk & 3) == 0) { mbar_wait(bars + (kBarW + 28 + (kk >> 2)) * 8); wg_fence(); }
        wgmma_rs_n64(acc[0], A[4 * kk], A[4 * kk + 1], A[4 * kk + 2], A[4 * kk + 3],
                     desc_at(dB, unit_slot(28 + (kk >> 2)) * kSlot + (kk & 3) * 2048), kk != 0);
        if (kk == ARRK) bar_arrive_pred(wg == 0);
      }
      wg_commit();
      wg_wait<0>();
#pragma unroll
      for (int jb = 0; jb < 8; jb += 2) {
        const uint32_t r0_ = pack_bf16(acc[0][4 * jb + 0], acc[0][4 * jb + 1]), r1_ = pack_bf16(acc[0][4 * jb + 2], acc[0][4 * jb + 3]);
        const uint32_t r2_ = pack_bf16(acc[0][4 * jb + 4], acc[0][4 * jb + 5]), r3_ = pack_bf16(acc[0][4 * jb + 6], acc[0][4 * jb + 7]);
        stsm_x4(st + (wg ? stage_off(1, 0) : stage_off(0, 0)) + (((jb + (mi >> 1)) ^ l8) << 4), r0_, r1_, r2_, r3_);
      }
      fence_async_smem();
      __syncwarp();
      mbar_arrive_pred(bars + (kBarPR + wg * 4) * 8, lane == 0);
      if (w == 0) TS(wg, 11);
#pragma unroll
      for (int j = 0; j < 4; j++) {
        const int jn = j + 1;
        if (jn == 2) {
#pragma unroll
          for (int i = 0; i < 4; i++) mbar_wait(bars + (kBarW + 32 + i) * 8);
        }
        if (j < 3) wg_fence();
        const uint32_t stj = st + (wg ? stage_off(1, j) : stage_off(0, j));
#pragma unroll
        for (int kk = 0; kk < 16; kk++) {
          if (j < 3)
            wgmma_rs_n64(acc[jn & 1], A[4 * kk], A[4 * kk + 1], A[4 * kk + 2], A[4 * kk + 3],
                         desc_at(dB, unit_slot(28 + (jn >> 1) * 4 + (kk >> 2)) * kSlot + (jn & 1) * 8192 + (kk & 3) * 2048), kk != 0);
          if (kk == 1 && j > 0) {
            if (j < 3) { wg_commit(); wg_wait<1>(); } else { wg_wait<0>(); }
          }
          if (j > 0 && kk >= 2 && kk < 10 && (kk & 1) == 0) {
            const int jb = kk - 2;
            const uint32_t r0_ = pack_bf16(acc[j & 1][4 * jb + 0], acc[j & 1][4 * jb + 1]), r1_ = pack_bf16(acc[j & 1][4 * jb + 2], acc[j & 1][4 * jb + 3]);
            const uint32_t r2_ = pack_bf16(acc[j & 1][4 * jb + 4], acc[j & 1][4 * jb + 5]), r3_ = pack_bf16(acc[j & 1][4 * jb + 6], acc[j & 1][4 * jb + 7]);
            stsm_x4(stj + (((jb + (mi >> 1)) ^ l8) << 4), r0_, r1_, r2_, r3_);
          }
          if (j > 0 && kk == 9) {
            fence_async_smem();
            __syncwarp();
            mbar_arrive_pred(bars + (kBarPR + wg * 4 + j) * 8, lane == 0);
          }
        }
        if (j < 3) wg_commit();
        if (j == 0 && w == 0) TS(wg, 12);
        if (j == 2 && w == 0) TS(wg, 13);
      }
      if (w == 0) TS(wg, 14);
    } else {
      if (wg == 0) asm volatile("bar.arrive 4, 256;" ::: "memory");
      if (wg == 1) asm volatile("bar.sync 4, 256;" ::: "memory");
      mbar_wait_cluster(bars + kBarFE * 8);
      asm volatile("barrier.cluster.arrive.relaxed.aligned;" ::: "memory");
    }
    asm volatile("barrier.cluster.wait.aligned;" ::: "memory");
    if (w == 0) TS_DUMP(wg, 0, 16);
  }
}

typedef CUresult (*EncodeFn)(CUtensorMap*, CUtensorMapDataType, cuuint32_t, void*, const cuuint64_t*, const cuuint64_t*,
                             const cuuint32_t*, const cuuint32_t*, CUtensorMapInterleave, CUtensorMapSwizzle,
                             CUtensorMapL2promotion, CUtensorMapFloatOOBfill);

void make_map3(EncodeFn enc, CUtensorMap* tm, const void* ptr, uint64_t rows, uint32_t box_rows, uint32_t box_panels) {
  cuuint64_t gd[3] = {64, rows, 4};
  cuuint64_t gs[2] = {512, 128};
  cuuint32_t bd[3] = {64, box_rows, box_panels};
  cuuint32_t es[3] = {1, 1, 1};
  enc(tm, CU_TENSOR_MAP_DATA_TYPE_BFLOAT16, 3, const_cast<void*>(ptr), gd, gs, bd, es, CU_TENSOR_MAP_INTERLEAVE_NONE,
      CU_TENSOR_MAP_SWIZZLE_128B, CU_TENSOR_MAP_L2_PROMOTION_L2_256B, CU_TENSOR_MAP_FLOAT_OOB_FILL_NONE);
}

}

extern "C" void kernel_launch(void* const* d_in, const int* in_sizes, int n_in, void* d_out, int out_size) {
  static EncodeFn enc = nullptr;
  if (!enc) {
    cudaDriverEntryPointQueryResult qr;
    cudaGetDriverEntryPoint("cuTensorMapEncodeTiled", (void**)&enc, cudaEnableDefault, &qr);
    cudaFuncSetAttribute(rnnt_joint_kernel, cudaFuncAttributeMaxDynamicSharedMemorySize, kSmemBytes);
  }
  Params P;
  {
    cuuint64_t gd[4] = {256, 2, 2000, 2};
    cuuint64_t gs[3] = {512, 1024, 4000ull * 512};
    cuuint32_t bd[4] = {64, 1, 64, 1};
    cuuint32_t es[4] = {1, 1, 1, 1};
    enc(&P.x, CU_TENSOR_MAP_DATA_TYPE_BFLOAT16, 4, d_in[0], gd, gs, bd, es, CU_TENSOR_MAP_INTERLEAVE_NONE,
        CU_TENSOR_MAP_SWIZZLE_128B, XPROMO, CU_TENSOR_MAP_FLOAT_OOB_FILL_NONE);
  }
  P.xptr = d_in[0];
  make_map3(enc, &P.w1, d_in[1], 768, 64, 2);
  make_map3(enc, &P.w2, d_in[2], 768, 64, 2);
  make_map3(enc, &P.g, d_in[3], 16, 8, 4);
  make_map3(enc, &P.wf, d_in[4], 256, 64, 2);
  make_map3(enc, &P.wg, d_in[5], 256, 64, 2);
  make_map3(enc, &P.wo, d_in[6], 256, 64, 2);
  make_map3(enc, &P.out64, d_out, 16000, 64, 1);
  make_map3(enc, &P.out56, d_out, 16000, 56, 1);
  rnnt_joint_kernel<<<kNumCtas, kThreads, kSmemBytes>>>(P);
}
```

```cpp
#include <cuda_runtime.h>
#include <cuda_bf16.h>
#include <cuda.h>
#include <stdint.h>

#define ARRK 3
#define XBULK 0
#define SKEW1 2
#define SKEW2 2
#define TSPLIT 0
#define WOGATE 1
#define XPREF 1
#define XFIRST 3
#define XSTEP 1
#define XPROMO CU_TENSOR_MAP_L2_PROMOTION_L2_128B
namespace {

constexpr int kT2 = 1000;
constexpr int kR = 31;
constexpr int kNumCtas = 132;
constexpr int kThreads = 384;
constexpr int kSlot = 16384;

constexpr int kSlotFE = 9, kSlotF = 10, kSlotH = 11;
constexpr int kOffG = 13 * kSlot;
constexpr int kOffGE = kOffG + 4096;
constexpr int kGEPitch = 272;
constexpr int kGEBytes = 32 * kGEPitch;
constexpr int kOffBar = kOffGE + kGEBytes;
constexpr int kBarX = 0;
constexpr int kBarW = 4;
constexpr int kBarE = 40;
constexpr int kBarHX = 67, kBarFX = 68, kBarFE = 69, kBarG = 70, kBarP0 = 71;
constexpr int kBarRH = 72, kBarRF = 74, kBarRE = 76;
constexpr int kBarPR = 78;
constexpr int kBarGW = 86;
constexpr int kBarFO = 87;
constexpr int kBarGE = 88;
constexpr int kNumBars = 89;
constexpr int kOffZero = kOffBar + kNumBars * 8;
constexpr int kSmemBytes = kOffZero + 16 + 1024;

__device__ __align__(128) float g_ge[2 * kGEBytes / 4];
__device__ unsigned int g_ge_flag[2];
__device__ unsigned int g_cta_count;

#define TS(slot_, idx_) do {} while (0)
#define GT(idx_) do {} while (0)
#define TS_DUMP(slot_, lo_, hi_) do {} while (0)
#define GT_DUMP(idx_) do {} while (0)

__device__ __forceinline__ uint32_t smem_u32(const void* p) { return (uint32_t)__cvta_generic_to_shared(p); }
__device__ __forceinline__ void mbar_init(uint32_t a, uint32_t c) { asm volatile("mbarrier.init.shared.b64 [%0], %1;" ::"r"(a), "r"(c) : "memory"); }
__device__ __forceinline__ void mbar_expect(uint32_t a, uint32_t b) { asm volatile("mbarrier.arrive.expect_tx.shared.b64 _, [%0], %1;" ::"r"(a), "r"(b) : "memory"); }
__device__ __forceinline__ void mbar_arrive(uint32_t a) { asm volatile("mbarrier.arrive.shared.b64 _, [%0];" ::"r"(a) : "memory"); }
__device__ __forceinline__ void mbar_arrive_pred(uint32_t a, bool p) {
  asm volatile("{\n.reg .pred q;\nsetp.ne.u32 q, %1, 0;\n@q mbarrier.arrive.shared.b64 _, [%0];\n}\n" ::"r"(a), "r"((uint32_t)p) : "memory");
}
__device__ __forceinline__ void bar_arrive_pred(bool p) {
  asm volatile("{\n.reg .pred q;\nsetp.ne.u32 q, %0, 0;\n@q bar.arrive 4, 256;\n}\n" ::"r"((uint32_t)p) : "memory");
}
#define DEF_NAMED(ID) \
__device__ __forceinline__ void bar_arrive_pred##ID(bool p) { asm volatile("{\n.reg .pred q;\nsetp.ne.u32 q, %0, 0;\n@q bar.arrive " #ID ", 256;\n}\n" ::"r"((uint32_t)p) : "memory"); } \
__device__ __forceinline__ void bar_sync_pred##ID(bool p) { asm volatile("{\n.reg .pred q;\nsetp.ne.u32 q, %0, 0;\n@q bar.sync " #ID ", 256;\n}\n" ::"r"((uint32_t)p) : "memory"); }
DEF_NAMED(4)
DEF_NAMED(5)
DEF_NAMED(6)
__device__ __forceinline__ bool mbar_try(uint32_t a) {
  uint32_t ok;
  asm volatile("{\n.reg .pred p;\nmbarrier.try_wait.parity.shared.b64 p, [%1], 0;\nselp.u32 %0, 1, 0, p;\n}\n" : "=r"(ok) : "r"(a) : "memory");
  return ok != 0;
}
__device__ __forceinline__ bool mbar_test(uint32_t a) {
  uint32_t ok;
  asm volatile("{\n.reg .pred p;\nmbarrier.test_wait.parity.shared.b64 p, [%1], 0;\nselp.u32 %0, 1, 0, p;\n}\n" : "=r"(ok) : "r"(a) : "memory");
  return ok != 0;
}
__device__ __forceinline__ bool mbar_try_cluster(uint32_t a) {
  uint32_t ok;
  asm volatile("{\n.reg .pred p;\nmbarrier.try_wait.parity.acquire.cluster.shared.b64 p, [%1], 0;\nselp.u32 %0, 1, 0, p;\n}\n" : "=r"(ok) : "r"(a) : "memory");
  return ok != 0;
}
__device__ __forceinline__ void mbar_wait_slow(uint32_t a) {
  const long long t0 = clock64();
  while (!mbar_try(a)) { if (clock64() - t0 > 4000000ll) break; }
}
__device__ __forceinline__ void mbar_wait_cluster_slow(uint32_t a) {
  const long long t0 = clock64();
  while (!mbar_try_cluster(a)) { if (clock64() - t0 > 4000000ll) break; }
}
__device__ __forceinline__ void mbar_wait(uint32_t a) { if (!mbar_try(a)) mbar_wait_slow(a); }
__device__ __forceinline__ void mbar_wait_cluster(uint32_t a) { if (!mbar_try_cluster(a)) mbar_wait_cluster_slow(a); }
__device__ __forceinline__ uint32_t mapa(uint32_t a, uint32_t r) { uint32_t d; asm volatile("mapa.shared::cluster.u32 %0, %1, %2;" : "=r"(d) : "r"(a), "r"(r)); return d; }
__device__ __forceinline__ bool elect_one() { uint32_t p; asm volatile("{\n.reg .pred P;\nelect.sync _|P, 0xffffffff;\nselp.u32 %0, 1, 0, P;\n}\n" : "=r"(p)); return p != 0; }
__device__ __forceinline__ void fence_async_smem() { asm volatile("fence.proxy.async.shared::cta;" ::: "memory"); }
__device__ __forceinline__ void bar_consumers() { asm volatile("bar.sync 1, 256;" ::: "memory"); }
__device__ __forceinline__ void bar_wg(int wg) { asm volatile("bar.sync %0, 128;" ::"r"(2 + wg) : "memory"); }
__device__ __forceinline__ void cluster_sync_relaxed() { asm volatile("barrier.cluster.arrive.relaxed.aligned;\nbarrier.cluster.wait.aligned;" ::: "memory"); }
__device__ __forceinline__ void wg_fence() { asm volatile("wgmma.fence.sync.aligned;" ::: "memory"); }
__device__ __forceinline__ void wg_commit() { asm volatile("wgmma.commit_group.sync.aligned;" ::: "memory"); }
template <int N> __device__ __forceinline__ void wg_wait() { asm volatile("wgmma.wait_group.sync.aligned %0;" ::"n"(N) : "memory"); }

__device__ __forceinline__ void tma_load_3d(uint32_t dst, const CUtensorMap* tm, uint32_t bar, int c0, int c1, int c2) {
  asm volatile("cp.async.bulk.tensor.3d.shared::cluster.global.mbarrier::complete_tx::bytes [%0], [%1, {%3, %4, %5}], [%2];"
               ::"r"(dst), "l"(tm), "r"(bar), "r"(c0), "r"(c1), "r"(c2) : "memory");
}
__device__ __forceinline__ void tma_load_4d(uint32_t dst, const CUtensorMap* tm, uint32_t bar, int c0, int c1, int c2, int c3) {
  asm volatile("cp.async.bulk.tensor.4d.shared::cluster.global.mbarrier::complete_tx::bytes [%0], [%1, {%3, %4, %5, %6}], [%2];"
               ::"r"(dst), "l"(tm), "r"(bar), "r"(c0), "r"(c1), "r"(c2), "r"(c3) : "memory");
}
__device__ __forceinline__ void tma_load_4d_mc(uint32_t dst, const CUtensorMap* tm, uint32_t bar, int c0, int c1, int c2, int c3, uint16_t mask) {
  asm volatile("cp.async.bulk.tensor.4d.shared::cluster.global.mbarrier::complete_tx::bytes.multicast::cluster [%0], [%1, {%3, %4, %5, %6}], [%2], %7;"
               ::"r"(dst), "l"(tm), "r"(bar), "r"(c0), "r"(c1), "r"(c2), "r"(c3), "h"(mask) : "memory");
}
__device__ __forceinline__ void tma_store_3d(const CUtensorMap* tm, uint32_t src, int c0, int c1, int c2) {
  asm volatile("cp.async.bulk.tensor.3d.global.shared::cta.bulk_group [%0, {%2, %3, %4}], [%1];"
               ::"l"(tm), "r"(src), "r"(c0), "r"(c1), "r"(c2) : "memory");
}
__device__ __forceinline__ void bulk_load(uint32_t dst, const void* src, uint32_t bytes, uint32_t bar) {
  asm volatile("cp.async.bulk.shared::cluster.global.mbarrier::complete_tx::bytes [%0], [%1], %2, [%3];"
               ::"r"(dst), "l"(src), "r"(bytes), "r"(bar) : "memory");
}
__device__ __forceinline__ void dsmem_copy(uint32_t dst_remote, uint32_t src, uint32_t bytes, uint32_t bar_remote) {
  asm volatile("cp.async.bulk.shared::cluster.shared::cta.mbarrier::complete_tx::bytes [%0], [%1], %2, [%3];"
               ::"r"(dst_remote), "r"(src), "r"(bytes), "r"(bar_remote) : "memory");
}
__device__ __forceinline__ void stsm_x4_trans(uint32_t addr, uint32_t r0, uint32_t r1, uint32_t r2, uint32_t r3) {
  asm volatile("stmatrix.sync.aligned.m8n8.x4.trans.shared.b16 [%0], {%1, %2, %3, %4};" ::"r"(addr), "r"(r0), "r"(r1), "r"(r2), "r"(r3) : "memory");
}
__device__ __forceinline__ void stsm_x4(uint32_t addr, uint32_t r0, uint32_t r1, uint32_t r2, uint32_t r3) {
  asm volatile("stmatrix.sync.aligned.m8n8.x4.shared.b16 [%0], {%1, %2, %3, %4};" ::"r"(addr), "r"(r0), "r"(r1), "r"(r2), "r"(r3) : "memory");
}
__device__ __forceinline__ float2 lds64(uint32_t a) { float2 v; asm volatile("ld.shared.v2.f32 {%0, %1}, [%2];" : "=f"(v.x), "=f"(v.y) : "r"(a) : "memory"); return v; }
__device__ __forceinline__ float4 lds128(uint32_t a) { float4 v; asm volatile("ld.shared.v4.f32 {%0, %1, %2, %3}, [%4];" : "=f"(v.x), "=f"(v.y), "=f"(v.z), "=f"(v.w) : "r"(a) : "memory"); return v; }
__device__ __forceinline__ void sts64(uint32_t a, float x, float y) { asm volatile("st.shared.v2.f32 [%0], {%1, %2};" ::"r"(a), "f"(x), "f"(y) : "memory"); }
__device__ __forceinline__ float tanh_fast(float x) { float y; asm("tanh.approx.f32 %0, %1;" : "=f"(y) : "f"(x)); return y; }
__device__ __forceinline__ uint32_t tanh2_pack(float lo, float hi) {
  uint32_t r;
  asm volatile("{\n.reg .f32 a, b;\ntanh.approx.f32 a, %1;\ntanh.approx.f32 b, %2;\ncvt.rn.bf16x2.f32 %0, b, a;\n}\n" : "=r"(r) : "f"(lo), "f"(hi));
  return r;
}
__device__ __forceinline__ uint32_t pack_bf16(float lo, float hi) { uint32_t r; asm("cvt.rn.bf16x2.f32 %0, %1, %2;" : "=r"(r) : "f"(hi), "f"(lo)); return r; }
__device__ __forceinline__ float gelu_tanh(float x) {
  const float k0 = 0.7978845608028654f, k1 = 0.7978845608028654f * 0.044715f;
  float u = x * fmaf(x * x, k1, k0);
  float hx = 0.5f * x;
  return fmaf(hx, tanh_fast(u), hx);
}
__device__ __forceinline__ uint64_t make_desc(uint32_t addr, uint32_t lbo, uint32_t sbo) {
  return (uint64_t)((addr & 0x3FFFF) >> 4) | ((uint64_t)(lbo >> 4) << 16) | ((uint64_t)(sbo >> 4) << 32) | ((uint64_t)1 << 62);
}

__device__ __forceinline__ uint32_t desc_lo(uint32_t addr, uint32_t lbo) { return ((addr & 0x3FFFF) >> 4) | ((lbo >> 4) << 16); }
__device__ __forceinline__ uint64_t desc_at(uint32_t lo, uint32_t off) { return ((uint64_t)0x40000040u << 32) | (uint64_t)(lo + (off >> 4)); }

__device__ __forceinline__ void wgmma_ss_n64(float (&d)[32], uint64_t da, uint64_t db, int scale_d) {
  asm volatile("{\n.reg .pred p;\nsetp.ne.b32 p, %34, 0;\n"
    "wgmma.mma_async.sync.aligned.m64n64k16.f32.bf16.bf16 {%0, %1, %2, %3, %4, %5, %6, %7, %8, %9, %10, %11, %12, %13, %14, %15, %16, %17, %18, %19, %20, %21, %22, %23, %24, %25, %26, %27, %28, %29, %30, %31}, %32, %33, p, 1, 1, 1, 0;\n}\n"
    : "+f"(d[0]), "+f"(d[1]), "+f"(d[2]), "+f"(d[3]), "+f"(d[4]), "+f"(d[5]), "+f"(d[6]), "+f"(d[7]), "+f"(d[8]), "+f"(d[9]), "+f"(d[10]), "+f"(d[11]), "+f"(d[12]), "+f"(d[13]), "+f"(d[14]), "+f"(d[15]), "+f"(d[16]), "+f"(d[17]), "+f"(d[18]), "+f"(d[19]), "+f"(d[20]), "+f"(d[21]), "+f"(d[22]), "+f"(d[23]), "+f"(d[24]), "+f"(d[25]), "+f"(d[26]), "+f"(d[27]), "+f"(d[28]), "+f"(d[29]), "+f"(d[30]), "+f"(d[31])
    : "l"(da), "l"(db), "r"(scale_d));
}

__device__ __forceinline__ void wgmma_ss_n32(float (&d)[16], uint64_t da, uint64_t db, int scale_d) {
  asm volatile("{\n.reg .pred p;\nsetp.ne.b32 p, %18, 0;\n"
    "wgmma.mma_async.sync.aligned.m64n32k16.f32.bf16.bf16 {%0, %1, %2, %3, %4, %5, %6, %7, %8, %9, %10, %11, %12, %13, %14, %15}, %16, %17, p, 1, 1, 1, 0;\n}\n"
    : "+f"(d[0]), "+f"(d[1]), "+f"(d[2]), "+f"(d[3]), "+f"(d[4]), "+f"(d[5]), "+f"(d[6]), "+f"(d[7]), "+f"(d[8]), "+f"(d[9]), "+f"(d[10]), "+f"(d[11]), "+f"(d[12]), "+f"(d[13]), "+f"(d[14]), "+f"(d[15])
    : "l"(da), "l"(db), "r"(scale_d));
}

__device__ __forceinline__ void wgmma_ss_n8(float (&d)[4], uint64_t da, uint64_t db, int scale_d) {
  asm volatile("{\n.reg .pred p;\nsetp.ne.b32 p, %6, 0;\n"
    "wgmma.mma_async.sync.aligned.m64n8k16.f32.bf16.bf16 {%0, %1, %2, %3}, %4, %5, p, 1, 1, 1, 0;\n}\n"
    : "+f"(d[0]), "+f"(d[1]), "+f"(d[2]), "+f"(d[3])
    : "l"(da), "l"(db), "r"(scale_d));
}

__device__ __forceinline__ void wgmma_rs_n64(float (&d)[32], uint32_t a0, uint32_t a1, uint32_t a2, uint32_t a3, uint64_t db, int scale_d) {
  asm volatile("{\n.reg .pred p;\nsetp.ne.b32 p, %37, 0;\n"
    "wgmma.mma_async.sync.aligned.m64n64k16.f32.bf16.bf16 {%0, %1, %2, %3, %4, %5, %6, %7, %8, %9, %10, %11, %12, %13, %14, %15, %16, %17, %18, %19, %20, %21, %22, %23, %24, %25, %26, %27, %28, %29, %30, %31}, {%32, %33, %34, %35}, %36, p, 1, 1, 1;\n}\n"
    : "+f"(d[0]), "+f"(d[1]), "+f"(d[2]), "+f"(d[3]), "+f"(d[4]), "+f"(d[5]), "+f"(d[6]), "+f"(d[7]), "+f"(d[8]), "+f"(d[9]), "+f"(d[10]), "+f"(d[11]), "+f"(d[12]), "+f"(d[13]), "+f"(d[14]), "+f"(d[15]), "+f"(d[16]), "+f"(d[17]), "+f"(d[18]), "+f"(d[19]), "+f"(d[20]), "+f"(d[21]), "+f"(d[22]), "+f"(d[23]), "+f"(d[24]), "+f"(d[25]), "+f"(d[26]), "+f"(d[27]), "+f"(d[28]), "+f"(d[29]), "+f"(d[30]), "+f"(d[31])
    : "r"(a0), "r"(a1), "r"(a2), "r"(a3), "l"(db), "r"(scale_d));
}

__host__ __device__ constexpr int unit_slot(int u) {
  constexpr int t[36] = {4, 5, 6, 7, 8, 4, 5, 6, 0, 7, 8, 4,  1, 5, 6, 0, 2, 7, 8, 4, 3, 1, 5, 6,
                         0, 2, 7, 8,  4, 3, 1, 5, 6, 0, 2, 7};
  return t[u];
}
__host__ __device__ constexpr int unit_wait(int u) {
  constexpr int t[36] = {-1, -1, -1, -1, -1, 0, 1, 2, 2, 3, 4, 5,  5, 6, 7, 8, 8, 9, 10, 11, 11, 12, 13, 14,
                         15, 16, 17, 18,  19, 20, 21, 22, 23, 24, 25, 26};
  return t[u];
}

__device__ __forceinline__ uint32_t stage_off(int g, int j) {
  return g == 0 ? (j < 2 ? 8 * kSlot + j * 8192 : 10 * kSlot + (j - 2) * 8192)
                : (j < 2 ? 12 * kSlot + j * 8192 : (j == 2 ? 11 * kSlot + 8192 : 9 * kSlot));
}

struct Params {
  CUtensorMap x, w1, w2, wf, wg, wo, g, out64, out56;
  const void* xptr;
};

__device__ __forceinline__ void init_bar(uint32_t bars, int i) {
  const uint32_t a = bars + i * 8;
  const bool is_e = (i >= kBarE && i < kBarE + 27);
  mbar_init(a, is_e ? 8 : 1);
  if (!is_e) {
    uint32_t bytes = 16384;
    if (i == kBarFX) bytes = 8192;
    if (i == kBarFE) bytes = 8192;
    mbar_expect(a, bytes);
  }
}

__device__ __forceinline__ void store_pieces(const Params& P, uint32_t sb, uint32_t bars, int g, uint32_t cta, int b, int r0, int rvalid) {
  const int rl0 = cta * 16 + g * 8;
  if (rl0 >= rvalid) return;
  const CUtensorMap* omap = (rl0 + 8 <= rvalid) ? &P.out64 : &P.out56;
#pragma unroll
  for (int j = 0; j < 4; j++) {
    mbar_wait(bars + (kBarPR + g * 4 + j) * 8);
    if (elect_one()) {
      tma_store_3d(omap, sb + stage_off(g, j), 0, (b * kT2 + r0 + rl0) * 8, j);
      asm volatile("cp.async.bulk.commit_group;" ::: "memory");
    }
    __syncwarp();
    if (j == 0) TS(2, 12 + g);
    if (j == 3) TS(2, 14 + g);
  }
  if (elect_one()) asm volatile("cp.async.bulk.wait_group.read 0;" ::: "memory");
  __syncwarp();
  if (g == 1) { TS(2, 11); GT(1); TS_DUMP(2, 11, 12); GT_DUMP(1); }
  TS_DUMP(2, 12 + g, 13 + g); TS_DUMP(2, 14 + g, 15 + g);
}

__global__ void __cluster_dims__(2, 1, 1) __launch_bounds__(kThreads, 1)
rnnt_joint_kernel(const __grid_constant__ Params P) {
  extern __shared__ uint8_t smem_raw[];
  const uint32_t sb = (smem_u32(smem_raw) + 1023u) & ~1023u;
  const uint32_t bars = sb + kOffBar;
  const int warp = threadIdx.x >> 5, lane = threadIdx.x & 31;
  uint32_t cta;
  asm volatile("mov.u32 %0, %%cluster_ctarank;" : "=r"(cta));
  const uint32_t peer = cta ^ 1u;
  const int cl = blockIdx.x >> 1;
  const bool ge_cta = cl < 2;
  const int b = ge_cta ? cl : ((cl - 2) >> 5);
  const int r0 = ge_cta ? 32 * kR : ((cl - 2) & 31) * kR;
  const int rvalid = ge_cta ? kT2 - 32 * kR : kR;

  if (warp >= 8) {
    asm volatile("setmaxnreg.dec.sync.aligned.u32 40;");
    if (warp > 8) {
      if (elect_one()) {
#pragma unroll
        for (int i = 0; i < 5; i++) if (57 + (warp - 9) * 5 + i < kBarG) init_bar(bars, 57 + (warp - 9) * 5 + i);
#pragma unroll
        for (int i = 0; i < 5; i++) if (kBarRH + (warp - 9) * 5 + i < kBarGW) mbar_init(bars + (kBarRH + (warp - 9) * 5 + i) * 8, 4);
        if (warp == 10) asm volatile("st.shared.u32 [%0], 0;" ::"r"(sb + kOffZero) : "memory");
        if (warp == 11) { mbar_init(bars + kBarGW * 8, 8); mbar_init(bars + kBarFO * 8, 8); mbar_init(bars + kBarGE * 8, 1); mbar_expect(bars + kBarGE * 8, kGEBytes); }
        asm volatile("fence.mbarrier_init.release.cluster;" ::: "memory");
      }
      __syncwarp();
      asm volatile("barrier.cluster.arrive.relaxed.aligned;" ::: "memory");
      if (warp == 11 && lane < 9) asm volatile("prefetch.tensormap [%0];" ::"l"(reinterpret_cast<const CUtensorMap*>(&P) + lane) : "memory");
      __syncwarp();
      asm volatile("barrier.cluster.wait.aligned;" ::: "memory");
      if (warp == 10 && ge_cta) {
        mbar_wait(bars + kBarGW * 8);
        if (elect_one()) {
          __threadfence();
          asm volatile("red.release.gpu.global.add.u32 [%0], 1;" ::"l"(&g_ge_flag[b]) : "memory");
        }
        __syncwarp();
      }
      if (warp == 11) {
        if (elect_one()) {
          const unsigned int ticket = atomicAdd(&g_cta_count, 1u);
          const unsigned int want = (ticket / kNumCtas + 1u) * 2u;
          const long long t0 = clock64();
          unsigned int v;
          do {
            __nanosleep(200);
            asm volatile("ld.acquire.gpu.global.u32 %0, [%1];" : "=r"(v) : "l"(&g_ge_flag[b]) : "memory");
          } while ((int)(v - want) < 0 && clock64() - t0 < 4000000ll);
          asm volatile("fence.proxy.async;" ::: "memory");
          bulk_load(sb + kOffGE, reinterpret_cast<const char*>(g_ge) + b * kGEBytes, kGEBytes, bars + kBarGE * 8);
        }
        __syncwarp();
        return;
      }
      if (warp == 10) store_pieces(P, sb, bars, 1, cta, b, r0, rvalid);
      if (warp == 10) return;
#pragma unroll
      for (int g = 0; g < 2; g++) {
        mbar_wait(bars + (kBarRH + g) * 8);
        if (elect_one()) {
          const uint32_t src = sb + kSlotH * kSlot + (2 * cta + g) * 8192;
          dsmem_copy(mapa(src, peer), src, 8192, mapa(bars + kBarHX * 8, peer));
        }
        __syncwarp();
      }
#pragma unroll
      for (int g = 0; g < 2; g++) {
        mbar_wait(bars + (kBarRF + g) * 8);
        if (elect_one()) {
          const uint32_t src = sb + kSlotF * kSlot + (2 * cta + g) * 4096;
          dsmem_copy(mapa(src, peer), src, 4096, mapa(bars + kBarFX * 8, peer));
        }
        __syncwarp();
      }
#pragma unroll
      for (int g = 0; g < 2; g++) {
        mbar_wait(bars + (kBarRE + g) * 8);
        if (elect_one())
          dsmem_copy(mapa(sb + kSlotFE * kSlot + (2 * cta + g) * 4096, peer), sb + kSlotH * kSlot + g * 4096, 4096, mapa(bars + kBarFE * 8, peer));
        __syncwarp();
      }
      store_pieces(P, sb, bars, 0, cta, b, r0, rvalid);
      return;
    }
    TS(2, 0);
    GT(0);
    const int par = cta == 0 ? 1 : 0;
    const int q0 = cta == 0 ? 2 * r0 - 2 : 2 * r0 - 1;
    if (elect_one()) {
      mbar_init(bars + kBarX * 8, 1); mbar_expect(bars + kBarX * 8, 16384);
      mbar_init(bars + kBarW * 8, 1); mbar_expect(bars + kBarW * 8, 16384);
      fence_async_smem();
      tma_load_4d(sb, &P.x, bars + kBarX * 8, 0, 1, 2 * r0 - 2, b);
      tma_load_4d(sb + 8192, &P.x, bars + kBarX * 8, 0, 0, 2 * r0 - 1, b);
      tma_load_3d(sb + unit_slot(0) * kSlot, &P.w1, bars + kBarW * 8, 0, 0, 2 * cta);
      TS(2, 7);
#pragma unroll
      for (int i = 1; i < 9; i++) if (i != kBarW) { mbar_init(bars + i * 8, 1); mbar_expect(bars + i * 8, 16384); }
      if (ge_cta) { mbar_init(bars + kBarG * 8, 1); mbar_expect(bars + kBarG * 8, 4 * 16384 + 4096); mbar_init(bars + kBarP0 * 8, 8); }
      asm volatile("fence.mbarrier_init.release.cluster;" ::: "memory");
      fence_async_smem();
      TS(2, 8);
      if (ge_cta) {
        tma_load_3d(sb + kOffG, &P.g, bars + kBarG * 8, 0, b * 8, 0);
#pragma unroll
        for (int i = 0; i < 4; i++) tma_load_3d(sb + (9 + i) * kSlot, &P.wg, bars + kBarG * 8, 0, i * 64, 2 * cta);
      }
#pragma unroll
      for (int u = 1; u < 5; u++)
        tma_load_3d(sb + unit_slot(u) * kSlot, &P.w1, bars + (kBarW + u) * 8, 0, (u % 3) * 256 + (u / 3) * 64, 2 * cta);
      TS(2, 10);
    }
    __syncwarp();
    TS(2, 6);
    cluster_sync_relaxed();
    TS(2, 1);
    if (elect_one()) {
#pragma unroll
      for (int p = 1; p < XFIRST; p++)
        tma_load_4d_mc(sb + p * kSlot + cta * 8192, &P.x, bars + (kBarX + p) * 8, p * 64, par, q0, b, (uint16_t)3);
    }
    __syncwarp();
#pragma unroll
    for (int p = XFIRST; p < 4; p++) {
      if (XSTEP == 1 || ((p - XFIRST) & 1) == 0) mbar_wait(bars + (kBarX + p - XFIRST) * 8);
      if (ge_cta && p == 3) mbar_wait(bars + kBarP0 * 8);
      if (elect_one())
        tma_load_4d_mc(sb + p * kSlot + cta * 8192, &P.x, bars + (kBarX + p) * 8, p * 64, par, q0, b, (uint16_t)3);
      __syncwarp();
    }
#pragma unroll
    for (int u = 5; u < 36; u++) {
      if (unit_wait(u) != unit_wait(u - 1)) mbar_wait(bars + (kBarE + unit_wait(u)) * 8);
      if (WOGATE >= 1 && u == 28) mbar_wait(bars + kBarFX * 8);
      if (WOGATE >= 2 && u == 32) mbar_wait(bars + kBarFE * 8);
      if (elect_one()) {
        const uint32_t dst = sb + unit_slot(u) * kSlot, bar = bars + (kBarW + u) * 8;
        if (u < 12) tma_load_3d(dst, &P.w1, bar, 0, (u % 3) * 256 + (u / 3) * 64, 2 * cta);
        else if (u < 24) tma_load_3d(dst, &P.w2, bar, 0, ((u - 12) % 3) * 256 + ((2 * cta + (u - 12) / 3) & 3) * 64, 2 * cta);
        else if (u < 28) tma_load_3d(dst, &P.wf, bar, 0, ((2 * cta + (u - 24)) & 3) * 64, 2 * cta);
        else tma_load_3d(dst, &P.wo, bar, 0, ((2 * cta + (u - 28)) & 3) * 64, ((u - 28) >> 2) * 2);
      }
      __syncwarp();
      if (u == 11) TS(2, 2);
      if (u == 23) TS(2, 3);
      if (u == 27) TS(2, 4);
      if (u == 35) TS(2, 5);
    }
    TS_DUMP(2, 0, 11); GT_DUMP(0);
  } else {
    asm volatile("setmaxnreg.inc.sync.aligned.u32 232;");
    const int wg = warp >> 2, w = warp & 3;
    const int gq = lane >> 2, q = lane & 3;
    const uint32_t panel = 2 * cta + wg;
    const int ch = panel * 64 + w * 16 + gq;
    const uint32_t dA = desc_lo(sb + wg * 8192, 8192);
    const uint32_t dB = desc_lo(sb, 16);
    const uint32_t dBo = desc_lo(sb + cta * 2 * 8192, 16), dBp = desc_lo(sb + (cta ^ 1) * 2 * 8192, 16);
    const uint32_t dFo = desc_lo(sb + cta * 2 * 4096, 16), dFp = desc_lo(sb + (cta ^ 1) * 2 * 4096, 16);
    if (elect_one()) {
#pragma unroll
      for (int i = 0; i < 6; i++) init_bar(bars, 9 + warp * 6 + i);
      asm volatile("fence.mbarrier_init.release.cluster;" ::: "memory");
    }
    __syncwarp();
    cluster_sync_relaxed();
    if (w == 0) TS(wg, 0);

    if (ge_cta) {
      float ga[4];
      mbar_wait(bars + kBarG * 8);
      wg_fence();
#pragma unroll
      for (int i = 0; i < 4; i++) {
#pragma unroll
        for (int s = 0; s < 4; s++)
          wgmma_ss_n8(ga, desc_at(dA, (9 + i) * kSlot + s * 2048), desc_at(dB, kOffG + i * 1024 + s * 32), (i | s) != 0);
      }
      wg_commit();
      wg_wait<0>();
      if (lane == 0) mbar_arrive(bars + kBarP0 * 8);
      float* gp = g_ge + b * (kGEBytes / 4) + ((ch & 7) >> 1) * (kGEPitch / 4) + (ch >> 4) * 4 + (ch & 1);
      gp[(2 * q) * 4 * (kGEPitch / 4)] = ga[0];
      gp[(2 * q + 1) * 4 * (kGEPitch / 4)] = ga[1];
      gp[(2 * q) * 4 * (kGEPitch / 4) + 2] = ga[2];
      gp[(2 * q + 1) * 4 * (kGEPitch / 4) + 2] = ga[3];
      __syncwarp();
      if (lane == 0) mbar_arrive(bars + kBarGW * 8);
    }

    {
      float acc[32];
#pragma unroll
      for (int u = 0; u < 12; u++) {
        const int p = u / 3, tap = u % 3;
        if (SKEW1 > 0 && u == 12 - SKEW1) bar_sync_pred5(wg == 1);
        if (tap == 0) mbar_wait(bars + (kBarX + p) * 8);
        mbar_wait(bars + (kBarW + u) * 8);
        if (u == 0 && w == 0) TS(wg, 1);
        wg_fence();
#pragma unroll
        for (int s = 0; s < 4; s++)
          wgmma_ss_n64(acc, desc_at(dA, unit_slot(u) * kSlot + s * 2048),
                       desc_at(dB, p * kSlot + (tap == 1 ? 8192 : (tap == 2 ? 128 : 0)) + s * 32), (u | s) != 0);
        wg_commit();
        if (SKEW1 > 0 && u == 11) bar_arrive_pred5(wg == 0);
        if (u > 0) {
          wg_wait<1>();
          if (lane == 0) mbar_arrive(bars + (kBarE + u - 1) * 8);
        }
      }
      wg_wait<0>();
      if (lane == 0) mbar_arrive(bars + (kBarE + 11) * 8);
      if (w == 0) TS(wg, 2);
      const uint32_t hp = sb + kSlotH * kSlot + panel * 8192;
      const int mi = lane >> 3, l8 = lane & 7;
#pragma unroll
      for (int jb = 0; jb < 8; jb += 2) {
        uint32_t r[4];
#pragma unroll
        for (int t = 0; t < 2; t++) {
          r[2 * t + 0] = pack_bf16(gelu_tanh(acc[4 * (jb + t) + 0]), gelu_tanh(acc[4 * (jb + t) + 1]));
          r[2 * t + 1] = pack_bf16(gelu_tanh(acc[4 * (jb + t) + 2]), gelu_tanh(acc[4 * (jb + t) + 3]));
        }
        const int n = 8 * (jb + (mi >> 1)) + l8;
        const int row = n >> 1, chunk = 2 * w + (mi & 1);
        stsm_x4_trans(hp + (n & 1) * 4096 + row * 128 + ((chunk ^ (row & 7)) << 4), r[0], r[1], r[2], r[3]);
      }
      __syncwarp();
      if (w == 0) TS(wg, 15);
      fence_async_smem();
      __syncwarp();
      if (lane == 0) mbar_arrive(bars + (kBarRH + wg) * 8);
      if (w == 0) TS(wg, 3);
    }
    {
      float acc[16];
#pragma unroll
      for (int v = 0; v < 12; v++) {
        const int i = v / 3, tap = v % 3;
        if (SKEW2 > 0 && v == 12 - SKEW2) bar_sync_pred6(wg == 1);
        if (v == 0) mbar_wait(bars + kBarRH * 8);
        if (v == 3) mbar_wait(bars + (kBarRH + 1) * 8);
        if (v == 6) { mbar_wait_cluster(bars + kBarHX * 8); if (w == 0) TS(wg, 4); }
        mbar_wait(bars + (kBarW + 12 + v) * 8);
        wg_fence();
#pragma unroll
        for (int s = 0; s < 4; s++)
          wgmma_ss_n32(acc, desc_at(dA, unit_slot(12 + v) * kSlot + s * 2048),
                       desc_at(i < 2 ? dBo : dBp, kSlotH * kSlot + (i & 1) * 8192 + (tap == 1 ? 4096 : (tap == 2 ? 128 : 0)) + s * 32), (v | s) != 0);
        wg_commit();
        if (SKEW2 > 0 && v == 11) bar_arrive_pred6(wg == 0);
        if (v > 0) {
          wg_wait<1>();
          if (lane == 0) mbar_arrive(bars + (kBarE + 12 + v - 1) * 8);
        }
      }
      wg_wait<0>();
      if (lane == 0) mbar_arrive(bars + (kBarE + 23) * 8);
      if (w == 0) TS(wg, 5);
      const uint32_t fp = sb + kSlotF * kSlot + panel * 4096;
      const int mi = lane >> 3, l8 = lane & 7;
#pragma unroll
      for (int jb = 0; jb < 4; jb += 2) {
        uint32_t r[4];
#pragma unroll
        for (int t = 0; t < 2; t++) {
          r[2 * t + 0] = pack_bf16(gelu_tanh(acc[4 * (jb + t) + 0]), gelu_tanh(acc[4 * (jb + t) + 1]));
          r[2 * t + 1] = pack_bf16(gelu_tanh(acc[4 * (jb + t) + 2]), gelu_tanh(acc[4 * (jb + t) + 3]));
        }
        const int n = 8 * (jb + (mi >> 1)) + l8;
        const int chunk = 2 * w + (mi & 1);
        stsm_x4_trans(fp + n * 128 + ((chunk ^ (n & 7)) << 4), r[0], r[1], r[2], r[3]);
      }
      fence_async_smem();
      __syncwarp();
      if (lane == 0) mbar_arrive(bars + (kBarRF + wg) * 8);
      if (w == 0) TS(wg, 6);
    }
    {
      float acc[16];
#pragma unroll
      for (int i = 0; i < 4; i++) {
        if (i < 2) mbar_wait(bars + (kBarRF + i) * 8);
        if (i == 2) { mbar_wait_cluster(bars + kBarFX * 8); if (w == 0) TS(wg, 7); }
        mbar_wait(bars + (kBarW + 24 + i) * 8);
        wg_fence();
#pragma unroll
        for (int s = 0; s < 4; s++)
          wgmma_ss_n32(acc, desc_at(dA, unit_slot(24 + i) * kSlot + s * 2048),
                       desc_at(i < 2 ? dFo : dFp, kSlotF * kSlot + (i & 1) * 4096 + s * 32), (i | s) != 0);
        wg_commit();
        if (i > 0) {
          wg_wait<1>();
          if (lane == 0) mbar_arrive(bars + (kBarE + 24 + i - 1) * 8);
        }
      }
      wg_wait<0>();
      if (w == 0) TS(wg, 8);
      const uint32_t qk = gq >> 1;
      const uint32_t off0 = qk * 128 + (((2 * w) ^ (2 * qk)) << 4) + (gq & 1) * 8;
      const uint32_t off1 = qk * 128 + (((2 * w + 1) ^ (2 * qk)) << 4) + (gq & 1) * 8;
      const uint32_t own = sb + kSlotFE * kSlot + panel * 4096;
      const uint32_t stg = sb + kSlotH * kSlot + wg * 4096;
#pragma unroll
      for (int jb = 0; jb < 4; jb++) {
        const uint32_t base = (((uint32_t)(jb >> 1) == cta) ? own : stg) + (4 * (jb & 1) + q) * 512;
        sts64(base + off0, acc[4 * jb + 0], acc[4 * jb + 1]);
        sts64(base + off1, acc[4 * jb + 2], acc[4 * jb + 3]);
      }
      fence_async_smem();
      __syncwarp();
      if (lane == 0) { mbar_arrive(bars + (kBarRE + wg) * 8); mbar_arrive(bars + kBarFO * 8); }
      if (w == 0) TS(wg, 9);
    }
    const int rl0 = cta * 16 + wg * 8;
    mbar_wait(bars + kBarFO * 8);
    mbar_wait(bars + kBarGE * 8);
    if (rl0 < rvalid) {
      if (w == 0) TS(wg, 10);
      const uint32_t fe_row = sb + kSlotFE * kSlot + ((4 * wg + w) * 4 + q) * 128;
      const uint32_t fe_h[2] = {fe_row + cta * 8192, fe_row + (cta ^ 1) * 8192};
      const uint32_t ge_h[2] = {sb + kOffGE + lane * kGEPitch + cta * 128, sb + kOffGE + lane * kGEPitch + (cta ^ 1) * 128};
      const int mi = lane >> 3, l8 = lane & 7;
      const uint32_t st = sb + (16 * w + (mi & 1) * 8 + l8) * 128;
      uint32_t A[64];
      float acc[2][32];
      if (wg == 0) {
        constexpr int PD = 3;
        float4 fa[PD], fb[PD], gg[PD];
#pragma unroll
        for (int kk = 0; kk < 16 + PD; kk++) {
          if (kk >= PD) {
            const int k = kk - PD, sl = k % PD;
            A[4 * k + 0] = tanh2_pack(fa[sl].x + gg[sl].x, fa[sl].z + gg[sl].y);
            A[4 * k + 1] = tanh2_pack(fa[sl].y + gg[sl].x, fa[sl].w + gg[sl].y);
            A[4 * k + 2] = tanh2_pack(fb[sl].x + gg[sl].z, fb[sl].z + gg[sl].w);
            A[4 * k + 3] = tanh2_pack(fb[sl].y + gg[sl].z, fb[sl].w + gg[sl].w);
          }
          if (kk < 16) {
            const int sl = kk % PD;
            if (kk == 8) {
              mbar_wait_cluster(bars + kBarFE * 8);
            }
            fa[sl] = lds128(fe_h[kk >> 3] + ((kk >> 2) & 1) * 4096 + ((((kk & 3) * 2) ^ (2 * q)) << 4));
            fb[sl] = lds128(fe_h[kk >> 3] + ((kk >> 2) & 1) * 4096 + ((((kk & 3) * 2 + 1) ^ (2 * q)) << 4));
            gg[sl] = lds128(ge_h[kk >> 3] + (kk & 7) * 16);
          }
        }
      } else {
        float sm_[128];
#pragma unroll
        for (int kk = 0; kk < 16; kk++) {
          if (kk == 8) mbar_wait_cluster(bars + kBarFE * 8);
          const float4 fa = lds128(fe_h[kk >> 3] + ((kk >> 2) & 1) * 4096 + ((((kk & 3) * 2) ^ (2 * q)) << 4));
          const float4 fb = lds128(fe_h[kk >> 3] + ((kk >> 2) & 1) * 4096 + ((((kk & 3) * 2 + 1) ^ (2 * q)) << 4));
          const float4 gg = lds128(ge_h[kk >> 3] + (kk & 7) * 16);
          sm_[8 * kk + 0] = fa.x + gg.x; sm_[8 * kk + 1] = fa.z + gg.y; sm_[8 * kk + 2] = fa.y + gg.x; sm_[8 * kk + 3] = fa.w + gg.y;
          sm_[8 * kk + 4] = fb.x + gg.z; sm_[8 * kk + 5] = fb.z + gg.w; sm_[8 * kk + 6] = fb.y + gg.z; sm_[8 * kk + 7] = fb.w + gg.w;
        }
        asm volatile("bar.sync 4, 256;" ::: "memory");
        float z;
        asm volatile("ld.shared.f32 %0, [%1];" : "=f"(z) : "r"(sb + kOffZero) : "memory");
#pragma unroll
        for (int i = 0; i < 64; i++) A[i] = tanh2_pack(sm_[2 * i] + z, sm_[2 * i + 1] + z);
      }
      asm volatile("barrier.cluster.arrive.relaxed.aligned;" ::: "memory");
#pragma unroll
      for (int kk = 0; kk < 16; kk++) {
        if ((kk & 3) == 0) { mbar_wait(bars + (kBarW + 28 + (kk >> 2)) * 8); wg_fence(); }
        wgmma_rs_n64(acc[0], A[4 * kk], A[4 * kk + 1], A[4 * kk + 2], A[4 * kk + 3],
                     desc_at(dB, unit_slot(28 + (kk >> 2)) * kSlot + (kk & 3) * 2048), kk != 0);
        if (kk == ARRK) bar_arrive_pred(wg == 0);
      }
      wg_commit();
      wg_wait<0>();
#pragma unroll
      for (int jb = 0; jb < 8; jb += 2) {
        const uint32_t r0_ = pack_bf16(acc[0][4 * jb + 0], acc[0][4 * jb + 1]), r1_ = pack_bf16(acc[0][4 * jb + 2], acc[0][4 * jb + 3]);
        const uint32_t r2_ = pack_bf16(acc[0][4 * jb + 4], acc[0][4 * jb + 5]), r3_ = pack_bf16(acc[0][4 * jb + 6], acc[0][4 * jb + 7]);
        stsm_x4(st + (wg ? stage_off(1, 0) : stage_off(0, 0)) + (((jb + (mi >> 1)) ^ l8) << 4), r0_, r1_, r2_, r3_);
      }
      fence_async_smem();
      __syncwarp();
      mbar_arrive_pred(bars + (kBarPR + wg * 4) * 8, lane == 0);
      if (w == 0) TS(wg, 11);
#pragma unroll
      for (int j = 0; j < 4; j++) {
        const int jn = j + 1;
        if (jn == 2) {
#pragma unroll
          for (int i = 0; i < 4; i++) mbar_wait(bars + (kBarW + 32 + i) * 8);
        }
        if (j < 3) wg_fence();
        const uint32_t stj = st + (wg ? stage_off(1, j) : stage_off(0, j));
#pragma unroll
        for (int kk = 0; kk < 16; kk++) {
          if (j < 3)
            wgmma_rs_n64(acc[jn & 1], A[4 * kk], A[4 * kk + 1], A[4 * kk + 2], A[4 * kk + 3],
                         desc_at(dB, unit_slot(28 + (jn >> 1) * 4 + (kk >> 2)) * kSlot + (jn & 1) * 8192 + (kk & 3) * 2048), kk != 0);
          if (kk == 1 && j > 0) {
            if (j < 3) { wg_commit(); wg_wait<1>(); } else { wg_wait<0>(); }
          }
          if (j > 0 && kk >= 2 && kk < 10 && (kk & 1) == 0) {
            const int jb = kk - 2;
            const uint32_t r0_ = pack_bf16(acc[j & 1][4 * jb + 0], acc[j & 1][4 * jb + 1]), r1_ = pack_bf16(acc[j & 1][4 * jb + 2], acc[j & 1][4 * jb + 3]);
            const uint32_t r2_ = pack_bf16(acc[j & 1][4 * jb + 4], acc[j & 1][4 * jb + 5]), r3_ = pack_bf16(acc[j & 1][4 * jb + 6], acc[j & 1][4 * jb + 7]);
            stsm_x4(stj + (((jb + (mi >> 1)) ^ l8) << 4), r0_, r1_, r2_, r3_);
          }
          if (j > 0 && kk == 9) {
            fence_async_smem();
            __syncwarp();
            mbar_arrive_pred(bars + (kBarPR + wg * 4 + j) * 8, lane == 0);
          }
        }
        if (j < 3) wg_commit();
        if (j == 0 && w == 0) TS(wg, 12);
        if (j == 2 && w == 0) TS(wg, 13);
      }
      if (w == 0) TS(wg, 14);
    } else {
      if (wg == 0) asm volatile("bar.arrive 4, 256;" ::: "memory");
      if (wg == 1) asm volatile("bar.sync 4, 256;" ::: "memory");
      mbar_wait_cluster(bars + kBarFE * 8);
      asm volatile("barrier.cluster.arrive.relaxed.aligned;" ::: "memory");
    }
    asm volatile("barrier.cluster.wait.aligned;" ::: "memory");
    if (w == 0) TS_DUMP(wg, 0, 16);
  }
}

typedef CUresult (*EncodeFn)(CUtensorMap*, CUtensorMapDataType, cuuint32_t, void*, const cuuint64_t*, const cuuint64_t*,
                             const cuuint32_t*, const cuuint32_t*, CUtensorMapInterleave, CUtensorMapSwizzle,
                             CUtensorMapL2promotion, CUtensorMapFloatOOBfill);

void make_map3(EncodeFn enc, CUtensorMap* tm, const void* ptr, uint64_t rows, uint32_t box_rows, uint32_t box_panels) {
  cuuint64_t gd[3] = {64, rows, 4};
  cuuint64_t gs[2] = {512, 128};
  cuuint32_t bd[3] = {64, box_rows, box_panels};
  cuuint32_t es[3] = {1, 1, 1};
  enc(tm, CU_TENSOR_MAP_DATA_TYPE_BFLOAT16, 3, const_cast<void*>(ptr), gd, gs, bd, es, CU_TENSOR_MAP_INTERLEAVE_NONE,
      CU_TENSOR_MAP_SWIZZLE_128B, CU_TENSOR_MAP_L2_PROMOTION_L2_256B, CU_TENSOR_MAP_FLOAT_OOB_FILL_NONE);
}

}

extern "C" void kernel_launch(void* const* d_in, const int* in_sizes, int n_in, void* d_out, int out_size) {
  static EncodeFn enc = nullptr;
  if (!enc) {
    cudaDriverEntryPointQueryResult qr;
    cudaGetDriverEntryPoint("cuTensorMapEncodeTiled", (void**)&enc, cudaEnableDefault, &qr);
    cudaFuncSetAttribute(rnnt_joint_kernel, cudaFuncAttributeMaxDynamicSharedMemorySize, kSmemBytes);
  }
  Params P;
  {
    cuuint64_t gd[4] = {256, 2, 2000, 2};
    cuuint64_t gs[3] = {512, 1024, 4000ull * 512};
    cuuint32_t bd[4] = {64, 1, 64, 1};
    cuuint32_t es[4] = {1, 1, 1, 1};
    enc(&P.x, CU_TENSOR_MAP_DATA_TYPE_BFLOAT16, 4, d_in[0], gd, gs, bd, es, CU_TENSOR_MAP_INTERLEAVE_NONE,
        CU_TENSOR_MAP_SWIZZLE_128B, XPROMO, CU_TENSOR_MAP_FLOAT_OOB_FILL_NONE);
  }
  P.xptr = d_in[0];
  make_map3(enc, &P.w1, d_in[1], 768, 64, 2);
  make_map3(enc, &P.w2, d_in[2], 768, 64, 2);
  make_map3(enc, &P.g, d_in[3], 16, 8, 4);
  make_map3(enc, &P.wf, d_in[4], 256, 64, 2);
  make_map3(enc, &P.wg, d_in[5], 256, 64, 2);
  make_map3(enc, &P.wo, d_in[6], 256, 64, 2);
  make_map3(enc, &P.out64, d_out, 16000, 64, 1);
  make_map3(enc, &P.out56, d_out, 16000, 56, 1);
  rnnt_joint_kernel<<<kNumCtas, kThreads, kSmemBytes>>>(P);
}
```

```cpp
#include <cuda_runtime.h>
#include <cuda_bf16.h>
#include <cuda.h>
#include <stdint.h>

#define ARRK 3
#define XBULK 0
#define SKEW1 2
#define SKEW2 2
#define TSPLIT 0
#define WOGATE 1
#define XPREF 1
#define XFIRST 3
#define XSTEP 1
#define XPROMO CU_TENSOR_MAP_L2_PROMOTION_L2_128B
namespace {

constexpr int kT2 = 1000;
constexpr int kR = 31;
constexpr int kNumCtas = 132;
constexpr int kThreads = 384;
constexpr int kSlot = 16384;

constexpr int kSlotFE = 9, kSlotF = 10, kSlotH = 11;
constexpr int kOffG = 13 * kSlot;
constexpr int kOffGE = kOffG + 4096;
constexpr int kGEPitch = 272;
constexpr int kGEBytes = 32 * kGEPitch;
constexpr int kOffBar = kOffGE + kGEBytes;
constexpr int kBarX = 0;
constexpr int kBarW = 4;
constexpr int kBarE = 40;
constexpr int kBarHX = 67, kBarFX = 68, kBarFE = 69, kBarG = 70, kBarP0 = 71;
constexpr int kBarRH = 72, kBarRF = 74, kBarRE = 76;
constexpr int kBarPR = 78;
constexpr int kBarGW = 86;
constexpr int kBarFO = 87;
constexpr int kBarGE = 88;
constexpr int kNumBars = 89;
constexpr int kSmemBytes = kOffBar + kNumBars * 8 + 1024;

__device__ __align__(128) float g_ge[2 * kGEBytes / 4];
__device__ unsigned int g_ge_flag[2];
__device__ unsigned int g_cta_count;

#define TS(slot_, idx_) do {} while (0)
#define GT(idx_) do {} while (0)
#define TS_DUMP(slot_, lo_, hi_) do {} while (0)
#define GT_DUMP(idx_) do {} while (0)

__device__ __forceinline__ uint32_t smem_u32(const void* p) { return (uint32_t)__cvta_generic_to_shared(p); }
__device__ __forceinline__ void mbar_init(uint32_t a, uint32_t c) { asm volatile("mbarrier.init.shared.b64 [%0], %1;" ::"r"(a), "r"(c) : "memory"); }
__device__ __forceinline__ void mbar_expect(uint32_t a, uint32_t b) { asm volatile("mbarrier.arrive.expect_tx.shared.b64 _, [%0], %1;" ::"r"(a), "r"(b) : "memory"); }
__device__ __forceinline__ void mbar_arrive(uint32_t a) { asm volatile("mbarrier.arrive.shared.b64 _, [%0];" ::"r"(a) : "memory"); }
__device__ __forceinline__ void mbar_arrive_pred(uint32_t a, bool p) {
  asm volatile("{\n.reg .pred q;\nsetp.ne.u32 q, %1, 0;\n@q mbarrier.arrive.shared.b64 _, [%0];\n}\n" ::"r"(a), "r"((uint32_t)p) : "memory");
}
__device__ __forceinline__ void bar_arrive_pred(bool p) {
  asm volatile("{\n.reg .pred q;\nsetp.ne.u32 q, %0, 0;\n@q bar.arrive 4, 256;\n}\n" ::"r"((uint32_t)p) : "memory");
}
#define DEF_NAMED(ID) \
__device__ __forceinline__ void bar_arrive_pred##ID(bool p) { asm volatile("{\n.reg .pred q;\nsetp.ne.u32 q, %0, 0;\n@q bar.arrive " #ID ", 256;\n}\n" ::"r"((uint32_t)p) : "memory"); } \
__device__ __forceinline__ void bar_sync_pred##ID(bool p) { asm volatile("{\n.reg .pred q;\nsetp.ne.u32 q, %0, 0;\n@q bar.sync " #ID ", 256;\n}\n" ::"r"((uint32_t)p) : "memory"); }
DEF_NAMED(4)
DEF_NAMED(5)
DEF_NAMED(6)
__device__ __forceinline__ bool mbar_try(uint32_t a) {
  uint32_t ok;
  asm volatile("{\n.reg .pred p;\nmbarrier.try_wait.parity.shared.b64 p, [%1], 0;\nselp.u32 %0, 1, 0, p;\n}\n" : "=r"(ok) : "r"(a) : "memory");
  return ok != 0;
}
__device__ __forceinline__ bool mbar_test(uint32_t a) {
  uint32_t ok;
  asm volatile("{\n.reg .pred p;\nmbarrier.test_wait.parity.shared.b64 p, [%1], 0;\nselp.u32 %0, 1, 0, p;\n}\n" : "=r"(ok) : "r"(a) : "memory");
  return ok != 0;
}
__device__ __forceinline__ bool mbar_try_cluster(uint32_t a) {
  uint32_t ok;
  asm volatile("{\n.reg .pred p;\nmbarrier.try_wait.parity.acquire.cluster.shared.b64 p, [%1], 0;\nselp.u32 %0, 1, 0, p;\n}\n" : "=r"(ok) : "r"(a) : "memory");
  return ok != 0;
}
__device__ __forceinline__ void mbar_wait_slow(uint32_t a) {
  const long long t0 = clock64();
  while (!mbar_try(a)) { if (clock64() - t0 > 4000000ll) break; }
}
__device__ __forceinline__ void mbar_wait_cluster_slow(uint32_t a) {
  const long long t0 = clock64();
  while (!mbar_try_cluster(a)) { if (clock64() - t0 > 4000000ll) break; }
}
__device__ __forceinline__ void mbar_wait(uint32_t a) { if (!mbar_try(a)) mbar_wait_slow(a); }
__device__ __forceinline__ void mbar_wait_cluster(uint32_t a) { if (!mbar_try_cluster(a)) mbar_wait_cluster_slow(a); }
__device__ __forceinline__ uint32_t mapa(uint32_t a, uint32_t r) { uint32_t d; asm volatile("mapa.shared::cluster.u32 %0, %1, %2;" : "=r"(d) : "r"(a), "r"(r)); return d; }
__device__ __forceinline__ bool elect_one() { uint32_t p; asm volatile("{\n.reg .pred P;\nelect.sync _|P, 0xffffffff;\nselp.u32 %0, 1, 0, P;\n}\n" : "=r"(p)); return p != 0; }
__device__ __forceinline__ void fence_async_smem() { asm volatile("fence.proxy.async.shared::cta;" ::: "memory"); }
__device__ __forceinline__ void bar_consumers() { asm volatile("bar.sync 1, 256;" ::: "memory"); }
__device__ __forceinline__ void bar_wg(int wg) { asm volatile("bar.sync %0, 128;" ::"r"(2 + wg) : "memory"); }
__device__ __forceinline__ void cluster_sync_relaxed() { asm volatile("barrier.cluster.arrive.relaxed.aligned;\nbarrier.cluster.wait.aligned;" ::: "memory"); }
__device__ __forceinline__ void wg_fence() { asm volatile("wgmma.fence.sync.aligned;" ::: "memory"); }
__device__ __forceinline__ void wg_commit() { asm volatile("wgmma.commit_group.sync.aligned;" ::: "memory"); }
template <int N> __device__ __forceinline__ void wg_wait() { asm volatile("wgmma.wait_group.sync.aligned %0;" ::"n"(N) : "memory"); }

__device__ __forceinline__ void tma_load_3d(uint32_t dst, const CUtensorMap* tm, uint32_t bar, int c0, int c1, int c2) {
  asm volatile("cp.async.bulk.tensor.3d.shared::cluster.global.mbarrier::complete_tx::bytes [%0], [%1, {%3, %4, %5}], [%2];"
               ::"r"(dst), "l"(tm), "r"(bar), "r"(c0), "r"(c1), "r"(c2) : "memory");
}
__device__ __forceinline__ void tma_load_4d(uint32_t dst, const CUtensorMap* tm, uint32_t bar, int c0, int c1, int c2, int c3) {
  asm volatile("cp.async.bulk.tensor.4d.shared::cluster.global.mbarrier::complete_tx::bytes [%0], [%1, {%3, %4, %5, %6}], [%2];"
               ::"r"(dst), "l"(tm), "r"(bar), "r"(c0), "r"(c1), "r"(c2), "r"(c3) : "memory");
}
__device__ __forceinline__ void tma_load_4d_mc(uint32_t dst, const CUtensorMap* tm, uint32_t bar, int c0, int c1, int c2, int c3, uint16_t mask) {
  asm volatile("cp.async.bulk.tensor.4d.shared::cluster.global.mbarrier::complete_tx::bytes.multicast::cluster [%0], [%1, {%3, %4, %5, %6}], [%2], %7;"
               ::"r"(dst), "l"(tm), "r"(bar), "r"(c0), "r"(c1), "r"(c2), "r"(c3), "h"(mask) : "memory");
}
__device__ __forceinline__ void tma_store_3d(const CUtensorMap* tm, uint32_t src, int c0, int c1, int c2) {
  asm volatile("cp.async.bulk.tensor.3d.global.shared::cta.bulk_group [%0, {%2, %3, %4}], [%1];"
               ::"l"(tm), "r"(src), "r"(c0), "r"(c1), "r"(c2) : "memory");
}
__device__ __forceinline__ void bulk_load(uint32_t dst, const void* src, uint32_t bytes, uint32_t bar) {
  asm volatile("cp.async.bulk.shared::cluster.global.mbarrier::complete_tx::bytes [%0], [%1], %2, [%3];"
               ::"r"(dst), "l"(src), "r"(bytes), "r"(bar) : "memory");
}
__device__ __forceinline__ void dsmem_copy(uint32_t dst_remote, uint32_t src, uint32_t bytes, uint32_t bar_remote) {
  asm volatile("cp.async.bulk.shared::cluster.shared::cta.mbarrier::complete_tx::bytes [%0], [%1], %2, [%3];"
               ::"r"(dst_remote), "r"(src), "r"(bytes), "r"(bar_remote) : "memory");
}
__device__ __forceinline__ void stsm_x4_trans(uint32_t addr, uint32_t r0, uint32_t r1, uint32_t r2, uint32_t r3) {
  asm volatile("stmatrix.sync.aligned.m8n8.x4.trans.shared.b16 [%0], {%1, %2, %3, %4};" ::"r"(addr), "r"(r0), "r"(r1), "r"(r2), "r"(r3) : "memory");
}
__device__ __forceinline__ void stsm_x4(uint32_t addr, uint32_t r0, uint32_t r1, uint32_t r2, uint32_t r3) {
  asm volatile("stmatrix.sync.aligned.m8n8.x4.shared.b16 [%0], {%1, %2, %3, %4};" ::"r"(addr), "r"(r0), "r"(r1), "r"(r2), "r"(r3) : "memory");
}
__device__ __forceinline__ float2 lds64(uint32_t a) { float2 v; asm volatile("ld.shared.v2.f32 {%0, %1}, [%2];" : "=f"(v.x), "=f"(v.y) : "r"(a) : "memory"); return v; }
__device__ __forceinline__ float4 lds128(uint32_t a) { float4 v; asm volatile("ld.shared.v4.f32 {%0, %1, %2, %3}, [%4];" : "=f"(v.x), "=f"(v.y), "=f"(v.z), "=f"(v.w) : "r"(a) : "memory"); return v; }
__device__ __forceinline__ void sts64(uint32_t a, float x, float y) { asm volatile("st.shared.v2.f32 [%0], {%1, %2};" ::"r"(a), "f"(x), "f"(y) : "memory"); }
__device__ __forceinline__ float tanh_fast(float x) { float y; asm("tanh.approx.f32 %0, %1;" : "=f"(y) : "f"(x)); return y; }
__device__ __forceinline__ uint32_t tanh2_pack(float lo, float hi) {
  uint32_t r;
  asm volatile("{\n.reg .f32 a, b;\ntanh.approx.f32 a, %1;\ntanh.approx.f32 b, %2;\ncvt.rn.bf16x2.f32 %0, b, a;\n}\n" : "=r"(r) : "f"(lo), "f"(hi));
  return r;
}
__device__ __forceinline__ uint32_t pack_bf16(float lo, float hi) { uint32_t r; asm("cvt.rn.bf16x2.f32 %0, %1, %2;" : "=r"(r) : "f"(hi), "f"(lo)); return r; }
__device__ __forceinline__ float gelu_tanh(float x) {
  const float k0 = 0.7978845608028654f, k1 = 0.7978845608028654f * 0.044715f;
  float u = x * fmaf(x * x, k1, k0);
  float hx = 0.5f * x;
  return fmaf(hx, tanh_fast(u), hx);
}
__device__ __forceinline__ uint64_t make_desc(uint32_t addr, uint32_t lbo, uint32_t sbo) {
  return (uint64_t)((addr & 0x3FFFF) >> 4) | ((uint64_t)(lbo >> 4) << 16) | ((uint64_t)(sbo >> 4) << 32) | ((uint64_t)1 << 62);
}

__device__ __forceinline__ uint32_t desc_lo(uint32_t addr, uint32_t lbo) { return ((addr & 0x3FFFF) >> 4) | ((lbo >> 4) << 16); }
__device__ __forceinline__ uint64_t desc_at(uint32_t lo, uint32_t off) { return ((uint64_t)0x40000040u << 32) | (uint64_t)(lo + (off >> 4)); }

__device__ __forceinline__ void wgmma_ss_n64(float (&d)[32], uint64_t da, uint64_t db, int scale_d) {
  asm volatile("{\n.reg .pred p;\nsetp.ne.b32 p, %34, 0;\n"
    "wgmma.mma_async.sync.aligned.m64n64k16.f32.bf16.bf16 {%0, %1, %2, %3, %4, %5, %6, %7, %8, %9, %10, %11, %12, %13, %14, %15, %16, %17, %18, %19, %20, %21, %22, %23, %24, %25, %26, %27, %28, %29, %30, %31}, %32, %33, p, 1, 1, 1, 0;\n}\n"
    : "+f"(d[0]), "+f"(d[1]), "+f"(d[2]), "+f"(d[3]), "+f"(d[4]), "+f"(d[5]), "+f"(d[6]), "+f"(d[7]), "+f"(d[8]), "+f"(d[9]), "+f"(d[10]), "+f"(d[11]), "+f"(d[12]), "+f"(d[13]), "+f"(d[14]), "+f"(d[15]), "+f"(d[16]), "+f"(d[17]), "+f"(d[18]), "+f"(d[19]), "+f"(d[20]), "+f"(d[21]), "+f"(d[22]), "+f"(d[23]), "+f"(d[24]), "+f"(d[25]), "+f"(d[26]), "+f"(d[27]), "+f"(d[28]), "+f"(d[29]), "+f"(d[30]), "+f"(d[31])
    : "l"(da), "l"(db), "r"(scale_d));
}

__device__ __forceinline__ void wgmma_ss_n32(float (&d)[16], uint64_t da, uint64_t db, int scale_d) {
  asm volatile("{\n.reg .pred p;\nsetp.ne.b32 p, %18, 0;\n"
    "wgmma.mma_async.sync.aligned.m64n32k16.f32.bf16.bf16 {%0, %1, %2, %3, %4, %5, %6, %7, %8, %9, %10, %11, %12, %13, %14, %15}, %16, %17, p, 1, 1, 1, 0;\n}\n"
    : "+f"(d[0]), "+f"(d[1]), "+f"(d[2]), "+f"(d[3]), "+f"(d[4]), "+f"(d[5]), "+f"(d[6]), "+f"(d[7]), "+f"(d[8]), "+f"(d[9]), "+f"(d[10]), "+f"(d[11]), "+f"(d[12]), "+f"(d[13]), "+f"(d[14]), "+f"(d[15])
    : "l"(da), "l"(db), "r"(scale_d));
}

__device__ __forceinline__ void wgmma_ss_n8(float (&d)[4], uint64_t da, uint64_t db, int scale_d) {
  asm volatile("{\n.reg .pred p;\nsetp.ne.b32 p, %6, 0;\n"
    "wgmma.mma_async.sync.aligned.m64n8k16.f32.bf16.bf16 {%0, %1, %2, %3}, %4, %5, p, 1, 1, 1, 0;\n}\n"
    : "+f"(d[0]), "+f"(d[1]), "+f"(d[2]), "+f"(d[3])
    : "l"(da), "l"(db), "r"(scale_d));
}

__device__ __forceinline__ void wgmma_rs_n64(float (&d)[32], uint32_t a0, uint32_t a1, uint32_t a2, uint32_t a3, uint64_t db, int scale_d) {
  asm volatile("{\n.reg .pred p;\nsetp.ne.b32 p, %37, 0;\n"
    "wgmma.mma_async.sync.aligned.m64n64k16.f32.bf16.bf16 {%0, %1, %2, %3, %4, %5, %6, %7, %8, %9, %10, %11, %12, %13, %14, %15, %16, %17, %18, %19, %20, %21, %22, %23, %24, %25, %26, %27, %28, %29, %30, %31}, {%32, %33, %34, %35}, %36, p, 1, 1, 1;\n}\n"
    : "+f"(d[0]), "+f"(d[1]), "+f"(d[2]), "+f"(d[3]), "+f"(d[4]), "+f"(d[5]), "+f"(d[6]), "+f"(d[7]), "+f"(d[8]), "+f"(d[9]), "+f"(d[10]), "+f"(d[11]), "+f"(d[12]), "+f"(d[13]), "+f"(d[14]), "+f"(d[15]), "+f"(d[16]), "+f"(d[17]), "+f"(d[18]), "+f"(d[19]), "+f"(d[20]), "+f"(d[21]), "+f"(d[22]), "+f"(d[23]), "+f"(d[24]), "+f"(d[25]), "+f"(d[26]), "+f"(d[27]), "+f"(d[28]), "+f"(d[29]), "+f"(d[30]), "+f"(d[31])
    : "r"(a0), "r"(a1), "r"(a2), "r"(a3), "l"(db), "r"(scale_d));
}

__host__ __device__ constexpr int unit_slot(int u) {
  constexpr int t[36] = {4, 5, 6, 7, 8, 4, 5, 6, 0, 7, 8, 4,  1, 5, 6, 0, 2, 7, 8, 4, 3, 1, 5, 6,
                         0, 2, 7, 8,  4, 3, 1, 5, 6, 0, 2, 7};
  return t[u];
}
__host__ __device__ constexpr int unit_wait(int u) {
  constexpr int t[36] = {-1, -1, -1, -1, -1, 0, 1, 2, 2, 3, 4, 5,  5, 6, 7, 8, 8, 9, 10, 11, 11, 12, 13, 14,
                         15, 16, 17, 18,  19, 20, 21, 22, 23, 24, 25, 26};
  return t[u];
}

__device__ __forceinline__ uint32_t stage_off(int g, int j) {
  return g == 0 ? (j < 2 ? 8 * kSlot + j * 8192 : 10 * kSlot + (j - 2) * 8192)
                : (j < 2 ? 12 * kSlot + j * 8192 : (j == 2 ? 11 * kSlot + 8192 : 9 * kSlot));
}

struct Params {
  CUtensorMap x, w1, w2, wf, wg, wo, g, out64, out56;
  const void* xptr;
};

__device__ __forceinline__ void init_bar(uint32_t bars, int i) {
  const uint32_t a = bars + i * 8;
  const bool is_e = (i >= kBarE && i < kBarE + 27);
  mbar_init(a, is_e ? 8 : 1);
  if (!is_e) {
    uint32_t bytes = 16384;
    if (i == kBarFX) bytes = 8192;
    if (i == kBarFE) bytes = 8192;
    mbar_expect(a, bytes);
  }
}

__device__ __forceinline__ void store_pieces(const Params& P, uint32_t sb, uint32_t bars, int g, uint32_t cta, int b, int r0, int rvalid) {
  const int rl0 = cta * 16 + g * 8;
  if (rl0 >= rvalid) return;
  const CUtensorMap* omap = (rl0 + 8 <= rvalid) ? &P.out64 : &P.out56;
#pragma unroll
  for (int j = 0; j < 4; j++) {
    mbar_wait(bars + (kBarPR + g * 4 + j) * 8);
    if (elect_one()) {
      tma_store_3d(omap, sb + stage_off(g, j), 0, (b * kT2 + r0 + rl0) * 8, j);
      asm volatile("cp.async.bulk.commit_group;" ::: "memory");
    }
    __syncwarp();
    if (j == 0) TS(2, 12 + g);
    if (j == 3) TS(2, 14 + g);
  }
  if (elect_one()) asm volatile("cp.async.bulk.wait_group.read 0;" ::: "memory");
  __syncwarp();
  if (g == 1) { TS(2, 11); GT(1); TS_DUMP(2, 11, 12); GT_DUMP(1); }
  TS_DUMP(2, 12 + g, 13 + g); TS_DUMP(2, 14 + g, 15 + g);
}

__global__ void __cluster_dims__(2, 1, 1) __launch_bounds__(kThreads, 1)
rnnt_joint_kernel(const __grid_constant__ Params P) {
  extern __shared__ uint8_t smem_raw[];
  const uint32_t sb = (smem_u32(smem_raw) + 1023u) & ~1023u;
  const uint32_t bars = sb + kOffBar;
  const int warp = threadIdx.x >> 5, lane = threadIdx.x & 31;
  uint32_t cta;
  asm volatile("mov.u32 %0, %%cluster_ctarank;" : "=r"(cta));
  const uint32_t peer = cta ^ 1u;
  const int cl = blockIdx.x >> 1;
  const bool ge_cta = cl < 2;
  const int b = ge_cta ? cl : ((cl - 2) >> 5);
  const int r0 = ge_cta ? 32 * kR : ((cl - 2) & 31) * kR;
  const int rvalid = ge_cta ? kT2 - 32 * kR : kR;

  if (warp >= 8) {
    asm volatile("setmaxnreg.dec.sync.aligned.u32 40;");
    if (warp > 8) {
      if (elect_one()) {
#pragma unroll
        for (int i = 0; i < 5; i++) if (57 + (warp - 9) * 5 + i < kBarG) init_bar(bars, 57 + (warp - 9) * 5 + i);
#pragma unroll
        for (int i = 0; i < 5; i++) if (kBarRH + (warp - 9) * 5 + i < kBarGW) mbar_init(bars + (kBarRH + (warp - 9) * 5 + i) * 8, 4);
        if (warp == 11) { mbar_init(bars + kBarGW * 8, 8); mbar_init(bars + kBarFO * 8, 8); mbar_init(bars + kBarGE * 8, 1); mbar_expect(bars + kBarGE * 8, kGEBytes); }
        asm volatile("fence.mbarrier_init.release.cluster;" ::: "memory");
      }
      __syncwarp();
      asm volatile("barrier.cluster.arrive.relaxed.aligned;" ::: "memory");
      if (warp == 11 && lane < 9) asm volatile("prefetch.tensormap [%0];" ::"l"(reinterpret_cast<const CUtensorMap*>(&P) + lane) : "memory");
      __syncwarp();
      asm volatile("barrier.cluster.wait.aligned;" ::: "memory");
      if (warp == 10 && ge_cta) {
        mbar_wait(bars + kBarGW * 8);
        if (elect_one()) {
          __threadfence();
          asm volatile("red.release.gpu.global.add.u32 [%0], 1;" ::"l"(&g_ge_flag[b]) : "memory");
        }
        __syncwarp();
      }
      if (warp == 11) {
        if (elect_one()) {
          const unsigned int ticket = atomicAdd(&g_cta_count, 1u);
          const unsigned int want = (ticket / kNumCtas + 1u) * 2u;
          const long long t0 = clock64();
          unsigned int v;
          do {
            asm volatile("ld.acquire.gpu.global.u32 %0, [%1];" : "=r"(v) : "l"(&g_ge_flag[b]) : "memory");
          } while ((int)(v - want) < 0 && clock64() - t0 < 4000000ll);
          asm volatile("fence.proxy.async;" ::: "memory");
          bulk_load(sb + kOffGE, reinterpret_cast<const char*>(g_ge) + b * kGEBytes, kGEBytes, bars + kBarGE * 8);
        }
        __syncwarp();
        return;
      }
      if (warp == 10) store_pieces(P, sb, bars, 1, cta, b, r0, rvalid);
      if (warp == 10) return;
#pragma unroll
      for (int g = 0; g < 2; g++) {
        mbar_wait(bars + (kBarRH + g) * 8);
        if (elect_one()) {
          const uint32_t src = sb + kSlotH * kSlot + (2 * cta + g) * 8192;
          dsmem_copy(mapa(src, peer), src, 8192, mapa(bars + kBarHX * 8, peer));
        }
        __syncwarp();
      }
#pragma unroll
      for (int g = 0; g < 2; g++) {
        mbar_wait(bars + (kBarRF + g) * 8);
        if (elect_one()) {
          const uint32_t src = sb + kSlotF * kSlot + (2 * cta + g) * 4096;
          dsmem_copy(mapa(src, peer), src, 4096, mapa(bars + kBarFX * 8, peer));
        }
        __syncwarp();
      }
#pragma unroll
      for (int g = 0; g < 2; g++) {
        mbar_wait(bars + (kBarRE + g) * 8);
        if (elect_one())
          dsmem_copy(mapa(sb + kSlotFE * kSlot + (2 * cta + g) * 4096, peer), sb + kSlotH * kSlot + g * 4096, 4096, mapa(bars + kBarFE * 8, peer));
        __syncwarp();
      }
      store_pieces(P, sb, bars, 0, cta, b, r0, rvalid);
      return;
    }
    TS(2, 0);
    GT(0);
    const int par = cta == 0 ? 1 : 0;
    const int q0 = cta == 0 ? 2 * r0 - 2 : 2 * r0 - 1;
    if (elect_one()) {
      mbar_init(bars + kBarX * 8, 1); mbar_expect(bars + kBarX * 8, 16384);
      mbar_init(bars + kBarW * 8, 1); mbar_expect(bars + kBarW * 8, 16384);
      fence_async_smem();
      tma_load_4d(sb, &P.x, bars + kBarX * 8, 0, 1, 2 * r0 - 2, b);
      tma_load_4d(sb + 8192, &P.x, bars + kBarX * 8, 0, 0, 2 * r0 - 1, b);
      tma_load_3d(sb + unit_slot(0) * kSlot, &P.w1, bars + kBarW * 8, 0, 0, 2 * cta);
      TS(2, 7);
#pragma unroll
      for (int i = 1; i < 9; i++) if (i != kBarW) { mbar_init(bars + i * 8, 1); mbar_expect(bars + i * 8, 16384); }
      if (ge_cta) { mbar_init(bars + kBarG * 8, 1); mbar_expect(bars + kBarG * 8, 4 * 16384 + 4096); mbar_init(bars + kBarP0 * 8, 8); }
      asm volatile("fence.mbarrier_init.release.cluster;" ::: "memory");
      fence_async_smem();
      TS(2, 8);
      if (ge_cta) {
        tma_load_3d(sb + kOffG, &P.g, bars + kBarG * 8, 0, b * 8, 0);
#pragma unroll
        for (int i = 0; i < 4; i++) tma_load_3d(sb + (9 + i) * kSlot, &P.wg, bars + kBarG * 8, 0, i * 64, 2 * cta);
      }
#pragma unroll
      for (int u = 1; u < 5; u++)
        tma_load_3d(sb + unit_slot(u) * kSlot, &P.w1, bars + (kBarW + u) * 8, 0, (u % 3) * 256 + (u / 3) * 64, 2 * cta);
      TS(2, 10);
    }
    __syncwarp();
    TS(2, 6);
    cluster_sync_relaxed();
    TS(2, 1);
    if (elect_one()) {
#pragma unroll
      for (int p = 1; p < XFIRST; p++)
        tma_load_4d_mc(sb + p * kSlot + cta * 8192, &P.x, bars + (kBarX + p) * 8, p * 64, par, q0, b, (uint16_t)3);
    }
    __syncwarp();
#pragma unroll
    for (int p = XFIRST; p < 4; p++) {
      if (XSTEP == 1 || ((p - XFIRST) & 1) == 0) mbar_wait(bars + (kBarX + p - XFIRST) * 8);
      if (ge_cta && p == 3) mbar_wait(bars + kBarP0 * 8);
      if (elect_one())
        tma_load_4d_mc(sb + p * kSlot + cta * 8192, &P.x, bars + (kBarX + p) * 8, p * 64, par, q0, b, (uint16_t)3);
      __syncwarp();
    }
#pragma unroll
    for (int u = 5; u < 36; u++) {
      if (unit_wait(u) != unit_wait(u - 1)) mbar_wait(bars + (kBarE + unit_wait(u)) * 8);
      if (WOGATE >= 1 && u == 28) mbar_wait(bars + kBarFX * 8);
      if (WOGATE >= 2 && u == 32) mbar_wait(bars + kBarFE * 8);
      if (elect_one()) {
        const uint32_t dst = sb + unit_slot(u) * kSlot, bar = bars + (kBarW + u) * 8;
        if (u < 12) tma_load_3d(dst, &P.w1, bar, 0, (u % 3) * 256 + (u / 3) * 64, 2 * cta);
        else if (u < 24) tma_load_3d(dst, &P.w2, bar, 0, ((u - 12) % 3) * 256 + ((2 * cta + (u - 12) / 3) & 3) * 64, 2 * cta);
        else if (u < 28) tma_load_3d(dst, &P.wf, bar, 0, ((2 * cta + (u - 24)) & 3) * 64, 2 * cta);
        else tma_load_3d(dst, &P.wo, bar, 0, ((2 * cta + (u - 28)) & 3) * 64, ((u - 28) >> 2) * 2);
      }
      __syncwarp();
      if (u == 11) TS(2, 2);
      if (u == 23) TS(2, 3);
      if (u == 27) TS(2, 4);
      if (u == 35) TS(2, 5);
    }
    TS_DUMP(2, 0, 11); GT_DUMP(0);
  } else {
    asm volatile("setmaxnreg.inc.sync.aligned.u32 232;");
    const int wg = warp >> 2, w = warp & 3;
    const int gq = lane >> 2, q = lane & 3;
    const uint32_t panel = 2 * cta + wg;
    const int ch = panel * 64 + w * 16 + gq;
    const uint32_t dA = desc_lo(sb + wg * 8192, 8192);
    const uint32_t dB = desc_lo(sb, 16);
    const uint32_t dBo = desc_lo(sb + cta * 2 * 8192, 16), dBp = desc_lo(sb + (cta ^ 1) * 2 * 8192, 16);
    const uint32_t dFo = desc_lo(sb + cta * 2 * 4096, 16), dFp = desc_lo(sb + (cta ^ 1) * 2 * 4096, 16);
    if (elect_one()) {
#pragma unroll
      for (int i = 0; i < 6; i++) init_bar(bars, 9 + warp * 6 + i);
      asm volatile("fence.mbarrier_init.release.cluster;" ::: "memory");
    }
    __syncwarp();
    cluster_sync_relaxed();
    if (w == 0) TS(wg, 0);

    if (ge_cta) {
      float ga[4];
      mbar_wait(bars + kBarG * 8);
      wg_fence();
#pragma unroll
      for (int i = 0; i < 4; i++) {
#pragma unroll
        for (int s = 0; s < 4; s++)
          wgmma_ss_n8(ga, desc_at(dA, (9 + i) * kSlot + s * 2048), desc_at(dB, kOffG + i * 1024 + s * 32), (i | s) != 0);
      }
      wg_commit();
      wg_wait<0>();
      if (lane == 0) mbar_arrive(bars + kBarP0 * 8);
      float* gp = g_ge + b * (kGEBytes / 4) + ((ch & 7) >> 1) * (kGEPitch / 4) + (ch >> 4) * 4 + (ch & 1);
      gp[(2 * q) * 4 * (kGEPitch / 4)] = ga[0];
      gp[(2 * q + 1) * 4 * (kGEPitch / 4)] = ga[1];
      gp[(2 * q) * 4 * (kGEPitch / 4) + 2] = ga[2];
      gp[(2 * q + 1) * 4 * (kGEPitch / 4) + 2] = ga[3];
      __syncwarp();
      if (lane == 0) mbar_arrive(bars + kBarGW * 8);
    }

    {
      float acc[32];
#pragma unroll
      for (int u = 0; u < 12; u++) {
        const int p = u / 3, tap = u % 3;
        if (SKEW1 > 0 && u == 12 - SKEW1) bar_sync_pred5(wg == 1);
        if (tap == 0) mbar_wait(bars + (kBarX + p) * 8);
        mbar_wait(bars + (kBarW + u) * 8);
        if (u == 0 && w == 0) TS(wg, 1);
        wg_fence();
#pragma unroll
        for (int s = 0; s < 4; s++)
          wgmma_ss_n64(acc, desc_at(dA, unit_slot(u) * kSlot + s * 2048),
                       desc_at(dB, p * kSlot + (tap == 1 ? 8192 : (tap == 2 ? 128 : 0)) + s * 32), (u | s) != 0);
        wg_commit();
        if (SKEW1 > 0 && u == 11) bar_arrive_pred5(wg == 0);
        if (u > 0) {
          wg_wait<1>();
          if (lane == 0) mbar_arrive(bars + (kBarE + u - 1) * 8);
        }
      }
      wg_wait<0>();
      if (lane == 0) mbar_arrive(bars + (kBarE + 11) * 8);
      if (w == 0) TS(wg, 2);
      const uint32_t hp = sb + kSlotH * kSlot + panel * 8192;
      const int mi = lane >> 3, l8 = lane & 7;
#pragma unroll
      for (int jb = 0; jb < 8; jb += 2) {
        uint32_t r[4];
#pragma unroll
        for (int t = 0; t < 2; t++) {
          r[2 * t + 0] = pack_bf16(gelu_tanh(acc[4 * (jb + t) + 0]), gelu_tanh(acc[4 * (jb + t) + 1]));
          r[2 * t + 1] = pack_bf16(gelu_tanh(acc[4 * (jb + t) + 2]), gelu_tanh(acc[4 * (jb + t) + 3]));
        }
        const int n = 8 * (jb + (mi >> 1)) + l8;
        const int row = n >> 1, chunk = 2 * w + (mi & 1);
        stsm_x4_trans(hp + (n & 1) * 4096 + row * 128 + ((chunk ^ (row & 7)) << 4), r[0], r[1], r[2], r[3]);
      }
      __syncwarp();
      if (w == 0) TS(wg, 15);
      fence_async_smem();
      __syncwarp();
      if (lane == 0) mbar_arrive(bars + (kBarRH + wg) * 8);
      if (w == 0) TS(wg, 3);
    }
    {
      float acc[16];
#pragma unroll
      for (int v = 0; v < 12; v++) {
        const int i = v / 3, tap = v % 3;
        if (SKEW2 > 0 && v == 12 - SKEW2) bar_sync_pred6(wg == 1);
        if (v == 0) mbar_wait(bars + kBarRH * 8);
        if (v == 3) mbar_wait(bars + (kBarRH + 1) * 8);
        if (v == 6) { mbar_wait_cluster(bars + kBarHX * 8); if (w == 0) TS(wg, 4); }
        mbar_wait(bars + (kBarW + 12 + v) * 8);
        wg_fence();
#pragma unroll
        for (int s = 0; s < 4; s++)
          wgmma_ss_n32(acc, desc_at(dA, unit_slot(12 + v) * kSlot + s * 2048),
                       desc_at(i < 2 ? dBo : dBp, kSlotH * kSlot + (i & 1) * 8192 + (tap == 1 ? 4096 : (tap == 2 ? 128 : 0)) + s * 32), (v | s) != 0);
        wg_commit();
        if (SKEW2 > 0 && v == 11) bar_arrive_pred6(wg == 0);
        if (v > 0) {
          wg_wait<1>();
          if (lane == 0) mbar_arrive(bars + (kBarE + 12 + v - 1) * 8);
        }
      }
      wg_wait<0>();
      if (lane == 0) mbar_arrive(bars + (kBarE + 23) * 8);
      if (w == 0) TS(wg, 5);
      const uint32_t fp = sb + kSlotF * kSlot + panel * 4096;
      const int mi = lane >> 3, l8 = lane & 7;
#pragma unroll
      for (int jb = 0; jb < 4; jb += 2) {
        uint32_t r[4];
#pragma unroll
        for (int t = 0; t < 2; t++) {
          r[2 * t + 0] = pack_bf16(gelu_tanh(acc[4 * (jb + t) + 0]), gelu_tanh(acc[4 * (jb + t) + 1]));
          r[2 * t + 1] = pack_bf16(gelu_tanh(acc[4 * (jb + t) + 2]), gelu_tanh(acc[4 * (jb + t) + 3]));
        }
        const int n = 8 * (jb + (mi >> 1)) + l8;
        const int chunk = 2 * w + (mi & 1);
        stsm_x4_trans(fp + n * 128 + ((chunk ^ (n & 7)) << 4), r[0], r[1], r[2], r[3]);
      }
      fence_async_smem();
      __syncwarp();
      if (lane == 0) mbar_arrive(bars + (kBarRF + wg) * 8);
      if (w == 0) TS(wg, 6);
    }
    {
      float acc[16];
#pragma unroll
      for (int i = 0; i < 4; i++) {
        if (i < 2) mbar_wait(bars + (kBarRF + i) * 8);
        if (i == 2) { mbar_wait_cluster(bars + kBarFX * 8); if (w == 0) TS(wg, 7); }
        mbar_wait(bars + (kBarW + 24 + i) * 8);
        wg_fence();
#pragma unroll
        for (int s = 0; s < 4; s++)
          wgmma_ss_n32(acc, desc_at(dA, unit_slot(24 + i) * kSlot + s * 2048),
                       desc_at(i < 2 ? dFo : dFp, kSlotF * kSlot + (i & 1) * 4096 + s * 32), (i | s) != 0);
        wg_commit();
        if (i > 0) {
          wg_wait<1>();
          if (lane == 0) mbar_arrive(bars + (kBarE + 24 + i - 1) * 8);
        }
      }
      wg_wait<0>();
      if (w == 0) TS(wg, 8);
      const uint32_t qk = gq >> 1;
      const uint32_t off0 = qk * 128 + (((2 * w) ^ (2 * qk)) << 4) + (gq & 1) * 8;
      const uint32_t off1 = qk * 128 + (((2 * w + 1) ^ (2 * qk)) << 4) + (gq & 1) * 8;
      const uint32_t own = sb + kSlotFE * kSlot + panel * 4096;
      const uint32_t stg = sb + kSlotH * kSlot + wg * 4096;
#pragma unroll
      for (int jb = 0; jb < 4; jb++) {
        const uint32_t base = (((uint32_t)(jb >> 1) == cta) ? own : stg) + (4 * (jb & 1) + q) * 512;
        sts64(base + off0, acc[4 * jb + 0], acc[4 * jb + 1]);
        sts64(base + off1, acc[4 * jb + 2], acc[4 * jb + 3]);
      }
      fence_async_smem();
      __syncwarp();
      if (lane == 0) { mbar_arrive(bars + (kBarRE + wg) * 8); mbar_arrive(bars + kBarFO * 8); }
      if (w == 0) TS(wg, 9);
    }
    const int rl0 = cta * 16 + wg * 8;
    mbar_wait(bars + kBarFO * 8);
    mbar_wait(bars + kBarGE * 8);
    if (!TSPLIT && wg == 1) asm volatile("bar.sync 4, 256;" ::: "memory");
    if (rl0 < rvalid) {
      if (w == 0) TS(wg, 10);
      const uint32_t fe_row = sb + kSlotFE * kSlot + ((4 * wg + w) * 4 + q) * 128;
      const uint32_t fe_h[2] = {fe_row + cta * 8192, fe_row + (cta ^ 1) * 8192};
      const uint32_t ge_h[2] = {sb + kOffGE + lane * kGEPitch + cta * 128, sb + kOffGE + lane * kGEPitch + (cta ^ 1) * 128};
      const int mi = lane >> 3, l8 = lane & 7;
      const uint32_t st = sb + (16 * w + (mi & 1) * 8 + l8) * 128;
      uint32_t A[64];
      float acc[2][32];
      {
        constexpr int PD = 3;
        float4 fa[PD], fb[PD], gg[PD];
#pragma unroll
        for (int kk = 0; kk < 16 + PD; kk++) {
          if (kk >= PD) {
            const int k = kk - PD, sl = k % PD;
            A[4 * k + 0] = tanh2_pack(fa[sl].x + gg[sl].x, fa[sl].z + gg[sl].y);
            A[4 * k + 1] = tanh2_pack(fa[sl].y + gg[sl].x, fa[sl].w + gg[sl].y);
            A[4 * k + 2] = tanh2_pack(fb[sl].x + gg[sl].z, fb[sl].z + gg[sl].w);
            A[4 * k + 3] = tanh2_pack(fb[sl].y + gg[sl].z, fb[sl].w + gg[sl].w);
          }
          if (kk < 16) {
            const int sl = kk % PD;
            if (kk == 8) {
              if (TSPLIT) bar_sync_pred4(wg == 1);
              mbar_wait_cluster(bars + kBarFE * 8);
            }
            fa[sl] = lds128(fe_h[kk >> 3] + ((kk >> 2) & 1) * 4096 + ((((kk & 3) * 2) ^ (2 * q)) << 4));
            fb[sl] = lds128(fe_h[kk >> 3] + ((kk >> 2) & 1) * 4096 + ((((kk & 3) * 2 + 1) ^ (2 * q)) << 4));
            gg[sl] = lds128(ge_h[kk >> 3] + (kk & 7) * 16);
          }
        }
      }
      asm volatile("barrier.cluster.arrive.relaxed.aligned;" ::: "memory");
#pragma unroll
      for (int kk = 0; kk < 16; kk++) {
        if ((kk & 3) == 0) { mbar_wait(bars + (kBarW + 28 + (kk >> 2)) * 8); wg_fence(); }
        wgmma_rs_n64(acc[0], A[4 * kk], A[4 * kk + 1], A[4 * kk + 2], A[4 * kk + 3],
                     desc_at(dB, unit_slot(28 + (kk >> 2)) * kSlot + (kk & 3) * 2048), kk != 0);
        if (kk == ARRK) bar_arrive_pred(wg == 0);
      }
      wg_commit();
      wg_wait<0>();
#pragma unroll
      for (int jb = 0; jb < 8; jb += 2) {
        const uint32_t r0_ = pack_bf16(acc[0][4 * jb + 0], acc[0][4 * jb + 1]), r1_ = pack_bf16(acc[0][4 * jb + 2], acc[0][4 * jb + 3]);
        const uint32_t r2_ = pack_bf16(acc[0][4 * jb + 4], acc[0][4 * jb + 5]), r3_ = pack_bf16(acc[0][4 * jb + 6], acc[0][4 * jb + 7]);
        stsm_x4(st + (wg ? stage_off(1, 0) : stage_off(0, 0)) + (((jb + (mi >> 1)) ^ l8) << 4), r0_, r1_, r2_, r3_);
      }
      fence_async_smem();
      __syncwarp();
      mbar_arrive_pred(bars + (kBarPR + wg * 4) * 8, lane == 0);
      if (w == 0) TS(wg, 11);
#pragma unroll
      for (int j = 0; j < 4; j++) {
        const int jn = j + 1;
        if (jn == 2) {
#pragma unroll
          for (int i = 0; i < 4; i++) mbar_wait(bars + (kBarW + 32 + i) * 8);
        }
        if (j < 3) wg_fence();
        const uint32_t stj = st + (wg ? stage_off(1, j) : stage_off(0, j));
#pragma unroll
        for (int kk = 0; kk < 16; kk++) {
          if (j < 3)
            wgmma_rs_n64(acc[jn & 1], A[4 * kk], A[4 * kk + 1], A[4 * kk + 2], A[4 * kk + 3],
                         desc_at(dB, unit_slot(28 + (jn >> 1) * 4 + (kk >> 2)) * kSlot + (jn & 1) * 8192 + (kk & 3) * 2048), kk != 0);
          if (kk == 1 && j > 0) {
            if (j < 3) { wg_commit(); wg_wait<1>(); } else { wg_wait<0>(); }
          }
          if (j > 0 && kk >= 2 && kk < 10 && (kk & 1) == 0) {
            const int jb = kk - 2;
            const uint32_t r0_ = pack_bf16(acc[j & 1][4 * jb + 0], acc[j & 1][4 * jb + 1]), r1_ = pack_bf16(acc[j & 1][4 * jb + 2], acc[j & 1][4 * jb + 3]);
            const uint32_t r2_ = pack_bf16(acc[j & 1][4 * jb + 4], acc[j & 1][4 * jb + 5]), r3_ = pack_bf16(acc[j & 1][4 * jb + 6], acc[j & 1][4 * jb + 7]);
            stsm_x4(stj + (((jb + (mi >> 1)) ^ l8) << 4), r0_, r1_, r2_, r3_);
          }
          if (j > 0 && kk == 9) {
            fence_async_smem();
            __syncwarp();
            mbar_arrive_pred(bars + (kBarPR + wg * 4 + j) * 8, lane == 0);
          }
        }
        if (j < 3) wg_commit();
        if (j == 0 && w == 0) TS(wg, 12);
        if (j == 2 && w == 0) TS(wg, 13);
      }
      if (w == 0) TS(wg, 14);
    } else {
      if (wg == 0) asm volatile("bar.arrive 4, 256;" ::: "memory");
      if (TSPLIT && wg == 1) asm volatile("bar.sync 4, 256;" ::: "memory");
      mbar_wait_cluster(bars + kBarFE * 8);
      asm volatile("barrier.cluster.arrive.relaxed.aligned;" ::: "memory");
    }
    asm volatile("barrier.cluster.wait.aligned;" ::: "memory");
    if (w == 0) TS_DUMP(wg, 0, 16);
  }
}

typedef CUresult (*EncodeFn)(CUtensorMap*, CUtensorMapDataType, cuuint32_t, void*, const cuuint64_t*, const cuuint64_t*,
                             const cuuint32_t*, const cuuint32_t*, CUtensorMapInterleave, CUtensorMapSwizzle,
                             CUtensorMapL2promotion, CUtensorMapFloatOOBfill);

void make_map3(EncodeFn enc, CUtensorMap* tm, const void* ptr, uint64_t rows, uint32_t box_rows, uint32_t box_panels) {
  cuuint64_t gd[3] = {64, rows, 4};
  cuuint64_t gs[2] = {512, 128};
  cuuint32_t bd[3] = {64, box_rows, box_panels};
  cuuint32_t es[3] = {1, 1, 1};
  enc(tm, CU_TENSOR_MAP_DATA_TYPE_BFLOAT16, 3, const_cast<void*>(ptr), gd, gs, bd, es, CU_TENSOR_MAP_INTERLEAVE_NONE,
      CU_TENSOR_MAP_SWIZZLE_128B, CU_TENSOR_MAP_L2_PROMOTION_L2_256B, CU_TENSOR_MAP_FLOAT_OOB_FILL_NONE);
}

}

extern "C" void kernel_launch(void* const* d_in, const int* in_sizes, int n_in, void* d_out, int out_size) {
  static EncodeFn enc = nullptr;
  if (!enc) {
    cudaDriverEntryPointQueryResult qr;
    cudaGetDriverEntryPoint("cuTensorMapEncodeTiled", (void**)&enc, cudaEnableDefault, &qr);
    cudaFuncSetAttribute(rnnt_joint_kernel, cudaFuncAttributeMaxDynamicSharedMemorySize, kSmemBytes);
  }
  Params P;
  {
    cuuint64_t gd[4] = {256, 2, 2000, 2};
    cuuint64_t gs[3] = {512, 1024, 4000ull * 512};
    cuuint32_t bd[4] = {64, 1, 64, 1};
    cuuint32_t es[4] = {1, 1, 1, 1};
    enc(&P.x, CU_TENSOR_MAP_DATA_TYPE_BFLOAT16, 4, d_in[0], gd, gs, bd, es, CU_TENSOR_MAP_INTERLEAVE_NONE,
        CU_TENSOR_MAP_SWIZZLE_128B, XPROMO, CU_TENSOR_MAP_FLOAT_OOB_FILL_NONE);
  }
  P.xptr = d_in[0];
  make_map3(enc, &P.w1, d_in[1], 768, 64, 2);
  make_map3(enc, &P.w2, d_in[2], 768, 64, 2);
  make_map3(enc, &P.g, d_in[3], 16, 8, 4);
  make_map3(enc, &P.wf, d_in[4], 256, 64, 2);
  make_map3(enc, &P.wg, d_in[5], 256, 64, 2);
  make_map3(enc, &P.wo, d_in[6], 256, 64, 2);
  make_map3(enc, &P.out64, d_out, 16000, 64, 1);
  make_map3(enc, &P.out56, d_out, 16000, 56, 1);
  rnnt_joint_kernel<<<kNumCtas, kThreads, kSmemBytes>>>(P);
}
```

```cpp
#include <cuda_runtime.h>
#include <cuda_bf16.h>
#include <cuda.h>
#include <stdint.h>

#define ARRK 3
#define XBULK 0
#define SKEW1 2
#define SKEW2 2
#define TSPLIT 0
#define WOGATE 1
#define ARRPOS 1
#define XPREF 1
#define XFIRST 3
#define XSTEP 1
#define XPROMO CU_TENSOR_MAP_L2_PROMOTION_L2_128B
namespace {

constexpr int kT2 = 1000;
constexpr int kR = 31;
constexpr int kNumCtas = 132;
constexpr int kThreads = 384;
constexpr int kSlot = 16384;

constexpr int kSlotFE = 9, kSlotF = 10, kSlotH = 11;
constexpr int kOffG = 13 * kSlot;
constexpr int kOffGE = kOffG + 4096;
constexpr int kGEPitch = 272;
constexpr int kGEBytes = 32 * kGEPitch;
constexpr int kOffBar = kOffGE + kGEBytes;
constexpr int kBarX = 0;
constexpr int kBarW = 4;
constexpr int kBarE = 40;
constexpr int kBarHX = 67, kBarFX = 68, kBarFE = 69, kBarG = 70, kBarP0 = 71;
constexpr int kBarRH = 72, kBarRF = 74, kBarRE = 76;
constexpr int kBarPR = 78;
constexpr int kBarGW = 86;
constexpr int kBarFO = 87;
constexpr int kBarGE = 88;
constexpr int kNumBars = 89;
constexpr int kSmemBytes = kOffBar + kNumBars * 8 + 1024;

__device__ __align__(128) float g_ge[2 * kGEBytes / 4];
__device__ unsigned int g_ge_flag[2];
__device__ unsigned int g_cta_count;

#define TS(slot_, idx_) do {} while (0)
#define GT(idx_) do {} while (0)
#define TS_DUMP(slot_, lo_, hi_) do {} while (0)
#define GT_DUMP(idx_) do {} while (0)

__device__ __forceinline__ uint32_t smem_u32(const void* p) { return (uint32_t)__cvta_generic_to_shared(p); }
__device__ __forceinline__ void mbar_init(uint32_t a, uint32_t c) { asm volatile("mbarrier.init.shared.b64 [%0], %1;" ::"r"(a), "r"(c) : "memory"); }
__device__ __forceinline__ void mbar_expect(uint32_t a, uint32_t b) { asm volatile("mbarrier.arrive.expect_tx.shared.b64 _, [%0], %1;" ::"r"(a), "r"(b) : "memory"); }
__device__ __forceinline__ void mbar_arrive(uint32_t a) { asm volatile("mbarrier.arrive.shared.b64 _, [%0];" ::"r"(a) : "memory"); }
__device__ __forceinline__ void mbar_arrive_pred(uint32_t a, bool p) {
  asm volatile("{\n.reg .pred q;\nsetp.ne.u32 q, %1, 0;\n@q mbarrier.arrive.shared.b64 _, [%0];\n}\n" ::"r"(a), "r"((uint32_t)p) : "memory");
}
__device__ __forceinline__ void bar_arrive_pred(bool p) {
  asm volatile("{\n.reg .pred q;\nsetp.ne.u32 q, %0, 0;\n@q bar.arrive 4, 256;\n}\n" ::"r"((uint32_t)p) : "memory");
}
#define DEF_NAMED(ID) \
__device__ __forceinline__ void bar_arrive_pred##ID(bool p) { asm volatile("{\n.reg .pred q;\nsetp.ne.u32 q, %0, 0;\n@q bar.arrive " #ID ", 256;\n}\n" ::"r"((uint32_t)p) : "memory"); } \
__device__ __forceinline__ void bar_sync_pred##ID(bool p) { asm volatile("{\n.reg .pred q;\nsetp.ne.u32 q, %0, 0;\n@q bar.sync " #ID ", 256;\n}\n" ::"r"((uint32_t)p) : "memory"); }
DEF_NAMED(4)
DEF_NAMED(5)
DEF_NAMED(6)
__device__ __forceinline__ bool mbar_try(uint32_t a) {
  uint32_t ok;
  asm volatile("{\n.reg .pred p;\nmbarrier.try_wait.parity.shared.b64 p, [%1], 0;\nselp.u32 %0, 1, 0, p;\n}\n" : "=r"(ok) : "r"(a) : "memory");
  return ok != 0;
}
__device__ __forceinline__ bool mbar_test(uint32_t a) {
  uint32_t ok;
  asm volatile("{\n.reg .pred p;\nmbarrier.test_wait.parity.shared.b64 p, [%1], 0;\nselp.u32 %0, 1, 0, p;\n}\n" : "=r"(ok) : "r"(a) : "memory");
  return ok != 0;
}
__device__ __forceinline__ bool mbar_try_cluster(uint32_t a) {
  uint32_t ok;
  asm volatile("{\n.reg .pred p;\nmbarrier.try_wait.parity.acquire.cluster.shared.b64 p, [%1], 0;\nselp.u32 %0, 1, 0, p;\n}\n" : "=r"(ok) : "r"(a) : "memory");
  return ok != 0;
}
__device__ __forceinline__ void mbar_wait_slow(uint32_t a) {
  const long long t0 = clock64();
  while (!mbar_try(a)) { if (clock64() - t0 > 4000000ll) break; }
}
__device__ __forceinline__ void mbar_wait_cluster_slow(uint32_t a) {
  const long long t0 = clock64();
  while (!mbar_try_cluster(a)) { if (clock64() - t0 > 4000000ll) break; }
}
__device__ __forceinline__ void mbar_wait(uint32_t a) { if (!mbar_try(a)) mbar_wait_slow(a); }
__device__ __forceinline__ void mbar_wait_cluster(uint32_t a) { if (!mbar_try_cluster(a)) mbar_wait_cluster_slow(a); }
__device__ __forceinline__ uint32_t mapa(uint32_t a, uint32_t r) { uint32_t d; asm volatile("mapa.shared::cluster.u32 %0, %1, %2;" : "=r"(d) : "r"(a), "r"(r)); return d; }
__device__ __forceinline__ bool elect_one() { uint32_t p; asm volatile("{\n.reg .pred P;\nelect.sync _|P, 0xffffffff;\nselp.u32 %0, 1, 0, P;\n}\n" : "=r"(p)); return p != 0; }
__device__ __forceinline__ void fence_async_smem() { asm volatile("fence.proxy.async.shared::cta;" ::: "memory"); }
__device__ __forceinline__ void bar_consumers() { asm volatile("bar.sync 1, 256;" ::: "memory"); }
__device__ __forceinline__ void bar_wg(int wg) { asm volatile("bar.sync %0, 128;" ::"r"(2 + wg) : "memory"); }
__device__ __forceinline__ void cluster_sync_relaxed() { asm volatile("barrier.cluster.arrive.relaxed.aligned;\nbarrier.cluster.wait.aligned;" ::: "memory"); }
__device__ __forceinline__ void wg_fence() { asm volatile("wgmma.fence.sync.aligned;" ::: "memory"); }
__device__ __forceinline__ void wg_commit() { asm volatile("wgmma.commit_group.sync.aligned;" ::: "memory"); }
template <int N> __device__ __forceinline__ void wg_wait() { asm volatile("wgmma.wait_group.sync.aligned %0;" ::"n"(N) : "memory"); }

__device__ __forceinline__ void tma_load_3d(uint32_t dst, const CUtensorMap* tm, uint32_t bar, int c0, int c1, int c2) {
  asm volatile("cp.async.bulk.tensor.3d.shared::cluster.global.mbarrier::complete_tx::bytes [%0], [%1, {%3, %4, %5}], [%2];"
               ::"r"(dst), "l"(tm), "r"(bar), "r"(c0), "r"(c1), "r"(c2) : "memory");
}
__device__ __forceinline__ void tma_load_4d(uint32_t dst, const CUtensorMap* tm, uint32_t bar, int c0, int c1, int c2, int c3) {
  asm volatile("cp.async.bulk.tensor.4d.shared::cluster.global.mbarrier::complete_tx::bytes [%0], [%1, {%3, %4, %5, %6}], [%2];"
               ::"r"(dst), "l"(tm), "r"(bar), "r"(c0), "r"(c1), "r"(c2), "r"(c3) : "memory");
}
__device__ __forceinline__ void tma_load_4d_mc(uint32_t dst, const CUtensorMap* tm, uint32_t bar, int c0, int c1, int c2, int c3, uint16_t mask) {
  asm volatile("cp.async.bulk.tensor.4d.shared::cluster.global.mbarrier::complete_tx::bytes.multicast::cluster [%0], [%1, {%3, %4, %5, %6}], [%2], %7;"
               ::"r"(dst), "l"(tm), "r"(bar), "r"(c0), "r"(c1), "r"(c2), "r"(c3), "h"(mask) : "memory");
}
__device__ __forceinline__ void tma_store_3d(const CUtensorMap* tm, uint32_t src, int c0, int c1, int c2) {
  asm volatile("cp.async.bulk.tensor.3d.global.shared::cta.bulk_group [%0, {%2, %3, %4}], [%1];"
               ::"l"(tm), "r"(src), "r"(c0), "r"(c1), "r"(c2) : "memory");
}
__device__ __forceinline__ void bulk_load(uint32_t dst, const void* src, uint32_t bytes, uint32_t bar) {
  asm volatile("cp.async.bulk.shared::cluster.global.mbarrier::complete_tx::bytes [%0], [%1], %2, [%3];"
               ::"r"(dst), "l"(src), "r"(bytes), "r"(bar) : "memory");
}
__device__ __forceinline__ void dsmem_copy(uint32_t dst_remote, uint32_t src, uint32_t bytes, uint32_t bar_remote) {
  asm volatile("cp.async.bulk.shared::cluster.shared::cta.mbarrier::complete_tx::bytes [%0], [%1], %2, [%3];"
               ::"r"(dst_remote), "r"(src), "r"(bytes), "r"(bar_remote) : "memory");
}
__device__ __forceinline__ void stsm_x4_trans(uint32_t addr, uint32_t r0, uint32_t r1, uint32_t r2, uint32_t r3) {
  asm volatile("stmatrix.sync.aligned.m8n8.x4.trans.shared.b16 [%0], {%1, %2, %3, %4};" ::"r"(addr), "r"(r0), "r"(r1), "r"(r2), "r"(r3) : "memory");
}
__device__ __forceinline__ void stsm_x4(uint32_t addr, uint32_t r0, uint32_t r1, uint32_t r2, uint32_t r3) {
  asm volatile("stmatrix.sync.aligned.m8n8.x4.shared.b16 [%0], {%1, %2, %3, %4};" ::"r"(addr), "r"(r0), "r"(r1), "r"(r2), "r"(r3) : "memory");
}
__device__ __forceinline__ float2 lds64(uint32_t a) { float2 v; asm volatile("ld.shared.v2.f32 {%0, %1}, [%2];" : "=f"(v.x), "=f"(v.y) : "r"(a) : "memory"); return v; }
__device__ __forceinline__ float4 lds128(uint32_t a) { float4 v; asm volatile("ld.shared.v4.f32 {%0, %1, %2, %3}, [%4];" : "=f"(v.x), "=f"(v.y), "=f"(v.z), "=f"(v.w) : "r"(a) : "memory"); return v; }
__device__ __forceinline__ void sts64(uint32_t a, float x, float y) { asm volatile("st.shared.v2.f32 [%0], {%1, %2};" ::"r"(a), "f"(x), "f"(y) : "memory"); }
__device__ __forceinline__ float tanh_fast(float x) { float y; asm("tanh.approx.f32 %0, %1;" : "=f"(y) : "f"(x)); return y; }
__device__ __forceinline__ uint32_t tanh2_pack(float lo, float hi) {
  uint32_t r;
  asm volatile("{\n.reg .f32 a, b;\ntanh.approx.f32 a, %1;\ntanh.approx.f32 b, %2;\ncvt.rn.bf16x2.f32 %0, b, a;\n}\n" : "=r"(r) : "f"(lo), "f"(hi));
  return r;
}
__device__ __forceinline__ uint32_t pack_bf16(float lo, float hi) { uint32_t r; asm("cvt.rn.bf16x2.f32 %0, %1, %2;" : "=r"(r) : "f"(hi), "f"(lo)); return r; }
__device__ __forceinline__ float gelu_tanh(float x) {
  const float k0 = 0.7978845608028654f, k1 = 0.7978845608028654f * 0.044715f;
  float u = x * fmaf(x * x, k1, k0);
  float hx = 0.5f * x;
  return fmaf(hx, tanh_fast(u), hx);
}
__device__ __forceinline__ uint64_t make_desc(uint32_t addr, uint32_t lbo, uint32_t sbo) {
  return (uint64_t)((addr & 0x3FFFF) >> 4) | ((uint64_t)(lbo >> 4) << 16) | ((uint64_t)(sbo >> 4) << 32) | ((uint64_t)1 << 62);
}

__device__ __forceinline__ uint32_t desc_lo(uint32_t addr, uint32_t lbo) { return ((addr & 0x3FFFF) >> 4) | ((lbo >> 4) << 16); }
__device__ __forceinline__ uint64_t desc_at(uint32_t lo, uint32_t off) { return ((uint64_t)0x40000040u << 32) | (uint64_t)(lo + (off >> 4)); }

__device__ __forceinline__ void wgmma_ss_n64(float (&d)[32], uint64_t da, uint64_t db, int scale_d) {
  asm volatile("{\n.reg .pred p;\nsetp.ne.b32 p, %34, 0;\n"
    "wgmma.mma_async.sync.aligned.m64n64k16.f32.bf16.bf16 {%0, %1, %2, %3, %4, %5, %6, %7, %8, %9, %10, %11, %12, %13, %14, %15, %16, %17, %18, %19, %20, %21, %22, %23, %24, %25, %26, %27, %28, %29, %30, %31}, %32, %33, p, 1, 1, 1, 0;\n}\n"
    : "+f"(d[0]), "+f"(d[1]), "+f"(d[2]), "+f"(d[3]), "+f"(d[4]), "+f"(d[5]), "+f"(d[6]), "+f"(d[7]), "+f"(d[8]), "+f"(d[9]), "+f"(d[10]), "+f"(d[11]), "+f"(d[12]), "+f"(d[13]), "+f"(d[14]), "+f"(d[15]), "+f"(d[16]), "+f"(d[17]), "+f"(d[18]), "+f"(d[19]), "+f"(d[20]), "+f"(d[21]), "+f"(d[22]), "+f"(d[23]), "+f"(d[24]), "+f"(d[25]), "+f"(d[26]), "+f"(d[27]), "+f"(d[28]), "+f"(d[29]), "+f"(d[30]), "+f"(d[31])
    : "l"(da), "l"(db), "r"(scale_d));
}

__device__ __forceinline__ void wgmma_ss_n32(float (&d)[16], uint64_t da, uint64_t db, int scale_d) {
  asm volatile("{\n.reg .pred p;\nsetp.ne.b32 p, %18, 0;\n"
    "wgmma.mma_async.sync.aligned.m64n32k16.f32.bf16.bf16 {%0, %1, %2, %3, %4, %5, %6, %7, %8, %9, %10, %11, %12, %13, %14, %15}, %16, %17, p, 1, 1, 1, 0;\n}\n"
    : "+f"(d[0]), "+f"(d[1]), "+f"(d[2]), "+f"(d[3]), "+f"(d[4]), "+f"(d[5]), "+f"(d[6]), "+f"(d[7]), "+f"(d[8]), "+f"(d[9]), "+f"(d[10]), "+f"(d[11]), "+f"(d[12]), "+f"(d[13]), "+f"(d[14]), "+f"(d[15])
    : "l"(da), "l"(db), "r"(scale_d));
}

__device__ __forceinline__ void wgmma_ss_n8(float (&d)[4], uint64_t da, uint64_t db, int scale_d) {
  asm volatile("{\n.reg .pred p;\nsetp.ne.b32 p, %6, 0;\n"
    "wgmma.mma_async.sync.aligned.m64n8k16.f32.bf16.bf16 {%0, %1, %2, %3}, %4, %5, p, 1, 1, 1, 0;\n}\n"
    : "+f"(d[0]), "+f"(d[1]), "+f"(d[2]), "+f"(d[3])
    : "l"(da), "l"(db), "r"(scale_d));
}

__device__ __forceinline__ void wgmma_rs_n64(float (&d)[32], uint32_t a0, uint32_t a1, uint32_t a2, uint32_t a3, uint64_t db, int scale_d) {
  asm volatile("{\n.reg .pred p;\nsetp.ne.b32 p, %37, 0;\n"
    "wgmma.mma_async.sync.aligned.m64n64k16.f32.bf16.bf16 {%0, %1, %2, %3, %4, %5, %6, %7, %8, %9, %10, %11, %12, %13, %14, %15, %16, %17, %18, %19, %20, %21, %22, %23, %24, %25, %26, %27, %28, %29, %30, %31}, {%32, %33, %34, %35}, %36, p, 1, 1, 1;\n}\n"
    : "+f"(d[0]), "+f"(d[1]), "+f"(d[2]), "+f"(d[3]), "+f"(d[4]), "+f"(d[5]), "+f"(d[6]), "+f"(d[7]), "+f"(d[8]), "+f"(d[9]), "+f"(d[10]), "+f"(d[11]), "+f"(d[12]), "+f"(d[13]), "+f"(d[14]), "+f"(d[15]), "+f"(d[16]), "+f"(d[17]), "+f"(d[18]), "+f"(d[19]), "+f"(d[20]), "+f"(d[21]), "+f"(d[22]), "+f"(d[23]), "+f"(d[24]), "+f"(d[25]), "+f"(d[26]), "+f"(d[27]), "+f"(d[28]), "+f"(d[29]), "+f"(d[30]), "+f"(d[31])
    : "r"(a0), "r"(a1), "r"(a2), "r"(a3), "l"(db), "r"(scale_d));
}

__host__ __device__ constexpr int unit_slot(int u) {
  constexpr int t[36] = {4, 5, 6, 7, 8, 4, 5, 6, 0, 7, 8, 4,  1, 5, 6, 0, 2, 7, 8, 4, 3, 1, 5, 6,
                         0, 2, 7, 8,  4, 3, 1, 5, 6, 0, 2, 7};
  return t[u];
}
__host__ __device__ constexpr int unit_wait(int u) {
  constexpr int t[36] = {-1, -1, -1, -1, -1, 0, 1, 2, 2, 3, 4, 5,  5, 6, 7, 8, 8, 9, 10, 11, 11, 12, 13, 14,
                         15, 16, 17, 18,  19, 20, 21, 22, 23, 24, 25, 26};
  return t[u];
}

__device__ __forceinline__ uint32_t stage_off(int g, int j) {
  return g == 0 ? (j < 2 ? 8 * kSlot + j * 8192 : 10 * kSlot + (j - 2) * 8192)
                : (j < 2 ? 12 * kSlot + j * 8192 : (j == 2 ? 11 * kSlot + 8192 : 9 * kSlot));
}

struct Params {
  CUtensorMap x, w1, w2, wf, wg, wo, g, out64, out56;
  const void* xptr;
};

__device__ __forceinline__ void init_bar(uint32_t bars, int i) {
  const uint32_t a = bars + i * 8;
  const bool is_e = (i >= kBarE && i < kBarE + 27);
  mbar_init(a, is_e ? 8 : 1);
  if (!is_e) {
    uint32_t bytes = 16384;
    if (i == kBarFX) bytes = 8192;
    if (i == kBarFE) bytes = 8192;
    mbar_expect(a, bytes);
  }
}

__device__ __forceinline__ void store_pieces(const Params& P, uint32_t sb, uint32_t bars, int g, uint32_t cta, int b, int r0, int rvalid) {
  const int rl0 = cta * 16 + g * 8;
  if (rl0 >= rvalid) return;
  const CUtensorMap* omap = (rl0 + 8 <= rvalid) ? &P.out64 : &P.out56;
#pragma unroll
  for (int j = 0; j < 4; j++) {
    mbar_wait(bars + (kBarPR + g * 4 + j) * 8);
    if (elect_one()) {
      tma_store_3d(omap, sb + stage_off(g, j), 0, (b * kT2 + r0 + rl0) * 8, j);
      asm volatile("cp.async.bulk.commit_group;" ::: "memory");
    }
    __syncwarp();
    if (j == 0) TS(2, 12 + g);
    if (j == 3) TS(2, 14 + g);
  }
  if (elect_one()) asm volatile("cp.async.bulk.wait_group.read 0;" ::: "memory");
  __syncwarp();
  if (g == 1) { TS(2, 11); GT(1); TS_DUMP(2, 11, 12); GT_DUMP(1); }
  TS_DUMP(2, 12 + g, 13 + g); TS_DUMP(2, 14 + g, 15 + g);
}

__global__ void __cluster_dims__(2, 1, 1) __launch_bounds__(kThreads, 1)
rnnt_joint_kernel(const __grid_constant__ Params P) {
  extern __shared__ uint8_t smem_raw[];
  const uint32_t sb = (smem_u32(smem_raw) + 1023u) & ~1023u;
  const uint32_t bars = sb + kOffBar;
  const int warp = threadIdx.x >> 5, lane = threadIdx.x & 31;
  uint32_t cta;
  asm volatile("mov.u32 %0, %%cluster_ctarank;" : "=r"(cta));
  const uint32_t peer = cta ^ 1u;
  const int cl = blockIdx.x >> 1;
  const bool ge_cta = cl < 2;
  const int b = ge_cta ? cl : ((cl - 2) >> 5);
  const int r0 = ge_cta ? 32 * kR : ((cl - 2) & 31) * kR;
  const int rvalid = ge_cta ? kT2 - 32 * kR : kR;

  if (warp >= 8) {
    asm volatile("setmaxnreg.dec.sync.aligned.u32 40;");
    if (warp > 8) {
      if (elect_one()) {
#pragma unroll
        for (int i = 0; i < 5; i++) if (57 + (warp - 9) * 5 + i < kBarG) init_bar(bars, 57 + (warp - 9) * 5 + i);
#pragma unroll
        for (int i = 0; i < 5; i++) if (kBarRH + (warp - 9) * 5 + i < kBarGW) mbar_init(bars + (kBarRH + (warp - 9) * 5 + i) * 8, 4);
        if (warp == 11) { mbar_init(bars + kBarGW * 8, 8); mbar_init(bars + kBarFO * 8, 8); mbar_init(bars + kBarGE * 8, 1); mbar_expect(bars + kBarGE * 8, kGEBytes); }
        asm volatile("fence.mbarrier_init.release.cluster;" ::: "memory");
      }
      __syncwarp();
      asm volatile("barrier.cluster.arrive.relaxed.aligned;" ::: "memory");
      if (warp == 11 && lane < 9) asm volatile("prefetch.tensormap [%0];" ::"l"(reinterpret_cast<const CUtensorMap*>(&P) + lane) : "memory");
      __syncwarp();
      asm volatile("barrier.cluster.wait.aligned;" ::: "memory");
      if (warp == 10 && ge_cta) {
        mbar_wait(bars + kBarGW * 8);
        if (elect_one()) {
          __threadfence();
          asm volatile("red.release.gpu.global.add.u32 [%0], 1;" ::"l"(&g_ge_flag[b]) : "memory");
        }
        __syncwarp();
      }
      if (warp == 11) {
        if (elect_one()) {
          const unsigned int ticket = atomicAdd(&g_cta_count, 1u);
          const unsigned int want = (ticket / kNumCtas + 1u) * 2u;
          const long long t0 = clock64();
          unsigned int v;
          do {
            asm volatile("ld.acquire.gpu.global.u32 %0, [%1];" : "=r"(v) : "l"(&g_ge_flag[b]) : "memory");
          } while ((int)(v - want) < 0 && clock64() - t0 < 4000000ll);
          asm volatile("fence.proxy.async;" ::: "memory");
          bulk_load(sb + kOffGE, reinterpret_cast<const char*>(g_ge) + b * kGEBytes, kGEBytes, bars + kBarGE * 8);
        }
        __syncwarp();
        return;
      }
      if (warp == 10) store_pieces(P, sb, bars, 1, cta, b, r0, rvalid);
      if (warp == 10) return;
#pragma unroll
      for (int g = 0; g < 2; g++) {
        mbar_wait(bars + (kBarRH + g) * 8);
        if (elect_one()) {
          const uint32_t src = sb + kSlotH * kSlot + (2 * cta + g) * 8192;
          dsmem_copy(mapa(src, peer), src, 8192, mapa(bars + kBarHX * 8, peer));
        }
        __syncwarp();
      }
#pragma unroll
      for (int g = 0; g < 2; g++) {
        mbar_wait(bars + (kBarRF + g) * 8);
        if (elect_one()) {
          const uint32_t src = sb + kSlotF * kSlot + (2 * cta + g) * 4096;
          dsmem_copy(mapa(src, peer), src, 4096, mapa(bars + kBarFX * 8, peer));
        }
        __syncwarp();
      }
#pragma unroll
      for (int g = 0; g < 2; g++) {
        mbar_wait(bars + (kBarRE + g) * 8);
        if (elect_one())
          dsmem_copy(mapa(sb + kSlotFE * kSlot + (2 * cta + g) * 4096, peer), sb + kSlotH * kSlot + g * 4096, 4096, mapa(bars + kBarFE * 8, peer));
        __syncwarp();
      }
      store_pieces(P, sb, bars, 0, cta, b, r0, rvalid);
      return;
    }
    TS(2, 0);
    GT(0);
    const int par = cta == 0 ? 1 : 0;
    const int q0 = cta == 0 ? 2 * r0 - 2 : 2 * r0 - 1;
    if (elect_one()) {
      mbar_init(bars + kBarX * 8, 1); mbar_expect(bars + kBarX * 8, 16384);
      mbar_init(bars + kBarW * 8, 1); mbar_expect(bars + kBarW * 8, 16384);
      fence_async_smem();
      tma_load_4d(sb, &P.x, bars + kBarX * 8, 0, 1, 2 * r0 - 2, b);
      tma_load_4d(sb + 8192, &P.x, bars + kBarX * 8, 0, 0, 2 * r0 - 1, b);
      tma_load_3d(sb + unit_slot(0) * kSlot, &P.w1, bars + kBarW * 8, 0, 0, 2 * cta);
      TS(2, 7);
#pragma unroll
      for (int i = 1; i < 9; i++) if (i != kBarW) { mbar_init(bars + i * 8, 1); mbar_expect(bars + i * 8, 16384); }
      if (ge_cta) { mbar_init(bars + kBarG * 8, 1); mbar_expect(bars + kBarG * 8, 4 * 16384 + 4096); mbar_init(bars + kBarP0 * 8, 8); }
      asm volatile("fence.mbarrier_init.release.cluster;" ::: "memory");
      fence_async_smem();
      TS(2, 8);
      if (ge_cta) {
        tma_load_3d(sb + kOffG, &P.g, bars + kBarG * 8, 0, b * 8, 0);
#pragma unroll
        for (int i = 0; i < 4; i++) tma_load_3d(sb + (9 + i) * kSlot, &P.wg, bars + kBarG * 8, 0, i * 64, 2 * cta);
      }
#pragma unroll
      for (int u = 1; u < 5; u++)
        tma_load_3d(sb + unit_slot(u) * kSlot, &P.w1, bars + (kBarW + u) * 8, 0, (u % 3) * 256 + (u / 3) * 64, 2 * cta);
      TS(2, 10);
    }
    __syncwarp();
    TS(2, 6);
    cluster_sync_relaxed();
    TS(2, 1);
    if (elect_one()) {
#pragma unroll
      for (int p = 1; p < XFIRST; p++)
        tma_load_4d_mc(sb + p * kSlot + cta * 8192, &P.x, bars + (kBarX + p) * 8, p * 64, par, q0, b, (uint16_t)3);
    }
    __syncwarp();
#pragma unroll
    for (int p = XFIRST; p < 4; p++) {
      if (XSTEP == 1 || ((p - XFIRST) & 1) == 0) mbar_wait(bars + (kBarX + p - XFIRST) * 8);
      if (ge_cta && p == 3) mbar_wait(bars + kBarP0 * 8);
      if (elect_one())
        tma_load_4d_mc(sb + p * kSlot + cta * 8192, &P.x, bars + (kBarX + p) * 8, p * 64, par, q0, b, (uint16_t)3);
      __syncwarp();
    }
#pragma unroll
    for (int u = 5; u < 36; u++) {
      if (unit_wait(u) != unit_wait(u - 1)) mbar_wait(bars + (kBarE + unit_wait(u)) * 8);
      if (WOGATE >= 1 && u == 28) mbar_wait(bars + kBarFX * 8);
      if (WOGATE >= 2 && u == 32) mbar_wait(bars + kBarFE * 8);
      if (elect_one()) {
        const uint32_t dst = sb + unit_slot(u) * kSlot, bar = bars + (kBarW + u) * 8;
        if (u < 12) tma_load_3d(dst, &P.w1, bar, 0, (u % 3) * 256 + (u / 3) * 64, 2 * cta);
        else if (u < 24) tma_load_3d(dst, &P.w2, bar, 0, ((u - 12) % 3) * 256 + ((2 * cta + (u - 12) / 3) & 3) * 64, 2 * cta);
        else if (u < 28) tma_load_3d(dst, &P.wf, bar, 0, ((2 * cta + (u - 24)) & 3) * 64, 2 * cta);
        else tma_load_3d(dst, &P.wo, bar, 0, ((2 * cta + ((u - 28) >> 2) * 2 + ((u - 28) & 1)) & 3) * 64, (((u - 28) >> 1) & 1) * 2);
      }
      __syncwarp();
      if (u == 11) TS(2, 2);
      if (u == 23) TS(2, 3);
      if (u == 27) TS(2, 4);
      if (u == 35) TS(2, 5);
    }
    TS_DUMP(2, 0, 11); GT_DUMP(0);
  } else {
    asm volatile("setmaxnreg.inc.sync.aligned.u32 232;");
    const int wg = warp >> 2, w = warp & 3;
    const int gq = lane >> 2, q = lane & 3;
    const uint32_t panel = 2 * cta + wg;
    const int ch = panel * 64 + w * 16 + gq;
    const uint32_t dA = desc_lo(sb + wg * 8192, 8192);
    const uint32_t dB = desc_lo(sb, 16);
    const uint32_t dBo = desc_lo(sb + cta * 2 * 8192, 16), dBp = desc_lo(sb + (cta ^ 1) * 2 * 8192, 16);
    const uint32_t dFo = desc_lo(sb + cta * 2 * 4096, 16), dFp = desc_lo(sb + (cta ^ 1) * 2 * 4096, 16);
    if (elect_one()) {
#pragma unroll
      for (int i = 0; i < 6; i++) init_bar(bars, 9 + warp * 6 + i);
      asm volatile("fence.mbarrier_init.release.cluster;" ::: "memory");
    }
    __syncwarp();
    cluster_sync_relaxed();
    if (w == 0) TS(wg, 0);

    if (ge_cta) {
      float ga[4];
      mbar_wait(bars + kBarG * 8);
      wg_fence();
#pragma unroll
      for (int i = 0; i < 4; i++) {
#pragma unroll
        for (int s = 0; s < 4; s++)
          wgmma_ss_n8(ga, desc_at(dA, (9 + i) * kSlot + s * 2048), desc_at(dB, kOffG + i * 1024 + s * 32), (i | s) != 0);
      }
      wg_commit();
      wg_wait<0>();
      if (lane == 0) mbar_arrive(bars + kBarP0 * 8);
      float* gp = g_ge + b * (kGEBytes / 4) + ((ch & 7) >> 1) * (kGEPitch / 4) + (ch >> 4) * 4 + (ch & 1);
      gp[(2 * q) * 4 * (kGEPitch / 4)] = ga[0];
      gp[(2 * q + 1) * 4 * (kGEPitch / 4)] = ga[1];
      gp[(2 * q) * 4 * (kGEPitch / 4) + 2] = ga[2];
      gp[(2 * q + 1) * 4 * (kGEPitch / 4) + 2] = ga[3];
      __syncwarp();
      if (lane == 0) mbar_arrive(bars + kBarGW * 8);
    }

    {
      float acc[32];
#pragma unroll
      for (int u = 0; u < 12; u++) {
        const int p = u / 3, tap = u % 3;
        if (SKEW1 > 0 && u == 12 - SKEW1) bar_sync_pred5(wg == 1);
        if (tap == 0) mbar_wait(bars + (kBarX + p) * 8);
        mbar_wait(bars + (kBarW + u) * 8);
        if (u == 0 && w == 0) TS(wg, 1);
        wg_fence();
#pragma unroll
        for (int s = 0; s < 4; s++)
          wgmma_ss_n64(acc, desc_at(dA, unit_slot(u) * kSlot + s * 2048),
                       desc_at(dB, p * kSlot + (tap == 1 ? 8192 : (tap == 2 ? 128 : 0)) + s * 32), (u | s) != 0);
        wg_commit();
        if (SKEW1 > 0 && u == 11) bar_arrive_pred5(wg == 0);
        if (u > 0) {
          wg_wait<1>();
          if (lane == 0) mbar_arrive(bars + (kBarE + u - 1) * 8);
        }
      }
      wg_wait<0>();
      if (lane == 0) mbar_arrive(bars + (kBarE + 11) * 8);
      if (w == 0) TS(wg, 2);
      const uint32_t hp = sb + kSlotH * kSlot + panel * 8192;
      const int mi = lane >> 3, l8 = lane & 7;
#pragma unroll
      for (int jb = 0; jb < 8; jb += 2) {
        uint32_t r[4];
#pragma unroll
        for (int t = 0; t < 2; t++) {
          r[2 * t + 0] = pack_bf16(gelu_tanh(acc[4 * (jb + t) + 0]), gelu_tanh(acc[4 * (jb + t) + 1]));
          r[2 * t + 1] = pack_bf16(gelu_tanh(acc[4 * (jb + t) + 2]), gelu_tanh(acc[4 * (jb + t) + 3]));
        }
        const int n = 8 * (jb + (mi >> 1)) + l8;
        const int row = n >> 1, chunk = 2 * w + (mi & 1);
        stsm_x4_trans(hp + (n & 1) * 4096 + row * 128 + ((chunk ^ (row & 7)) << 4), r[0], r[1], r[2], r[3]);
      }
      __syncwarp();
      if (w == 0) TS(wg, 15);
      fence_async_smem();
      __syncwarp();
      if (lane == 0) mbar_arrive(bars + (kBarRH + wg) * 8);
      if (w == 0) TS(wg, 3);
    }
    {
      float acc[16];
#pragma unroll
      for (int v = 0; v < 12; v++) {
        const int i = v / 3, tap = v % 3;
        if (SKEW2 > 0 && v == 12 - SKEW2) bar_sync_pred6(wg == 1);
        if (v == 0) mbar_wait(bars + kBarRH * 8);
        if (v == 3) mbar_wait(bars + (kBarRH + 1) * 8);
        if (v == 6) { mbar_wait_cluster(bars + kBarHX * 8); if (w == 0) TS(wg, 4); }
        mbar_wait(bars + (kBarW + 12 + v) * 8);
        wg_fence();
#pragma unroll
        for (int s = 0; s < 4; s++)
          wgmma_ss_n32(acc, desc_at(dA, unit_slot(12 + v) * kSlot + s * 2048),
                       desc_at(i < 2 ? dBo : dBp, kSlotH * kSlot + (i & 1) * 8192 + (tap == 1 ? 4096 : (tap == 2 ? 128 : 0)) + s * 32), (v | s) != 0);
        wg_commit();
        if (SKEW2 > 0 && v == 11) bar_arrive_pred6(wg == 0);
        if (v > 0) {
          wg_wait<1>();
          if (lane == 0) mbar_arrive(bars + (kBarE + 12 + v - 1) * 8);
        }
      }
      wg_wait<0>();
      if (lane == 0) mbar_arrive(bars + (kBarE + 23) * 8);
      if (w == 0) TS(wg, 5);
      const uint32_t fp = sb + kSlotF * kSlot + panel * 4096;
      const int mi = lane >> 3, l8 = lane & 7;
#pragma unroll
      for (int jb = 0; jb < 4; jb += 2) {
        uint32_t r[4];
#pragma unroll
        for (int t = 0; t < 2; t++) {
          r[2 * t + 0] = pack_bf16(gelu_tanh(acc[4 * (jb + t) + 0]), gelu_tanh(acc[4 * (jb + t) + 1]));
          r[2 * t + 1] = pack_bf16(gelu_tanh(acc[4 * (jb + t) + 2]), gelu_tanh(acc[4 * (jb + t) + 3]));
        }
        const int n = 8 * (jb + (mi >> 1)) + l8;
        const int chunk = 2 * w + (mi & 1);
        stsm_x4_trans(fp + n * 128 + ((chunk ^ (n & 7)) << 4), r[0], r[1], r[2], r[3]);
      }
      fence_async_smem();
      __syncwarp();
      if (lane == 0) mbar_arrive(bars + (kBarRF + wg) * 8);
      if (w == 0) TS(wg, 6);
    }
    {
      float acc[16];
#pragma unroll
      for (int i = 0; i < 4; i++) {
        if (i < 2) mbar_wait(bars + (kBarRF + i) * 8);
        if (i == 2) { mbar_wait_cluster(bars + kBarFX * 8); if (w == 0) TS(wg, 7); }
        mbar_wait(bars + (kBarW + 24 + i) * 8);
        wg_fence();
#pragma unroll
        for (int s = 0; s < 4; s++)
          wgmma_ss_n32(acc, desc_at(dA, unit_slot(24 + i) * kSlot + s * 2048),
                       desc_at(i < 2 ? dFo : dFp, kSlotF * kSlot + (i & 1) * 4096 + s * 32), (i | s) != 0);
        wg_commit();
        if (i > 0) {
          wg_wait<1>();
          if (lane == 0) mbar_arrive(bars + (kBarE + 24 + i - 1) * 8);
        }
      }
      wg_wait<0>();
      if (w == 0) TS(wg, 8);
      const uint32_t qk = gq >> 1;
      const uint32_t off0 = qk * 128 + (((2 * w) ^ (2 * qk)) << 4) + (gq & 1) * 8;
      const uint32_t off1 = qk * 128 + (((2 * w + 1) ^ (2 * qk)) << 4) + (gq & 1) * 8;
      const uint32_t own = sb + kSlotFE * kSlot + panel * 4096;
      const uint32_t stg = sb + kSlotH * kSlot + wg * 4096;
#pragma unroll
      for (int jb = 0; jb < 4; jb++) {
        const uint32_t base = (((uint32_t)(jb >> 1) == cta) ? own : stg) + (4 * (jb & 1) + q) * 512;
        sts64(base + off0, acc[4 * jb + 0], acc[4 * jb + 1]);
        sts64(base + off1, acc[4 * jb + 2], acc[4 * jb + 3]);
      }
      fence_async_smem();
      __syncwarp();
      if (lane == 0) { mbar_arrive(bars + (kBarRE + wg) * 8); mbar_arrive(bars + kBarFO * 8); }
      if (w == 0) TS(wg, 9);
    }
    const int rl0 = cta * 16 + wg * 8;
    mbar_wait(bars + kBarFO * 8);
    mbar_wait(bars + kBarGE * 8);
    if (!TSPLIT && wg == 1) asm volatile("bar.sync 4, 256;" ::: "memory");
    if (rl0 < rvalid) {
      if (w == 0) TS(wg, 10);
      const uint32_t fe_row = sb + kSlotFE * kSlot + ((4 * wg + w) * 4 + q) * 128;
      const uint32_t fe_h[2] = {fe_row + cta * 8192, fe_row + (cta ^ 1) * 8192};
      const uint32_t ge_h[2] = {sb + kOffGE + lane * kGEPitch + cta * 128, sb + kOffGE + lane * kGEPitch + (cta ^ 1) * 128};
      const int mi = lane >> 3, l8 = lane & 7;
      const uint32_t st = sb + (16 * w + (mi & 1) * 8 + l8) * 128;
      uint32_t A[64];
      float acc[3][32];
#define WO_DESC(j, i) desc_at(dB, unit_slot(28 + ((i) >> 3) * 4 + ((j) >> 1) * 2 + (((i) >> 2) & 1)) * kSlot + ((j) & 1) * 8192 + ((i) & 3) * 2048)
#define WO_MMA(a, j, i) wgmma_rs_n64(acc[a], A[4 * (i)], A[4 * (i) + 1], A[4 * (i) + 2], A[4 * (i) + 3], WO_DESC(j, i), (i) != 0)
#define PIECE_CHUNK(a, j, jb) do { \
        const uint32_t r0_ = pack_bf16(acc[a][4 * (jb) + 0], acc[a][4 * (jb) + 1]), r1_ = pack_bf16(acc[a][4 * (jb) + 2], acc[a][4 * (jb) + 3]); \
        const uint32_t r2_ = pack_bf16(acc[a][4 * (jb) + 4], acc[a][4 * (jb) + 5]), r3_ = pack_bf16(acc[a][4 * (jb) + 6], acc[a][4 * (jb) + 7]); \
        stsm_x4(st + (wg ? stage_off(1, j) : stage_off(0, j)) + ((((jb) + (mi >> 1)) ^ l8) << 4), r0_, r1_, r2_, r3_); } while (0)
#define PIECE_DONE(j) do { fence_async_smem(); __syncwarp(); mbar_arrive_pred(bars + (kBarPR + wg * 4 + (j)) * 8, lane == 0); } while (0)
      {
        constexpr int PD = 3;
        float4 fa[PD], fb[PD], gg[PD];
#pragma unroll
        for (int kk = 0; kk < 8 + PD; kk++) {
          if (kk >= PD) {
            const int k = kk - PD, sl = k % PD;
            A[4 * k + 0] = tanh2_pack(fa[sl].x + gg[sl].x, fa[sl].z + gg[sl].y);
            A[4 * k + 1] = tanh2_pack(fa[sl].y + gg[sl].x, fa[sl].w + gg[sl].y);
            A[4 * k + 2] = tanh2_pack(fb[sl].x + gg[sl].z, fb[sl].z + gg[sl].w);
            A[4 * k + 3] = tanh2_pack(fb[sl].y + gg[sl].z, fb[sl].w + gg[sl].w);
          }
          if (kk < 8) {
            const int sl = kk % PD;
            fa[sl] = lds128(fe_h[0] + (kk >> 2) * 4096 + ((((kk & 3) * 2) ^ (2 * q)) << 4));
            fb[sl] = lds128(fe_h[0] + (kk >> 2) * 4096 + ((((kk & 3) * 2 + 1) ^ (2 * q)) << 4));
            gg[sl] = lds128(ge_h[0] + kk * 16);
          }
        }
      }
#pragma unroll
      for (int i = 0; i < 4; i++) mbar_wait(bars + (kBarW + 28 + i) * 8);
      wg_fence();
#pragma unroll
      for (int i = 0; i < 4; i++) WO_MMA(0, 0, i);
      wg_commit();
      if (ARRPOS == 0) bar_arrive_pred(wg == 0);
      mbar_wait_cluster(bars + kBarFE * 8);
      asm volatile("barrier.cluster.arrive.relaxed.aligned;" ::: "memory");
      wg_fence();
      {
        float4 fa[3], fb[3], gg[3];
#pragma unroll
        for (int t = 0; t < 20; t++) {
          if ((t & 1) == 0 && t < 16) {
            const int kk = t >> 1, sl = kk % 3;
            fa[sl] = lds128(fe_h[1] + (kk >> 2) * 4096 + ((((kk & 3) * 2) ^ (2 * q)) << 4));
            fb[sl] = lds128(fe_h[1] + (kk >> 2) * 4096 + ((((kk & 3) * 2 + 1) ^ (2 * q)) << 4));
            gg[sl] = lds128(ge_h[1] + kk * 16);
          }
          if (t < 4) WO_MMA(0, 0, 4 + t);
          else if (t < 12) WO_MMA(1, 1, t - 4);
          else WO_MMA(2, 2, t - 12);
          if (t >= 4) {
            const int kk = (t - 4) >> 1, sl = kk % 3, k = 8 + kk;
            if ((t & 1) == 0) {
              A[4 * k + 0] = tanh2_pack(fa[sl].x + gg[sl].x, fa[sl].z + gg[sl].y);
              A[4 * k + 1] = tanh2_pack(fa[sl].y + gg[sl].x, fa[sl].w + gg[sl].y);
            } else {
              A[4 * k + 2] = tanh2_pack(fb[sl].x + gg[sl].z, fb[sl].z + gg[sl].w);
              A[4 * k + 3] = tanh2_pack(fb[sl].y + gg[sl].z, fb[sl].w + gg[sl].w);
            }
          }
        }
      }
      wg_commit();
#pragma unroll
      for (int i = 4; i < 8; i++) mbar_wait(bars + (kBarW + 28 + i) * 8);
      wg_fence();
#pragma unroll
      for (int i = 8; i < 16; i++) { WO_MMA(0, 0, i); if (ARRPOS == 1 && i == 15) bar_arrive_pred(wg == 0); }
      wg_commit();
      wg_wait<0>();
#pragma unroll
      for (int jb = 0; jb < 8; jb += 2) PIECE_CHUNK(0, 0, jb);
      PIECE_DONE(0);
      if (w == 0) TS(wg, 11);
      wg_fence();
#pragma unroll
      for (int i = 8; i < 16; i++) WO_MMA(1, 1, i);
      wg_commit();
#pragma unroll
      for (int i = 8; i < 16; i++) {
        WO_MMA(2, 2, i);
        if (i == 9) { wg_commit(); wg_wait<1>(); }
        if (i >= 10 && i < 14) PIECE_CHUNK(1, 1, 2 * (i - 10));
        if (i == 14) PIECE_DONE(1);
      }
      wg_commit();
      if (w == 0) TS(wg, 12);
#pragma unroll
      for (int i = 0; i < 16; i++) {
        WO_MMA(0, 3, i);
        if (i == 1) { wg_commit(); wg_wait<1>(); }
        if (i >= 2 && i < 10 && (i & 1) == 0) PIECE_CHUNK(2, 2, i - 2);
        if (i == 9) PIECE_DONE(2);
      }
      wg_commit();
      if (w == 0) TS(wg, 13);
      wg_wait<0>();
#pragma unroll
      for (int jb = 0; jb < 8; jb += 2) PIECE_CHUNK(0, 3, jb);
      PIECE_DONE(3);
      if (w == 0) TS(wg, 14);
    } else {
      if (wg == 0) asm volatile("bar.arrive 4, 256;" ::: "memory");
      if (TSPLIT && wg == 1) asm volatile("bar.sync 4, 256;" ::: "memory");
      mbar_wait_cluster(bars + kBarFE * 8);
      asm volatile("barrier.cluster.arrive.relaxed.aligned;" ::: "memory");
    }
    asm volatile("barrier.cluster.wait.aligned;" ::: "memory");
    if (w == 0) TS_DUMP(wg, 0, 16);
  }
}

typedef CUresult (*EncodeFn)(CUtensorMap*, CUtensorMapDataType, cuuint32_t, void*, const cuuint64_t*, const cuuint64_t*,
                             const cuuint32_t*, const cuuint32_t*, CUtensorMapInterleave, CUtensorMapSwizzle,
                             CUtensorMapL2promotion, CUtensorMapFloatOOBfill);

void make_map3(EncodeFn enc, CUtensorMap* tm, const void* ptr, uint64_t rows, uint32_t box_rows, uint32_t box_panels) {
  cuuint64_t gd[3] = {64, rows, 4};
  cuuint64_t gs[2] = {512, 128};
  cuuint32_t bd[3] = {64, box_rows, box_panels};
  cuuint32_t es[3] = {1, 1, 1};
  enc(tm, CU_TENSOR_MAP_DATA_TYPE_BFLOAT16, 3, const_cast<void*>(ptr), gd, gs, bd, es, CU_TENSOR_MAP_INTERLEAVE_NONE,
      CU_TENSOR_MAP_SWIZZLE_128B, CU_TENSOR_MAP_L2_PROMOTION_L2_256B, CU_TENSOR_MAP_FLOAT_OOB_FILL_NONE);
}

}

extern "C" void kernel_launch(void* const* d_in, const int* in_sizes, int n_in, void* d_out, int out_size) {
  static EncodeFn enc = nullptr;
  if (!enc) {
    cudaDriverEntryPointQueryResult qr;
    cudaGetDriverEntryPoint("cuTensorMapEncodeTiled", (void**)&enc, cudaEnableDefault, &qr);
    cudaFuncSetAttribute(rnnt_joint_kernel, cudaFuncAttributeMaxDynamicSharedMemorySize, kSmemBytes);
  }
  Params P;
  {
    cuuint64_t gd[4] = {256, 2, 2000, 2};
    cuuint64_t gs[3] = {512, 1024, 4000ull * 512};
    cuuint32_t bd[4] = {64, 1, 64, 1};
    cuuint32_t es[4] = {1, 1, 1, 1};
    enc(&P.x, CU_TENSOR_MAP_DATA_TYPE_BFLOAT16, 4, d_in[0], gd, gs, bd, es, CU_TENSOR_MAP_INTERLEAVE_NONE,
        CU_TENSOR_MAP_SWIZZLE_128B, XPROMO, CU_TENSOR_MAP_FLOAT_OOB_FILL_NONE);
  }
  P.xptr = d_in[0];
  make_map3(enc, &P.w1, d_in[1], 768, 64, 2);
  make_map3(enc, &P.w2, d_in[2], 768, 64, 2);
  make_map3(enc, &P.g, d_in[3], 16, 8, 4);
  make_map3(enc, &P.wf, d_in[4], 256, 64, 2);
  make_map3(enc, &P.wg, d_in[5], 256, 64, 2);
  make_map3(enc, &P.wo, d_in[6], 256, 64, 2);
  make_map3(enc, &P.out64, d_out, 16000, 64, 1);
  make_map3(enc, &P.out56, d_out, 16000, 56, 1);
  rnnt_joint_kernel<<<kNumCtas, kThreads, kSmemBytes>>>(P);
}
```

```cpp
#include <cuda_runtime.h>
#include <cuda_bf16.h>
#include <cuda.h>
#include <stdint.h>

namespace {

constexpr int kT2 = 1000;
constexpr int kR = 31;
constexpr int kNumCtas = 132;
constexpr int kThreads = 384;
constexpr int kSlot = 16384;
constexpr int kSkew = 2;

constexpr int kSlotFE = 9, kSlotF = 10, kSlotH = 11;
constexpr int kOffG = 13 * kSlot;
constexpr int kOffGE = kOffG + 4096;
constexpr int kGEPitch = 272;
constexpr int kGEBytes = 32 * kGEPitch;
constexpr int kOffBar = kOffGE + kGEBytes;
constexpr int kBarX = 0;
constexpr int kBarW = 4;
constexpr int kBarE = 40;
constexpr int kBarHX = 67, kBarFX = 68, kBarFE = 69, kBarG = 70, kBarP0 = 71;
constexpr int kBarRH = 72, kBarRF = 74, kBarRE = 76;
constexpr int kBarPR = 78;
constexpr int kBarGW = 86;
constexpr int kBarFO = 87;
constexpr int kBarGE = 88;
constexpr int kNumBars = 89;
constexpr int kSmemBytes = kOffBar + kNumBars * 8 + 1024;

__device__ __align__(128) float g_ge[2 * kGEBytes / 4];
__device__ unsigned long long g_ge_flag[2];
__device__ unsigned long long g_cta_count;

#define TS(slot_, idx_) do {} while (0)
#define GT(idx_) do {} while (0)
#define TS_DUMP(slot_, lo_, hi_) do {} while (0)
#define GT_DUMP(idx_) do {} while (0)

__device__ __forceinline__ uint32_t smem_u32(const void* p) { return (uint32_t)__cvta_generic_to_shared(p); }
__device__ __forceinline__ void mbar_init(uint32_t a, uint32_t c) { asm volatile("mbarrier.init.shared.b64 [%0], %1;" ::"r"(a), "r"(c) : "memory"); }
__device__ __forceinline__ void mbar_expect(uint32_t a, uint32_t b) { asm volatile("mbarrier.arrive.expect_tx.shared.b64 _, [%0], %1;" ::"r"(a), "r"(b) : "memory"); }
__device__ __forceinline__ void mbar_arrive(uint32_t a) { asm volatile("mbarrier.arrive.shared.b64 _, [%0];" ::"r"(a) : "memory"); }
__device__ __forceinline__ void mbar_arrive_pred(uint32_t a, bool p) {
  asm volatile("{\n.reg .pred q;\nsetp.ne.u32 q, %1, 0;\n@q mbarrier.arrive.shared.b64 _, [%0];\n}\n" ::"r"(a), "r"((uint32_t)p) : "memory");
}
#define DEF_NAMED(ID) \
__device__ __forceinline__ void bar_arrive_pred##ID(bool p) { asm volatile("{\n.reg .pred q;\nsetp.ne.u32 q, %0, 0;\n@q bar.arrive " #ID ", 256;\n}\n" ::"r"((uint32_t)p) : "memory"); } \
__device__ __forceinline__ void bar_sync_pred##ID(bool p) { asm volatile("{\n.reg .pred q;\nsetp.ne.u32 q, %0, 0;\n@q bar.sync " #ID ", 256;\n}\n" ::"r"((uint32_t)p) : "memory"); }
DEF_NAMED(4)
DEF_NAMED(5)
DEF_NAMED(6)
__device__ __forceinline__ bool mbar_try(uint32_t a) {
  uint32_t ok;
  asm volatile("{\n.reg .pred p;\nmbarrier.try_wait.parity.shared.b64 p, [%1], 0;\nselp.u32 %0, 1, 0, p;\n}\n" : "=r"(ok) : "r"(a) : "memory");
  return ok != 0;
}
__device__ __forceinline__ bool mbar_try_cluster(uint32_t a) {
  uint32_t ok;
  asm volatile("{\n.reg .pred p;\nmbarrier.try_wait.parity.acquire.cluster.shared.b64 p, [%1], 0;\nselp.u32 %0, 1, 0, p;\n}\n" : "=r"(ok) : "r"(a) : "memory");
  return ok != 0;
}
__device__ __forceinline__ void mbar_wait_slow(uint32_t a) {
  const long long t0 = clock64();
  while (!mbar_try(a)) { if (clock64() - t0 > 4000000ll) break; }
}
__device__ __forceinline__ void mbar_wait_cluster_slow(uint32_t a) {
  const long long t0 = clock64();
  while (!mbar_try_cluster(a)) { if (clock64() - t0 > 4000000ll) break; }
}
__device__ __forceinline__ void mbar_wait(uint32_t a) { if (!mbar_try(a)) mbar_wait_slow(a); }
__device__ __forceinline__ void mbar_wait_cluster(uint32_t a) { if (!mbar_try_cluster(a)) mbar_wait_cluster_slow(a); }
__device__ __forceinline__ uint32_t mapa(uint32_t a, uint32_t r) { uint32_t d; asm volatile("mapa.shared::cluster.u32 %0, %1, %2;" : "=r"(d) : "r"(a), "r"(r)); return d; }
__device__ __forceinline__ bool elect_one() { uint32_t p; asm volatile("{\n.reg .pred P;\nelect.sync _|P, 0xffffffff;\nselp.u32 %0, 1, 0, P;\n}\n" : "=r"(p)); return p != 0; }
__device__ __forceinline__ void fence_async_smem() { asm volatile("fence.proxy.async.shared::cta;" ::: "memory"); }
__device__ __forceinline__ void cluster_sync_relaxed() { asm volatile("barrier.cluster.arrive.relaxed.aligned;\nbarrier.cluster.wait.aligned;" ::: "memory"); }
__device__ __forceinline__ void wg_fence() { asm volatile("wgmma.fence.sync.aligned;" ::: "memory"); }
__device__ __forceinline__ void wg_commit() { asm volatile("wgmma.commit_group.sync.aligned;" ::: "memory"); }
template <int N> __device__ __forceinline__ void wg_wait() { asm volatile("wgmma.wait_group.sync.aligned %0;" ::"n"(N) : "memory"); }

__device__ __forceinline__ void tma_load_3d(uint32_t dst, const CUtensorMap* tm, uint32_t bar, int c0, int c1, int c2) {
  asm volatile("cp.async.bulk.tensor.3d.shared::cluster.global.mbarrier::complete_tx::bytes [%0], [%1, {%3, %4, %5}], [%2];"
               ::"r"(dst), "l"(tm), "r"(bar), "r"(c0), "r"(c1), "r"(c2) : "memory");
}
__device__ __forceinline__ void tma_load_4d(uint32_t dst, const CUtensorMap* tm, uint32_t bar, int c0, int c1, int c2, int c3) {
  asm volatile("cp.async.bulk.tensor.4d.shared::cluster.global.mbarrier::complete_tx::bytes [%0], [%1, {%3, %4, %5, %6}], [%2];"
               ::"r"(dst), "l"(tm), "r"(bar), "r"(c0), "r"(c1), "r"(c2), "r"(c3) : "memory");
}
__device__ __forceinline__ void tma_load_4d_mc(uint32_t dst, const CUtensorMap* tm, uint32_t bar, int c0, int c1, int c2, int c3, uint16_t mask) {
  asm volatile("cp.async.bulk.tensor.4d.shared::cluster.global.mbarrier::complete_tx::bytes.multicast::cluster [%0], [%1, {%3, %4, %5, %6}], [%2], %7;"
               ::"r"(dst), "l"(tm), "r"(bar), "r"(c0), "r"(c1), "r"(c2), "r"(c3), "h"(mask) : "memory");
}
__device__ __forceinline__ void tma_store_3d(const CUtensorMap* tm, uint32_t src, int c0, int c1, int c2) {
  asm volatile("cp.async.bulk.tensor.3d.global.shared::cta.bulk_group [%0, {%2, %3, %4}], [%1];"
               ::"l"(tm), "r"(src), "r"(c0), "r"(c1), "r"(c2) : "memory");
}
__device__ __forceinline__ void bulk_load(uint32_t dst, const void* src, uint32_t bytes, uint32_t bar) {
  asm volatile("cp.async.bulk.shared::cluster.global.mbarrier::complete_tx::bytes [%0], [%1], %2, [%3];"
               ::"r"(dst), "l"(src), "r"(bytes), "r"(bar) : "memory");
}
__device__ __forceinline__ void dsmem_copy(uint32_t dst_remote, uint32_t src, uint32_t bytes, uint32_t bar_remote) {
  asm volatile("cp.async.bulk.shared::cluster.shared::cta.mbarrier::complete_tx::bytes [%0], [%1], %2, [%3];"
               ::"r"(dst_remote), "r"(src), "r"(bytes), "r"(bar_remote) : "memory");
}
__device__ __forceinline__ void stsm_x4_trans(uint32_t addr, uint32_t r0, uint32_t r1, uint32_t r2, uint32_t r3) {
  asm volatile("stmatrix.sync.aligned.m8n8.x4.trans.shared.b16 [%0], {%1, %2, %3, %4};" ::"r"(addr), "r"(r0), "r"(r1), "r"(r2), "r"(r3) : "memory");
}
__device__ __forceinline__ void stsm_x4(uint32_t addr, uint32_t r0, uint32_t r1, uint32_t r2, uint32_t r3) {
  asm volatile("stmatrix.sync.aligned.m8n8.x4.shared.b16 [%0], {%1, %2, %3, %4};" ::"r"(addr), "r"(r0), "r"(r1), "r"(r2), "r"(r3) : "memory");
}
__device__ __forceinline__ float4 lds128(uint32_t a) { float4 v; asm volatile("ld.shared.v4.f32 {%0, %1, %2, %3}, [%4];" : "=f"(v.x), "=f"(v.y), "=f"(v.z), "=f"(v.w) : "r"(a) : "memory"); return v; }
__device__ __forceinline__ void sts64(uint32_t a, float x, float y) { asm volatile("st.shared.v2.f32 [%0], {%1, %2};" ::"r"(a), "f"(x), "f"(y) : "memory"); }
__device__ __forceinline__ float tanh_fast(float x) { float y; asm("tanh.approx.f32 %0, %1;" : "=f"(y) : "f"(x)); return y; }
__device__ __forceinline__ uint32_t tanh2_pack(float lo, float hi) {
  uint32_t r;
  asm volatile("{\n.reg .f32 a, b;\ntanh.approx.f32 a, %1;\ntanh.approx.f32 b, %2;\ncvt.rn.bf16x2.f32 %0, b, a;\n}\n" : "=r"(r) : "f"(lo), "f"(hi));
  return r;
}
__device__ __forceinline__ uint32_t pack_bf16(float lo, float hi) { uint32_t r; asm("cvt.rn.bf16x2.f32 %0, %1, %2;" : "=r"(r) : "f"(hi), "f"(lo)); return r; }
__device__ __forceinline__ float gelu_tanh(float x) {
  const float k0 = 0.7978845608028654f, k1 = 0.7978845608028654f * 0.044715f;
  float u = x * fmaf(x * x, k1, k0);
  float hx = 0.5f * x;
  return fmaf(hx, tanh_fast(u), hx);
}

__device__ __forceinline__ uint32_t desc_lo(uint32_t addr, uint32_t lbo) { return ((addr & 0x3FFFF) >> 4) | ((lbo >> 4) << 16); }
__device__ __forceinline__ uint64_t desc_at(uint32_t lo, uint32_t off) { return ((uint64_t)0x40000040u << 32) | (uint64_t)(lo + (off >> 4)); }

__device__ __forceinline__ void wgmma_ss_n64(float (&d)[32], uint64_t da, uint64_t db, int scale_d) {
  asm volatile("{\n.reg .pred p;\nsetp.ne.b32 p, %34, 0;\n"
    "wgmma.mma_async.sync.aligned.m64n64k16.f32.bf16.bf16 {%0, %1, %2, %3, %4, %5, %6, %7, %8, %9, %10, %11, %12, %13, %14, %15, %16, %17, %18, %19, %20, %21, %22, %23, %24, %25, %26, %27, %28, %29, %30, %31}, %32, %33, p, 1, 1, 1, 0;\n}\n"
    : "+f"(d[0]), "+f"(d[1]), "+f"(d[2]), "+f"(d[3]), "+f"(d[4]), "+f"(d[5]), "+f"(d[6]), "+f"(d[7]), "+f"(d[8]), "+f"(d[9]), "+f"(d[10]), "+f"(d[11]), "+f"(d[12]), "+f"(d[13]), "+f"(d[14]), "+f"(d[15]), "+f"(d[16]), "+f"(d[17]), "+f"(d[18]), "+f"(d[19]), "+f"(d[20]), "+f"(d[21]), "+f"(d[22]), "+f"(d[23]), "+f"(d[24]), "+f"(d[25]), "+f"(d[26]), "+f"(d[27]), "+f"(d[28]), "+f"(d[29]), "+f"(d[30]), "+f"(d[31])
    : "l"(da), "l"(db), "r"(scale_d));
}

__device__ __forceinline__ void wgmma_ss_n32(float (&d)[16], uint64_t da, uint64_t db, int scale_d) {
  asm volatile("{\n.reg .pred p;\nsetp.ne.b32 p, %18, 0;\n"
    "wgmma.mma_async.sync.aligned.m64n32k16.f32.bf16.bf16 {%0, %1, %2, %3, %4, %5, %6, %7, %8, %9, %10, %11, %12, %13, %14, %15}, %16, %17, p, 1, 1, 1, 0;\n}\n"
    : "+f"(d[0]), "+f"(d[1]), "+f"(d[2]), "+f"(d[3]), "+f"(d[4]), "+f"(d[5]), "+f"(d[6]), "+f"(d[7]), "+f"(d[8]), "+f"(d[9]), "+f"(d[10]), "+f"(d[11]), "+f"(d[12]), "+f"(d[13]), "+f"(d[14]), "+f"(d[15])
    : "l"(da), "l"(db), "r"(scale_d));
}

__device__ __forceinline__ void wgmma_ss_n8(float (&d)[4], uint64_t da, uint64_t db, int scale_d) {
  asm volatile("{\n.reg .pred p;\nsetp.ne.b32 p, %6, 0;\n"
    "wgmma.mma_async.sync.aligned.m64n8k16.f32.bf16.bf16 {%0, %1, %2, %3}, %4, %5, p, 1, 1, 1, 0;\n}\n"
    : "+f"(d[0]), "+f"(d[1]), "+f"(d[2]), "+f"(d[3])
    : "l"(da), "l"(db), "r"(scale_d));
}

__device__ __forceinline__ void wgmma_rs_n64(float (&d)[32], uint32_t a0, uint32_t a1, uint32_t a2, uint32_t a3, uint64_t db, int scale_d) {
  asm volatile("{\n.reg .pred p;\nsetp.ne.b32 p, %37, 0;\n"
    "wgmma.mma_async.sync.aligned.m64n64k16.f32.bf16.bf16 {%0, %1, %2, %3, %4, %5, %6, %7, %8, %9, %10, %11, %12, %13, %14, %15, %16, %17, %18, %19, %20, %21, %22, %23, %24, %25, %26, %27, %28, %29, %30, %31}, {%32, %33, %34, %35}, %36, p, 1, 1, 1;\n}\n"
    : "+f"(d[0]), "+f"(d[1]), "+f"(d[2]), "+f"(d[3]), "+f"(d[4]), "+f"(d[5]), "+f"(d[6]), "+f"(d[7]), "+f"(d[8]), "+f"(d[9]), "+f"(d[10]), "+f"(d[11]), "+f"(d[12]), "+f"(d[13]), "+f"(d[14]), "+f"(d[15]), "+f"(d[16]), "+f"(d[17]), "+f"(d[18]), "+f"(d[19]), "+f"(d[20]), "+f"(d[21]), "+f"(d[22]), "+f"(d[23]), "+f"(d[24]), "+f"(d[25]), "+f"(d[26]), "+f"(d[27]), "+f"(d[28]), "+f"(d[29]), "+f"(d[30]), "+f"(d[31])
    : "r"(a0), "r"(a1), "r"(a2), "r"(a3), "l"(db), "r"(scale_d));
}

__host__ __device__ constexpr int unit_slot(int u) {
  constexpr int t[36] = {4, 5, 6, 7, 8, 4, 5, 6, 0, 7, 8, 4,  1, 5, 6, 0, 2, 7, 8, 4, 3, 1, 5, 6,
                         0, 2, 7, 8,  4, 3, 1, 5, 6, 0, 2, 7};
  return t[u];
}
__host__ __device__ constexpr int unit_wait(int u) {
  constexpr int t[36] = {-1, -1, -1, -1, -1, 0, 1, 2, 2, 3, 4, 5,  5, 6, 7, 8, 8, 9, 10, 11, 11, 12, 13, 14,
                         15, 16, 17, 18,  19, 20, 21, 22, 23, 24, 25, 26};
  return t[u];
}

__device__ __forceinline__ uint32_t stage_off(int g, int j) {
  return g == 0 ? (j < 2 ? 8 * kSlot + j * 8192 : 10 * kSlot + (j - 2) * 8192)
                : (j < 2 ? 12 * kSlot + j * 8192 : (j == 2 ? 11 * kSlot + 8192 : 9 * kSlot));
}

struct Params {
  CUtensorMap x, w1, w2, wf, wg, wo, g, out64, out56;
};

__device__ __forceinline__ void init_bar(uint32_t bars, int i) {
  const uint32_t a = bars + i * 8;
  const bool is_e = (i >= kBarE && i < kBarE + 27);
  mbar_init(a, is_e ? 8 : 1);
  if (!is_e) {
    uint32_t bytes = 16384;
    if (i == kBarFX) bytes = 8192;
    if (i == kBarFE) bytes = 8192;
    mbar_expect(a, bytes);
  }
}

__device__ __forceinline__ void store_pieces(const Params& P, uint32_t sb, uint32_t bars, int g, uint32_t cta, int b, int r0, int rvalid) {
  const int rl0 = cta * 16 + g * 8;
  if (rl0 >= rvalid) return;
  const CUtensorMap* omap = (rl0 + 8 <= rvalid) ? &P.out64 : &P.out56;
#pragma unroll
  for (int j = 0; j < 4; j++) {
    mbar_wait(bars + (kBarPR + g * 4 + j) * 8);
    if (elect_one()) {
      tma_store_3d(omap, sb + stage_off(g, j), 0, (b * kT2 + r0 + rl0) * 8, j);
      asm volatile("cp.async.bulk.commit_group;" ::: "memory");
    }
    __syncwarp();
    if (j == 0) TS(2, 12 + g);
    if (j == 3) TS(2, 14 + g);
  }
  if (elect_one()) asm volatile("cp.async.bulk.wait_group.read 0;" ::: "memory");
  __syncwarp();
  if (g == 1) { TS(2, 11); GT(1); TS_DUMP(2, 11, 12); GT_DUMP(1); }
  TS_DUMP(2, 12 + g, 13 + g); TS_DUMP(2, 14 + g, 15 + g);
}

__global__ void __cluster_dims__(2, 1, 1) __launch_bounds__(kThreads, 1)
rnnt_joint_kernel(const __grid_constant__ Params P) {
  extern __shared__ uint8_t smem_raw[];
  const uint32_t sb = (smem_u32(smem_raw) + 1023u) & ~1023u;
  const uint32_t bars = sb + kOffBar;
  const int warp = threadIdx.x >> 5, lane = threadIdx.x & 31;
  uint32_t cta;
  asm volatile("mov.u32 %0, %%cluster_ctarank;" : "=r"(cta));
  const uint32_t peer = cta ^ 1u;
  const int cl = blockIdx.x >> 1;
  const bool ge_cta = cl < 2;
  const int b = ge_cta ? cl : ((cl - 2) >> 5);
  const int r0 = ge_cta ? 32 * kR : ((cl - 2) & 31) * kR;
  const int rvalid = ge_cta ? kT2 - 32 * kR : kR;

  if (warp >= 8) {
    asm volatile("setmaxnreg.dec.sync.aligned.u32 40;");
    if (warp > 8) {
      if (elect_one()) {
#pragma unroll
        for (int i = 0; i < 5; i++) if (57 + (warp - 9) * 5 + i < kBarG) init_bar(bars, 57 + (warp - 9) * 5 + i);
#pragma unroll
        for (int i = 0; i < 5; i++) if (kBarRH + (warp - 9) * 5 + i < kBarGW) mbar_init(bars + (kBarRH + (warp - 9) * 5 + i) * 8, 4);
        if (warp == 11) { mbar_init(bars + kBarGW * 8, 8); mbar_init(bars + kBarFO * 8, 8); mbar_init(bars + kBarGE * 8, 1); mbar_expect(bars + kBarGE * 8, kGEBytes); }
        asm volatile("fence.mbarrier_init.release.cluster;" ::: "memory");
      }
      __syncwarp();
      asm volatile("barrier.cluster.arrive.relaxed.aligned;" ::: "memory");
      if (warp == 11 && lane < 9) asm volatile("prefetch.tensormap [%0];" ::"l"(reinterpret_cast<const CUtensorMap*>(&P) + lane) : "memory");
      __syncwarp();
      asm volatile("barrier.cluster.wait.aligned;" ::: "memory");
      if (warp == 10 && ge_cta) {
        mbar_wait(bars + kBarGW * 8);
        if (elect_one()) {
          __threadfence();
          asm volatile("red.release.gpu.global.add.u64 [%0], 1;" ::"l"(&g_ge_flag[b]) : "memory");
        }
        __syncwarp();
      }
      if (warp == 11) {
        if (elect_one()) {
          const unsigned long long ticket = atomicAdd(&g_cta_count, 1ull);
          const unsigned long long want = (ticket / kNumCtas + 1ull) * 2ull;
          const long long t0 = clock64();
          unsigned long long v;
          do {
            asm volatile("ld.acquire.gpu.global.u64 %0, [%1];" : "=l"(v) : "l"(&g_ge_flag[b]) : "memory");
          } while (v < want && clock64() - t0 < 4000000ll);
          asm volatile("fence.proxy.async;" ::: "memory");
          bulk_load(sb + kOffGE, reinterpret_cast<const char*>(g_ge) + b * kGEBytes, kGEBytes, bars + kBarGE * 8);
        }
        __syncwarp();
        return;
      }
      if (warp == 10) store_pieces(P, sb, bars, 1, cta, b, r0, rvalid);
      if (warp == 10) return;
#pragma unroll
      for (int g = 0; g < 2; g++) {
        mbar_wait(bars + (kBarRH + g) * 8);
        if (elect_one()) {
          const uint32_t src = sb + kSlotH * kSlot + (2 * cta + g) * 8192;
          dsmem_copy(mapa(src, peer), src, 8192, mapa(bars + kBarHX * 8, peer));
        }
        __syncwarp();
      }
#pragma unroll
      for (int g = 0; g < 2; g++) {
        mbar_wait(bars + (kBarRF + g) * 8);
        if (elect_one()) {
          const uint32_t src = sb + kSlotF * kSlot + (2 * cta + g) * 4096;
          dsmem_copy(mapa(src, peer), src, 4096, mapa(bars + kBarFX * 8, peer));
        }
        __syncwarp();
      }
#pragma unroll
      for (int g = 0; g < 2; g++) {
        mbar_wait(bars + (kBarRE + g) * 8);
        if (elect_one())
          dsmem_copy(mapa(sb + kSlotFE * kSlot + (2 * cta + g) * 4096, peer), sb + kSlotH * kSlot + g * 4096, 4096, mapa(bars + kBarFE * 8, peer));
        __syncwarp();
      }
      store_pieces(P, sb, bars, 0, cta, b, r0, rvalid);
      return;
    }
    TS(2, 0);
    GT(0);
    const int par = cta == 0 ? 1 : 0;
    const int q0 = cta == 0 ? 2 * r0 - 2 : 2 * r0 - 1;
    if (elect_one()) {
      mbar_init(bars + kBarX * 8, 1); mbar_expect(bars + kBarX * 8, 16384);
      mbar_init(bars + kBarW * 8, 1); mbar_expect(bars + kBarW * 8, 16384);
      fence_async_smem();
      tma_load_4d(sb, &P.x, bars + kBarX * 8, 0, 1, 2 * r0 - 2, b);
      tma_load_4d(sb + 8192, &P.x, bars + kBarX * 8, 0, 0, 2 * r0 - 1, b);
      tma_load_3d(sb + unit_slot(0) * kSlot, &P.w1, bars + kBarW * 8, 0, 0, 2 * cta);
      TS(2, 7);
#pragma unroll
      for (int i = 1; i < 9; i++) if (i != kBarW) { mbar_init(bars + i * 8, 1); mbar_expect(bars + i * 8, 16384); }
      if (ge_cta) { mbar_init(bars + kBarG * 8, 1); mbar_expect(bars + kBarG * 8, 4 * 16384 + 4096); mbar_init(bars + kBarP0 * 8, 8); }
      asm volatile("fence.mbarrier_init.release.cluster;" ::: "memory");
      fence_async_smem();
      TS(2, 8);
      if (ge_cta) {
        tma_load_3d(sb + kOffG, &P.g, bars + kBarG * 8, 0, b * 8, 0);
#pragma unroll
        for (int i = 0; i < 4; i++) tma_load_3d(sb + (9 + i) * kSlot, &P.wg, bars + kBarG * 8, 0, i * 64, 2 * cta);
      }
#pragma unroll
      for (int u = 1; u < 5; u++)
        tma_load_3d(sb + unit_slot(u) * kSlot, &P.w1, bars + (kBarW + u) * 8, 0, (u % 3) * 256 + (u / 3) * 64, 2 * cta);
      TS(2, 10);
    }
    __syncwarp();
    TS(2, 6);
    cluster_sync_relaxed();
    TS(2, 1);
    if (elect_one()) {
#pragma unroll
      for (int p = 1; p < 3; p++)
        tma_load_4d_mc(sb + p * kSlot + cta * 8192, &P.x, bars + (kBarX + p) * 8, p * 64, par, q0, b, (uint16_t)3);
    }
    __syncwarp();
    mbar_wait(bars + kBarX * 8);
    if (ge_cta) mbar_wait(bars + kBarP0 * 8);
    if (elect_one()) tma_load_4d_mc(sb + 3 * kSlot + cta * 8192, &P.x, bars + (kBarX + 3) * 8, 3 * 64, par, q0, b, (uint16_t)3);
    __syncwarp();
#pragma unroll
    for (int u = 5; u < 36; u++) {
      if (unit_wait(u) != unit_wait(u - 1)) mbar_wait(bars + (kBarE + unit_wait(u)) * 8);
      if (u == 28) mbar_wait(bars + kBarFX * 8);
      if (elect_one()) {
        const uint32_t dst = sb + unit_slot(u) * kSlot, bar = bars + (kBarW + u) * 8;
        if (u < 12) tma_load_3d(dst, &P.w1, bar, 0, (u % 3) * 256 + (u / 3) * 64, 2 * cta);
        else if (u < 24) tma_load_3d(dst, &P.w2, bar, 0, ((u - 12) % 3) * 256 + ((2 * cta + (u - 12) / 3) & 3) * 64, 2 * cta);
        else if (u < 28) tma_load_3d(dst, &P.wf, bar, 0, ((2 * cta + (u - 24)) & 3) * 64, 2 * cta);
        else tma_load_3d(dst, &P.wo, bar, 0, ((2 * cta + (u - 28)) & 3) * 64, ((u - 28) >> 2) * 2);
      }
      __syncwarp();
      if (u == 11) TS(2, 2);
      if (u == 23) TS(2, 3);
      if (u == 27) TS(2, 4);
      if (u == 35) TS(2, 5);
    }
    TS_DUMP(2, 0, 11); GT_DUMP(0);
  } else {
    asm volatile("setmaxnreg.inc.sync.aligned.u32 232;");
    const int wg = warp >> 2, w = warp & 3;
    const int gq = lane >> 2, q = lane & 3;
    const uint32_t panel = 2 * cta + wg;
    const int ch = panel * 64 + w * 16 + gq;
    const uint32_t dA = desc_lo(sb + wg * 8192, 8192);
    const uint32_t dB = desc_lo(sb, 16);
    const uint32_t dBo = desc_lo(sb + cta * 2 * 8192, 16), dBp = desc_lo(sb + (cta ^ 1) * 2 * 8192, 16);
    const uint32_t dFo = desc_lo(sb + cta * 2 * 4096, 16), dFp = desc_lo(sb + (cta ^ 1) * 2 * 4096, 16);
    if (elect_one()) {
#pragma unroll
      for (int i = 0; i < 6; i++) init_bar(bars, 9 + warp * 6 + i);
      asm volatile("fence.mbarrier_init.release.cluster;" ::: "memory");
    }
    __syncwarp();
    cluster_sync_relaxed();
    if (w == 0) TS(wg, 0);

    if (ge_cta) {
      float ga[4];
      mbar_wait(bars + kBarG * 8);
      wg_fence();
#pragma unroll
      for (int i = 0; i < 4; i++) {
#pragma unroll
        for (int s = 0; s < 4; s++)
          wgmma_ss_n8(ga, desc_at(dA, (9 + i) * kSlot + s * 2048), desc_at(dB, kOffG + i * 1024 + s * 32), (i | s) != 0);
      }
      wg_commit();
      wg_wait<0>();
      if (lane == 0) mbar_arrive(bars + kBarP0 * 8);
      float* gp = g_ge + b * (kGEBytes / 4) + ((ch & 7) >> 1) * (kGEPitch / 4) + (ch >> 4) * 4 + (ch & 1);
      gp[(2 * q) * 4 * (kGEPitch / 4)] = ga[0];
      gp[(2 * q + 1) * 4 * (kGEPitch / 4)] = ga[1];
      gp[(2 * q) * 4 * (kGEPitch / 4) + 2] = ga[2];
      gp[(2 * q + 1) * 4 * (kGEPitch / 4) + 2] = ga[3];
      __syncwarp();
      if (lane == 0) mbar_arrive(bars + kBarGW * 8);
    }

    {
      float acc[32];
#pragma unroll
      for (int u = 0; u < 12; u++) {
        const int p = u / 3, tap = u % 3;
        if (u == 12 - kSkew) bar_sync_pred5(wg == 1);
        if (tap == 0) mbar_wait(bars + (kBarX + p) * 8);
        mbar_wait(bars + (kBarW + u) * 8);
        if (u == 0 && w == 0) TS(wg, 1);
        wg_fence();
#pragma unroll
        for (int s = 0; s < 4; s++)
          wgmma_ss_n64(acc, desc_at(dA, unit_slot(u) * kSlot + s * 2048),
                       desc_at(dB, p * kSlot + (tap == 1 ? 8192 : (tap == 2 ? 128 : 0)) + s * 32), (u | s) != 0);
        wg_commit();
        if (u == 11) bar_arrive_pred5(wg == 0);
        if (u > 0) {
          wg_wait<1>();
          if (lane == 0) mbar_arrive(bars + (kBarE + u - 1) * 8);
        }
      }
      wg_wait<0>();
      if (lane == 0) mbar_arrive(bars + (kBarE + 11) * 8);
      if (w == 0) TS(wg, 2);
      const uint32_t hp = sb + kSlotH * kSlot + panel * 8192;
      const int mi = lane >> 3, l8 = lane & 7;
#pragma unroll
      for (int jb = 0; jb < 8; jb += 2) {
        uint32_t r[4];
#pragma unroll
        for (int t = 0; t < 2; t++) {
          r[2 * t + 0] = pack_bf16(gelu_tanh(acc[4 * (jb + t) + 0]), gelu_tanh(acc[4 * (jb + t) + 1]));
          r[2 * t + 1] = pack_bf16(gelu_tanh(acc[4 * (jb + t) + 2]), gelu_tanh(acc[4 * (jb + t) + 3]));
        }
        const int n = 8 * (jb + (mi >> 1)) + l8;
        const int row = n >> 1, chunk = 2 * w + (mi & 1);
        stsm_x4_trans(hp + (n & 1) * 4096 + row * 128 + ((chunk ^ (row & 7)) << 4), r[0], r[1], r[2], r[3]);
      }
      __syncwarp();
      if (w == 0) TS(wg, 15);
      fence_async_smem();
      __syncwarp();
      if (lane == 0) mbar_arrive(bars + (kBarRH + wg) * 8);
      if (w == 0) TS(wg, 3);
    }
    {
      float acc[16];
#pragma unroll
      for (int v = 0; v < 12; v++) {
        const int i = v / 3, tap = v % 3;
        if (v == 12 - kSkew) bar_sync_pred6(wg == 1);
        if (v == 0) mbar_wait(bars + kBarRH * 8);
        if (v == 3) mbar_wait(bars + (kBarRH + 1) * 8);
        if (v == 6) { mbar_wait_cluster(bars + kBarHX * 8); if (w == 0) TS(wg, 4); }
        mbar_wait(bars + (kBarW + 12 + v) * 8);
        wg_fence();
#pragma unroll
        for (int s = 0; s < 4; s++)
          wgmma_ss_n32(acc, desc_at(dA, unit_slot(12 + v) * kSlot + s * 2048),
                       desc_at(i < 2 ? dBo : dBp, kSlotH * kSlot + (i & 1) * 8192 + (tap == 1 ? 4096 : (tap == 2 ? 128 : 0)) + s * 32), (v | s) != 0);
        wg_commit();
        if (v == 11) bar_arrive_pred6(wg == 0);
        if (v > 0) {
          wg_wait<1>();
          if (lane == 0) mbar_arrive(bars + (kBarE + 12 + v - 1) * 8);
        }
      }
      wg_wait<0>();
      if (lane == 0) mbar_arrive(bars + (kBarE + 23) * 8);
      if (w == 0) TS(wg, 5);
      const uint32_t fp = sb + kSlotF * kSlot + panel * 4096;
      const int mi = lane >> 3, l8 = lane & 7;
#pragma unroll
      for (int jb = 0; jb < 4; jb += 2) {
        uint32_t r[4];
#pragma unroll
        for (int t = 0; t < 2; t++) {
          r[2 * t + 0] = pack_bf16(gelu_tanh(acc[4 * (jb + t) + 0]), gelu_tanh(acc[4 * (jb + t) + 1]));
          r[2 * t + 1] = pack_bf16(gelu_tanh(acc[4 * (jb + t) + 2]), gelu_tanh(acc[4 * (jb + t) + 3]));
        }
        const int n = 8 * (jb + (mi >> 1)) + l8;
        const int chunk = 2 * w + (mi & 1);
        stsm_x4_trans(fp + n * 128 + ((chunk ^ (n & 7)) << 4), r[0], r[1], r[2], r[3]);
      }
      fence_async_smem();
      __syncwarp();
      if (lane == 0) mbar_arrive(bars + (kBarRF + wg) * 8);
      if (w == 0) TS(wg, 6);
    }
    {
      float acc[16];
#pragma unroll
      for (int i = 0; i < 4; i++) {
        if (i < 2) mbar_wait(bars + (kBarRF + i) * 8);
        if (i == 2) { mbar_wait_cluster(bars + kBarFX * 8); if (w == 0) TS(wg, 7); }
        mbar_wait(bars + (kBarW + 24 + i) * 8);
        wg_fence();
#pragma unroll
        for (int s = 0; s < 4; s++)
          wgmma_ss_n32(acc, desc_at(dA, unit_slot(24 + i) * kSlot + s * 2048),
                       desc_at(i < 2 ? dFo : dFp, kSlotF * kSlot + (i & 1) * 4096 + s * 32), (i | s) != 0);
        wg_commit();
        if (i > 0) {
          wg_wait<1>();
          if (lane == 0) mbar_arrive(bars + (kBarE + 24 + i - 1) * 8);
        }
      }
      wg_wait<0>();
      if (w == 0) TS(wg, 8);
      const uint32_t qk = gq >> 1;
      const uint32_t off0 = qk * 128 + (((2 * w) ^ (2 * qk)) << 4) + (gq & 1) * 8;
      const uint32_t off1 = qk * 128 + (((2 * w + 1) ^ (2 * qk)) << 4) + (gq & 1) * 8;
      const uint32_t own = sb + kSlotFE * kSlot + panel * 4096;
      const uint32_t stg = sb + kSlotH * kSlot + wg * 4096;
#pragma unroll
      for (int jb = 0; jb < 4; jb++) {
        const uint32_t base = (((uint32_t)(jb >> 1) == cta) ? own : stg) + (4 * (jb & 1) + q) * 512;
        sts64(base + off0, acc[4 * jb + 0], acc[4 * jb + 1]);
        sts64(base + off1, acc[4 * jb + 2], acc[4 * jb + 3]);
      }
      fence_async_smem();
      __syncwarp();
      if (lane == 0) { mbar_arrive(bars + (kBarRE + wg) * 8); mbar_arrive(bars + kBarFO * 8); }
      if (w == 0) TS(wg, 9);
    }
    const int rl0 = cta * 16 + wg * 8;
    mbar_wait(bars + kBarFO * 8);
    mbar_wait(bars + kBarGE * 8);
    if (wg == 1) asm volatile("bar.sync 4, 256;" ::: "memory");
    if (rl0 < rvalid) {
      if (w == 0) TS(wg, 10);
      const uint32_t fe_row = sb + kSlotFE * kSlot + ((4 * wg + w) * 4 + q) * 128;
      const uint32_t fe_h[2] = {fe_row + cta * 8192, fe_row + (cta ^ 1) * 8192};
      const uint32_t ge_h[2] = {sb + kOffGE + lane * kGEPitch + cta * 128, sb + kOffGE + lane * kGEPitch + (cta ^ 1) * 128};
      const int mi = lane >> 3, l8 = lane & 7;
      const uint32_t st = sb + (16 * w + (mi & 1) * 8 + l8) * 128;
      uint32_t A[64];
      float acc[2][32];
      {
        constexpr int PD = 3;
        float4 fa[PD], fb[PD], gg[PD];
#pragma unroll
        for (int kk = 0; kk < 16 + PD; kk++) {
          if (kk >= PD) {
            const int k = kk - PD, sl = k % PD;
            A[4 * k + 0] = tanh2_pack(fa[sl].x + gg[sl].x, fa[sl].z + gg[sl].y);
            A[4 * k + 1] = tanh2_pack(fa[sl].y + gg[sl].x, fa[sl].w + gg[sl].y);
            A[4 * k + 2] = tanh2_pack(fb[sl].x + gg[sl].z, fb[sl].z + gg[sl].w);
            A[4 * k + 3] = tanh2_pack(fb[sl].y + gg[sl].z, fb[sl].w + gg[sl].w);
          }
          if (kk < 16) {
            const int sl = kk % PD;
            if (kk == 8) mbar_wait_cluster(bars + kBarFE * 8);
            fa[sl] = lds128(fe_h[kk >> 3] + ((kk >> 2) & 1) * 4096 + ((((kk & 3) * 2) ^ (2 * q)) << 4));
            fb[sl] = lds128(fe_h[kk >> 3] + ((kk >> 2) & 1) * 4096 + ((((kk & 3) * 2 + 1) ^ (2 * q)) << 4));
            gg[sl] = lds128(ge_h[kk >> 3] + (kk & 7) * 16);
          }
        }
      }
      asm volatile("barrier.cluster.arrive.relaxed.aligned;" ::: "memory");
#pragma unroll
      for (int kk = 0; kk < 16; kk++) {
        if ((kk & 3) == 0) { mbar_wait(bars + (kBarW + 28 + (kk >> 2)) * 8); wg_fence(); }
        wgmma_rs_n64(acc[0], A[4 * kk], A[4 * kk + 1], A[4 * kk + 2], A[4 * kk + 3],
                     desc_at(dB, unit_slot(28 + (kk >> 2)) * kSlot + (kk & 3) * 2048), kk != 0);
        if (kk == 3) bar_arrive_pred4(wg == 0);
      }
      wg_commit();
      wg_wait<0>();
#pragma unroll
      for (int jb = 0; jb < 8; jb += 2) {
        const uint32_t r0_ = pack_bf16(acc[0][4 * jb + 0], acc[0][4 * jb + 1]), r1_ = pack_bf16(acc[0][4 * jb + 2], acc[0][4 * jb + 3]);
        const uint32_t r2_ = pack_bf16(acc[0][4 * jb + 4], acc[0][4 * jb + 5]), r3_ = pack_bf16(acc[0][4 * jb + 6], acc[0][4 * jb + 7]);
        stsm_x4(st + (wg ? stage_off(1, 0) : stage_off(0, 0)) + (((jb + (mi >> 1)) ^ l8) << 4), r0_, r1_, r2_, r3_);
      }
      fence_async_smem();
      __syncwarp();
      mbar_arrive_pred(bars + (kBarPR + wg * 4) * 8, lane == 0);
      if (w == 0) TS(wg, 11);
#pragma unroll
      for (int j = 0; j < 4; j++) {
        const int jn = j + 1;
        if (jn == 2) {
#pragma unroll
          for (int i = 0; i < 4; i++) mbar_wait(bars + (kBarW + 32 + i) * 8);
        }
        if (j < 3) wg_fence();
        const uint32_t stj = st + (wg ? stage_off(1, j) : stage_off(0, j));
#pragma unroll
        for (int kk = 0; kk < 16; kk++) {
          if (j < 3)
            wgmma_rs_n64(acc[jn & 1], A[4 * kk], A[4 * kk + 1], A[4 * kk + 2], A[4 * kk + 3],
                         desc_at(dB, unit_slot(28 + (jn >> 1) * 4 + (kk >> 2)) * kSlot + (jn & 1) * 8192 + (kk & 3) * 2048), kk != 0);
          if (kk == 1 && j > 0) {
            if (j < 3) { wg_commit(); wg_wait<1>(); } else { wg_wait<0>(); }
          }
          if (j > 0 && kk >= 2 && kk < 10 && (kk & 1) == 0) {
            const int jb = kk - 2;
            const uint32_t r0_ = pack_bf16(acc[j & 1][4 * jb + 0], acc[j & 1][4 * jb + 1]), r1_ = pack_bf16(acc[j & 1][4 * jb + 2], acc[j & 1][4 * jb + 3]);
            const uint32_t r2_ = pack_bf16(acc[j & 1][4 * jb + 4], acc[j & 1][4 * jb + 5]), r3_ = pack_bf16(acc[j & 1][4 * jb + 6], acc[j & 1][4 * jb + 7]);
            stsm_x4(stj + (((jb + (mi >> 1)) ^ l8) << 4), r0_, r1_, r2_, r3_);
          }
          if (j > 0 && kk == 9) {
            fence_async_smem();
            __syncwarp();
            mbar_arrive_pred(bars + (kBarPR + wg * 4 + j) * 8, lane == 0);
          }
        }
        if (j < 3) wg_commit();
        if (j == 0 && w == 0) TS(wg, 12);
        if (j == 2 && w == 0) TS(wg, 13);
      }
      if (w == 0) TS(wg, 14);
    } else {
      if (wg == 0) asm volatile("bar.arrive 4, 256;" ::: "memory");
      mbar_wait_cluster(bars + kBarFE * 8);
      asm volatile("barrier.cluster.arrive.relaxed.aligned;" ::: "memory");
    }
    asm volatile("barrier.cluster.wait.aligned;" ::: "memory");
    if (w == 0) TS_DUMP(wg, 0, 16);
  }
}

typedef CUresult (*EncodeFn)(CUtensorMap*, CUtensorMapDataType, cuuint32_t, void*, const cuuint64_t*, const cuuint64_t*,
                             const cuuint32_t*, const cuuint32_t*, CUtensorMapInterleave, CUtensorMapSwizzle,
                             CUtensorMapL2promotion, CUtensorMapFloatOOBfill);

void make_map3(EncodeFn enc, CUtensorMap* tm, const void* ptr, uint64_t rows, uint32_t box_rows, uint32_t box_panels) {
  cuuint64_t gd[3] = {64, rows, 4};
  cuuint64_t gs[2] = {512, 128};
  cuuint32_t bd[3] = {64, box_rows, box_panels};
  cuuint32_t es[3] = {1, 1, 1};
  enc(tm, CU_TENSOR_MAP_DATA_TYPE_BFLOAT16, 3, const_cast<void*>(ptr), gd, gs, bd, es, CU_TENSOR_MAP_INTERLEAVE_NONE,
      CU_TENSOR_MAP_SWIZZLE_128B, CU_TENSOR_MAP_L2_PROMOTION_L2_256B, CU_TENSOR_MAP_FLOAT_OOB_FILL_NONE);
}

}

extern "C" void kernel_launch(void* const* d_in, const int* in_sizes, int n_in, void* d_out, int out_size) {
  static EncodeFn enc = nullptr;
  if (!enc) {
    cudaDriverEntryPointQueryResult qr;
    cudaGetDriverEntryPoint("cuTensorMapEncodeTiled", (void**)&enc, cudaEnableDefault, &qr);
    cudaFuncSetAttribute(rnnt_joint_kernel, cudaFuncAttributeMaxDynamicSharedMemorySize, kSmemBytes);
  }
  Params P;
  {
    cuuint64_t gd[4] = {256, 2, 2000, 2};
    cuuint64_t gs[3] = {512, 1024, 4000ull * 512};
    cuuint32_t bd[4] = {64, 1, 64, 1};
    cuuint32_t es[4] = {1, 1, 1, 1};
    enc(&P.x, CU_TENSOR_MAP_DATA_TYPE_BFLOAT16, 4, d_in[0], gd, gs, bd, es, CU_TENSOR_MAP_INTERLEAVE_NONE,
        CU_TENSOR_MAP_SWIZZLE_128B, CU_TENSOR_MAP_L2_PROMOTION_L2_128B, CU_TENSOR_MAP_FLOAT_OOB_FILL_NONE);
  }
  make_map3(enc, &P.w1, d_in[1], 768, 64, 2);
  make_map3(enc, &P.w2, d_in[2], 768, 64, 2);
  make_map3(enc, &P.g, d_in[3], 16, 8, 4);
  make_map3(enc, &P.wf, d_in[4], 256, 64, 2);
  make_map3(enc, &P.wg, d_in[5], 256, 64, 2);
  make_map3(enc, &P.wo, d_in[6], 256, 64, 2);
  make_map3(enc, &P.out64, d_out, 16000, 64, 1);
  make_map3(enc, &P.out56, d_out, 16000, 56, 1);
  rnnt_joint_kernel<<<kNumCtas, kThreads, kSmemBytes>>>(P);
}
```

```cpp
#include <cuda_runtime.h>
#include <cuda_bf16.h>
#include <cuda.h>
#include <stdint.h>

namespace {

constexpr int kT2 = 1000;
constexpr int kR = 31;
constexpr int kNumCtas = 132;
constexpr int kThreads = 384;
constexpr int kSlot = 16384;
constexpr int kSkew = 1;

constexpr int kSlotFE = 9, kSlotF = 10, kSlotH = 11;
constexpr int kOffG = 13 * kSlot;
constexpr int kOffGE = kOffG + 4096;
constexpr int kGEPitch = 144;
constexpr int kGEHalf = 32 * kGEPitch;
constexpr int kGEBytes = 2 * kGEHalf;
constexpr int kOffBar = kOffGE + kGEBytes;
constexpr int kBarX = 0;
constexpr int kBarW = 4;
constexpr int kBarE = 40;
constexpr int kBarHX = 67, kBarFX = 68, kBarFE = 69, kBarG = 70, kBarP0 = 71;
constexpr int kBarRH = 72, kBarRF = 74, kBarRE = 76;
constexpr int kBarPR = 78;
constexpr int kBarGW = 86;
constexpr int kBarFO = 87;
constexpr int kBarGE = 88;
constexpr int kNumBars = 89;
constexpr int kSmemBytes = kOffBar + kNumBars * 8 + 1024;

__device__ __align__(128) float g_ge[2 * kGEBytes / 4];
__device__ __align__(128) unsigned long long g_ge_flag[2 * 16];
__device__ unsigned long long g_cta_count;

#define TS(slot_, idx_) do {} while (0)
#define GT(idx_) do {} while (0)
#define TS_DUMP(slot_, lo_, hi_) do {} while (0)
#define GT_DUMP(idx_) do {} while (0)

__device__ __forceinline__ uint32_t smem_u32(const void* p) { return (uint32_t)__cvta_generic_to_shared(p); }
__device__ __forceinline__ void mbar_init(uint32_t a, uint32_t c) { asm volatile("mbarrier.init.shared.b64 [%0], %1;" ::"r"(a), "r"(c) : "memory"); }
__device__ __forceinline__ void mbar_expect(uint32_t a, uint32_t b) { asm volatile("mbarrier.arrive.expect_tx.shared.b64 _, [%0], %1;" ::"r"(a), "r"(b) : "memory"); }
__device__ __forceinline__ void mbar_arrive(uint32_t a) { asm volatile("mbarrier.arrive.shared.b64 _, [%0];" ::"r"(a) : "memory"); }
__device__ __forceinline__ void mbar_arrive_pred(uint32_t a, bool p) {
  asm volatile("{\n.reg .pred q;\nsetp.ne.u32 q, %1, 0;\n@q mbarrier.arrive.shared.b64 _, [%0];\n}\n" ::"r"(a), "r"((uint32_t)p) : "memory");
}
#define DEF_NAMED(ID) \
__device__ __forceinline__ void bar_arrive_pred##ID(bool p) { asm volatile("{\n.reg .pred q;\nsetp.ne.u32 q, %0, 0;\n@q bar.arrive " #ID ", 256;\n}\n" ::"r"((uint32_t)p) : "memory"); } \
__device__ __forceinline__ void bar_sync_pred##ID(bool p) { asm volatile("{\n.reg .pred q;\nsetp.ne.u32 q, %0, 0;\n@q bar.sync " #ID ", 256;\n}\n" ::"r"((uint32_t)p) : "memory"); }
DEF_NAMED(4)
DEF_NAMED(5)
DEF_NAMED(6)
__device__ __forceinline__ bool mbar_try(uint32_t a) {
  uint32_t ok;
  asm volatile("{\n.reg .pred p;\nmbarrier.try_wait.parity.shared.b64 p, [%1], 0;\nselp.u32 %0, 1, 0, p;\n}\n" : "=r"(ok) : "r"(a) : "memory");
  return ok != 0;
}
__device__ __forceinline__ bool mbar_try_cluster(uint32_t a) {
  uint32_t ok;
  asm volatile("{\n.reg .pred p;\nmbarrier.try_wait.parity.acquire.cluster.shared.b64 p, [%1], 0;\nselp.u32 %0, 1, 0, p;\n}\n" : "=r"(ok) : "r"(a) : "memory");
  return ok != 0;
}
__device__ __forceinline__ void mbar_wait_slow(uint32_t a) {
  const long long t0 = clock64();
  while (!mbar_try(a)) { if (clock64() - t0 > 4000000ll) break; }
}
__device__ __forceinline__ void mbar_wait_cluster_slow(uint32_t a) {
  const long long t0 = clock64();
  while (!mbar_try_cluster(a)) { if (clock64() - t0 > 4000000ll) break; }
}
__device__ __forceinline__ void mbar_wait(uint32_t a) { if (!mbar_try(a)) mbar_wait_slow(a); }
__device__ __forceinline__ void mbar_wait_cluster(uint32_t a) { if (!mbar_try_cluster(a)) mbar_wait_cluster_slow(a); }
__device__ __forceinline__ uint32_t mapa(uint32_t a, uint32_t r) { uint32_t d; asm volatile("mapa.shared::cluster.u32 %0, %1, %2;" : "=r"(d) : "r"(a), "r"(r)); return d; }
__device__ __forceinline__ bool elect_one() { uint32_t p; asm volatile("{\n.reg .pred P;\nelect.sync _|P, 0xffffffff;\nselp.u32 %0, 1, 0, P;\n}\n" : "=r"(p)); return p != 0; }
__device__ __forceinline__ void fence_async_smem() { asm volatile("fence.proxy.async.shared::cta;" ::: "memory"); }
__device__ __forceinline__ void cluster_sync_relaxed() { asm volatile("barrier.cluster.arrive.relaxed.aligned;\nbarrier.cluster.wait.aligned;" ::: "memory"); }
__device__ __forceinline__ void wg_fence() { asm volatile("wgmma.fence.sync.aligned;" ::: "memory"); }
__device__ __forceinline__ void wg_commit() { asm volatile("wgmma.commit_group.sync.aligned;" ::: "memory"); }
template <int N> __device__ __forceinline__ void wg_wait() { asm volatile("wgmma.wait_group.sync.aligned %0;" ::"n"(N) : "memory"); }

__device__ __forceinline__ void tma_load_3d(uint32_t dst, const CUtensorMap* tm, uint32_t bar, int c0, int c1, int c2) {
  asm volatile("cp.async.bulk.tensor.3d.shared::cluster.global.mbarrier::complete_tx::bytes [%0], [%1, {%3, %4, %5}], [%2];"
               ::"r"(dst), "l"(tm), "r"(bar), "r"(c0), "r"(c1), "r"(c2) : "memory");
}
__device__ __forceinline__ void tma_load_4d(uint32_t dst, const CUtensorMap* tm, uint32_t bar, int c0, int c1, int c2, int c3) {
  asm volatile("cp.async.bulk.tensor.4d.shared::cluster.global.mbarrier::complete_tx::bytes [%0], [%1, {%3, %4, %5, %6}], [%2];"
               ::"r"(dst), "l"(tm), "r"(bar), "r"(c0), "r"(c1), "r"(c2), "r"(c3) : "memory");
}
__device__ __forceinline__ void tma_load_4d_mc(uint32_t dst, const CUtensorMap* tm, uint32_t bar, int c0, int c1, int c2, int c3, uint16_t mask) {
  asm volatile("cp.async.bulk.tensor.4d.shared::cluster.global.mbarrier::complete_tx::bytes.multicast::cluster [%0], [%1, {%3, %4, %5, %6}], [%2], %7;"
               ::"r"(dst), "l"(tm), "r"(bar), "r"(c0), "r"(c1), "r"(c2), "r"(c3), "h"(mask) : "memory");
}
__device__ __forceinline__ void tma_store_3d(const CUtensorMap* tm, uint32_t src, int c0, int c1, int c2) {
  asm volatile("cp.async.bulk.tensor.3d.global.shared::cta.bulk_group [%0, {%2, %3, %4}], [%1];"
               ::"l"(tm), "r"(src), "r"(c0), "r"(c1), "r"(c2) : "memory");
}
__device__ __forceinline__ void bulk_load(uint32_t dst, const void* src, uint32_t bytes, uint32_t bar) {
  asm volatile("cp.async.bulk.shared::cluster.global.mbarrier::complete_tx::bytes [%0], [%1], %2, [%3];"
               ::"r"(dst), "l"(src), "r"(bytes), "r"(bar) : "memory");
}
__device__ __forceinline__ void dsmem_copy(uint32_t dst_remote, uint32_t src, uint32_t bytes, uint32_t bar_remote) {
  asm volatile("cp.async.bulk.shared::cluster.shared::cta.mbarrier::complete_tx::bytes [%0], [%1], %2, [%3];"
               ::"r"(dst_remote), "r"(src), "r"(bytes), "r"(bar_remote) : "memory");
}
__device__ __forceinline__ void stsm_x4_trans(uint32_t addr, uint32_t r0, uint32_t r1, uint32_t r2, uint32_t r3) {
  asm volatile("stmatrix.sync.aligned.m8n8.x4.trans.shared.b16 [%0], {%1, %2, %3, %4};" ::"r"(addr), "r"(r0), "r"(r1), "r"(r2), "r"(r3) : "memory");
}
__device__ __forceinline__ void stsm_x4(uint32_t addr, uint32_t r0, uint32_t r1, uint32_t r2, uint32_t r3) {
  asm volatile("stmatrix.sync.aligned.m8n8.x4.shared.b16 [%0], {%1, %2, %3, %4};" ::"r"(addr), "r"(r0), "r"(r1), "r"(r2), "r"(r3) : "memory");
}
__device__ __forceinline__ float4 lds128(uint32_t a) { float4 v; asm volatile("ld.shared.v4.f32 {%0, %1, %2, %3}, [%4];" : "=f"(v.x), "=f"(v.y), "=f"(v.z), "=f"(v.w) : "r"(a) : "memory"); return v; }
__device__ __forceinline__ void sts32(uint32_t a, float x) { asm volatile("st.shared.f32 [%0], %1;" ::"r"(a), "f"(x) : "memory"); }
__device__ __forceinline__ void sts64(uint32_t a, float x, float y) { asm volatile("st.shared.v2.f32 [%0], {%1, %2};" ::"r"(a), "f"(x), "f"(y) : "memory"); }
__device__ __forceinline__ float tanh_fast(float x) { float y; asm("tanh.approx.f32 %0, %1;" : "=f"(y) : "f"(x)); return y; }
__device__ __forceinline__ uint32_t tanh2_pack(float lo, float hi) {
  uint32_t r;
  asm volatile("{\n.reg .f32 a, b;\ntanh.approx.f32 a, %1;\ntanh.approx.f32 b, %2;\ncvt.rn.bf16x2.f32 %0, b, a;\n}\n" : "=r"(r) : "f"(lo), "f"(hi));
  return r;
}
__device__ __forceinline__ uint32_t pack_bf16(float lo, float hi) { uint32_t r; asm("cvt.rn.bf16x2.f32 %0, %1, %2;" : "=r"(r) : "f"(hi), "f"(lo)); return r; }
__device__ __forceinline__ float gelu_tanh(float x) {
  const float k0 = 0.7978845608028654f, k1 = 0.7978845608028654f * 0.044715f;
  float u = x * fmaf(x * x, k1, k0);
  float hx = 0.5f * x;
  return fmaf(hx, tanh_fast(u), hx);
}

__device__ __forceinline__ uint32_t desc_lo(uint32_t addr, uint32_t lbo) { return ((addr & 0x3FFFF) >> 4) | ((lbo >> 4) << 16); }
__device__ __forceinline__ uint64_t desc_at(uint32_t lo, uint32_t off) { return ((uint64_t)0x40000040u << 32) | (uint64_t)(lo + (off >> 4)); }

__device__ __forceinline__ void wgmma_ss_n64(float (&d)[32], uint64_t da, uint64_t db, int scale_d) {
  asm volatile("{\n.reg .pred p;\nsetp.ne.b32 p, %34, 0;\n"
    "wgmma.mma_async.sync.aligned.m64n64k16.f32.bf16.bf16 {%0, %1, %2, %3, %4, %5, %6, %7, %8, %9, %10, %11, %12, %13, %14, %15, %16, %17, %18, %19, %20, %21, %22, %23, %24, %25, %26, %27, %28, %29, %30, %31}, %32, %33, p, 1, 1, 1, 0;\n}\n"
    : "+f"(d[0]), "+f"(d[1]), "+f"(d[2]), "+f"(d[3]), "+f"(d[4]), "+f"(d[5]), "+f"(d[6]), "+f"(d[7]), "+f"(d[8]), "+f"(d[9]), "+f"(d[10]), "+f"(d[11]), "+f"(d[12]), "+f"(d[13]), "+f"(d[14]), "+f"(d[15]), "+f"(d[16]), "+f"(d[17]), "+f"(d[18]), "+f"(d[19]), "+f"(d[20]), "+f"(d[21]), "+f"(d[22]), "+f"(d[23]), "+f"(d[24]), "+f"(d[25]), "+f"(d[26]), "+f"(d[27]), "+f"(d[28]), "+f"(d[29]), "+f"(d[30]), "+f"(d[31])
    : "l"(da), "l"(db), "r"(scale_d));
}

__device__ __forceinline__ void wgmma_ss_n32(float (&d)[16], uint64_t da, uint64_t db, int scale_d) {
  asm volatile("{\n.reg .pred p;\nsetp.ne.b32 p, %18, 0;\n"
    "wgmma.mma_async.sync.aligned.m64n32k16.f32.bf16.bf16 {%0, %1, %2, %3, %4, %5, %6, %7, %8, %9, %10, %11, %12, %13, %14, %15}, %16, %17, p, 1, 1, 1, 0;\n}\n"
    : "+f"(d[0]), "+f"(d[1]), "+f"(d[2]), "+f"(d[3]), "+f"(d[4]), "+f"(d[5]), "+f"(d[6]), "+f"(d[7]), "+f"(d[8]), "+f"(d[9]), "+f"(d[10]), "+f"(d[11]), "+f"(d[12]), "+f"(d[13]), "+f"(d[14]), "+f"(d[15])
    : "l"(da), "l"(db), "r"(scale_d));
}

__device__ __forceinline__ void wgmma_ss_n8(float (&d)[4], uint64_t da, uint64_t db, int scale_d) {
  asm volatile("{\n.reg .pred p;\nsetp.ne.b32 p, %6, 0;\n"
    "wgmma.mma_async.sync.aligned.m64n8k16.f32.bf16.bf16 {%0, %1, %2, %3}, %4, %5, p, 1, 1, 1, 0;\n}\n"
    : "+f"(d[0]), "+f"(d[1]), "+f"(d[2]), "+f"(d[3])
    : "l"(da), "l"(db), "r"(scale_d));
}

__device__ __forceinline__ void wgmma_rs_n64(float (&d)[32], uint32_t a0, uint32_t a1, uint32_t a2, uint32_t a3, uint64_t db, int scale_d) {
  asm volatile("{\n.reg .pred p;\nsetp.ne.b32 p, %37, 0;\n"
    "wgmma.mma_async.sync.aligned.m64n64k16.f32.bf16.bf16 {%0, %1, %2, %3, %4, %5, %6, %7, %8, %9, %10, %11, %12, %13, %14, %15, %16, %17, %18, %19, %20, %21, %22, %23, %24, %25, %26, %27, %28, %29, %30, %31}, {%32, %33, %34, %35}, %36, p, 1, 1, 1;\n}\n"
    : "+f"(d[0]), "+f"(d[1]), "+f"(d[2]), "+f"(d[3]), "+f"(d[4]), "+f"(d[5]), "+f"(d[6]), "+f"(d[7]), "+f"(d[8]), "+f"(d[9]), "+f"(d[10]), "+f"(d[11]), "+f"(d[12]), "+f"(d[13]), "+f"(d[14]), "+f"(d[15]), "+f"(d[16]), "+f"(d[17]), "+f"(d[18]), "+f"(d[19]), "+f"(d[20]), "+f"(d[21]), "+f"(d[22]), "+f"(d[23]), "+f"(d[24]), "+f"(d[25]), "+f"(d[26]), "+f"(d[27]), "+f"(d[28]), "+f"(d[29]), "+f"(d[30]), "+f"(d[31])
    : "r"(a0), "r"(a1), "r"(a2), "r"(a3), "l"(db), "r"(scale_d));
}

__host__ __device__ constexpr int unit_slot(int u) {
  constexpr int t[36] = {4, 5, 6, 7, 8, 4, 5, 6, 0, 7, 8, 4,  1, 5, 6, 0, 2, 7, 8, 4, 3, 1, 5, 6,
                         0, 2, 7, 8,  4, 3, 1, 5, 6, 0, 2, 7};
  return t[u];
}
__host__ __device__ constexpr int unit_wait(int u) {
  constexpr int t[36] = {-1, -1, -1, -1, -1, 0, 1, 2, 2, 3, 4, 5,  5, 6, 7, 8, 8, 9, 10, 11, 11, 12, 13, 14,
                         15, 16, 17, 18,  19, 20, 21, 22, 23, 24, 25, 26};
  return t[u];
}

__device__ __forceinline__ uint32_t stage_off(int g, int j) {
  return g == 0 ? (j < 2 ? 8 * kSlot + j * 8192 : 10 * kSlot + (j - 2) * 8192)
                : (j < 2 ? 12 * kSlot + j * 8192 : (j == 2 ? 11 * kSlot + 8192 : 9 * kSlot));
}

struct Params {
  CUtensorMap x, w1, w2, wf, wg, wo, g, out64, out56;
};

__device__ __forceinline__ void init_bar(uint32_t bars, int i) {
  const uint32_t a = bars + i * 8;
  const bool is_e = (i >= kBarE && i < kBarE + 27);
  mbar_init(a, is_e ? 8 : 1);
  if (!is_e) {
    uint32_t bytes = 16384;
    if (i == kBarFX) bytes = 8192;
    if (i == kBarFE) bytes = 8192;
    mbar_expect(a, bytes);
  }
}

__device__ __forceinline__ void store_pieces(const Params& P, uint32_t sb, uint32_t bars, int g, uint32_t cta, int b, int r0, int rvalid) {
  const int rl0 = cta * 16 + g * 8;
  if (rl0 >= rvalid) return;
  const CUtensorMap* omap = (rl0 + 8 <= rvalid) ? &P.out64 : &P.out56;
#pragma unroll
  for (int j = 0; j < 4; j++) {
    mbar_wait(bars + (kBarPR + g * 4 + j) * 8);
    if (elect_one()) {
      tma_store_3d(omap, sb + stage_off(g, j), 0, (b * kT2 + r0 + rl0) * 8, j);
      asm volatile("cp.async.bulk.commit_group;" ::: "memory");
    }
    __syncwarp();
    if (j == 0) TS(2, 12 + g);
    if (j == 3) TS(2, 14 + g);
  }
  if (elect_one()) asm volatile("cp.async.bulk.wait_group.read 0;" ::: "memory");
  __syncwarp();
  if (g == 1) { TS(2, 11); GT(1); TS_DUMP(2, 11, 12); GT_DUMP(1); }
  TS_DUMP(2, 12 + g, 13 + g); TS_DUMP(2, 14 + g, 15 + g);
}

__global__ void __cluster_dims__(2, 1, 1) __launch_bounds__(kThreads, 1)
rnnt_joint_kernel(const __grid_constant__ Params P) {
  extern __shared__ uint8_t smem_raw[];
  const uint32_t sb = (smem_u32(smem_raw) + 1023u) & ~1023u;
  const uint32_t bars = sb + kOffBar;
  const int warp = threadIdx.x >> 5, lane = threadIdx.x & 31;
  uint32_t cta;
  asm volatile("mov.u32 %0, %%cluster_ctarank;" : "=r"(cta));
  const uint32_t peer = cta ^ 1u;
  const int cl = blockIdx.x >> 1;
  const bool ge_cta = cl < 2;
  const int b = ge_cta ? cl : ((cl - 2) >> 5);
  const int r0 = ge_cta ? 32 * kR : ((cl - 2) & 31) * kR;
  const int rvalid = ge_cta ? kT2 - 32 * kR : kR;

  if (warp >= 8) {
    asm volatile("setmaxnreg.dec.sync.aligned.u32 40;");
    if (warp > 8) {
      if (elect_one()) {
#pragma unroll
        for (int i = 0; i < 5; i++) if (57 + (warp - 9) * 5 + i < kBarG) init_bar(bars, 57 + (warp - 9) * 5 + i);
#pragma unroll
        for (int i = 0; i < 5; i++) if (kBarRH + (warp - 9) * 5 + i < kBarGW) mbar_init(bars + (kBarRH + (warp - 9) * 5 + i) * 8, 4);
        if (warp == 11) { mbar_init(bars + kBarGW * 8, 8); mbar_init(bars + kBarFO * 8, 8); mbar_init(bars + kBarGE * 8, 1); mbar_expect(bars + kBarGE * 8, kGEBytes); }
        asm volatile("fence.mbarrier_init.release.cluster;" ::: "memory");
      }
      __syncwarp();
      asm volatile("barrier.cluster.arrive.relaxed.aligned;" ::: "memory");
      if (warp == 11 && lane < 9) asm volatile("prefetch.tensormap [%0];" ::"l"(reinterpret_cast<const CUtensorMap*>(&P) + lane) : "memory");
      __syncwarp();
      asm volatile("barrier.cluster.wait.aligned;" ::: "memory");
      if (warp == 10 && ge_cta) {
        mbar_wait(bars + kBarGW * 8);
        if (elect_one()) {
          asm volatile("cp.async.bulk.global.shared::cta.bulk_group [%0], [%1], %2;"
                       ::"l"(reinterpret_cast<char*>(g_ge) + b * kGEBytes + cta * kGEHalf), "r"(sb + kOffGE + cta * kGEHalf), "r"(kGEHalf) : "memory");
          asm volatile("cp.async.bulk.commit_group;\ncp.async.bulk.wait_group 0;" ::: "memory");
          asm volatile("fence.proxy.async;" ::: "memory");
          asm volatile("red.release.gpu.global.add.u64 [%0], 1;" ::"l"(&g_ge_flag[b * 16]) : "memory");
        }
        __syncwarp();
      }
      if (warp == 11) {
        if (elect_one()) {
          const unsigned long long ticket = atomicAdd(&g_cta_count, 1ull);
          const unsigned long long want = (ticket / kNumCtas + 1ull) * 2ull;
          const long long t0 = clock64();
          unsigned long long v;
          do {
            const long long t1 = clock64();
            while (clock64() - t1 < 400) {}
            asm volatile("ld.acquire.gpu.global.u64 %0, [%1];" : "=l"(v) : "l"(&g_ge_flag[b * 16]) : "memory");
          } while (v < want && clock64() - t0 < 4000000ll);
          asm volatile("fence.proxy.async;" ::: "memory");
          bulk_load(sb + kOffGE, reinterpret_cast<const char*>(g_ge) + b * kGEBytes, kGEBytes, bars + kBarGE * 8);
        }
        __syncwarp();
        return;
      }
      if (warp == 10) store_pieces(P, sb, bars, 1, cta, b, r0, rvalid);
      if (warp == 10) return;
#pragma unroll
      for (int g = 0; g < 2; g++) {
        mbar_wait(bars + (kBarRH + g) * 8);
        if (elect_one()) {
          const uint32_t src = sb + kSlotH * kSlot + (2 * cta + g) * 8192;
          dsmem_copy(mapa(src, peer), src, 8192, mapa(bars + kBarHX * 8, peer));
        }
        __syncwarp();
      }
#pragma unroll
      for (int g = 0; g < 2; g++) {
        mbar_wait(bars + (kBarRF + g) * 8);
        if (elect_one()) {
          const uint32_t src = sb + kSlotF * kSlot + (2 * cta + g) * 4096;
          dsmem_copy(mapa(src, peer), src, 4096, mapa(bars + kBarFX * 8, peer));
        }
        __syncwarp();
      }
#pragma unroll
      for (int g = 0; g < 2; g++) {
        mbar_wait(bars + (kBarRE + g) * 8);
        if (elect_one())
          dsmem_copy(mapa(sb + kSlotFE * kSlot + (2 * cta + g) * 4096, peer), sb + kSlotH * kSlot + g * 4096, 4096, mapa(bars + kBarFE * 8, peer));
        __syncwarp();
      }
      store_pieces(P, sb, bars, 0, cta, b, r0, rvalid);
      return;
    }
    TS(2, 0);
    GT(0);
    const int par = cta == 0 ? 1 : 0;
    const int q0 = cta == 0 ? 2 * r0 - 2 : 2 * r0 - 1;
    if (elect_one()) {
      mbar_init(bars + kBarX * 8, 1); mbar_expect(bars + kBarX * 8, 16384);
      mbar_init(bars + kBarW * 8, 1); mbar_expect(bars + kBarW * 8, 16384);
      fence_async_smem();
      tma_load_4d(sb, &P.x, bars + kBarX * 8, 0, 1, 2 * r0 - 2, b);
      tma_load_4d(sb + 8192, &P.x, bars + kBarX * 8, 0, 0, 2 * r0 - 1, b);
      tma_load_3d(sb + unit_slot(0) * kSlot, &P.w1, bars + kBarW * 8, 0, 0, 2 * cta);
      TS(2, 7);
#pragma unroll
      for (int i = 1; i < 9; i++) if (i != kBarW) { mbar_init(bars + i * 8, 1); mbar_expect(bars + i * 8, 16384); }
      if (ge_cta) { mbar_init(bars + kBarG * 8, 1); mbar_expect(bars + kBarG * 8, 4 * 16384 + 4096); mbar_init(bars + kBarP0 * 8, 8); }
      asm volatile("fence.mbarrier_init.release.cluster;" ::: "memory");
      fence_async_smem();
      TS(2, 8);
      if (ge_cta) {
        tma_load_3d(sb + kOffG, &P.g, bars + kBarG * 8, 0, b * 8, 0);
#pragma unroll
        for (int i = 0; i < 4; i++) tma_load_3d(sb + (9 + i) * kSlot, &P.wg, bars + kBarG * 8, 0, i * 64, 2 * cta);
      }
#pragma unroll
      for (int u = 1; u < 5; u++)
        tma_load_3d(sb + unit_slot(u) * kSlot, &P.w1, bars + (kBarW + u) * 8, 0, (u % 3) * 256 + (u / 3) * 64, 2 * cta);
      TS(2, 10);
    }
    __syncwarp();
    TS(2, 6);
    cluster_sync_relaxed();
    TS(2, 1);
    if (elect_one()) {
#pragma unroll
      for (int p = 1; p < 3; p++)
        tma_load_4d_mc(sb + p * kSlot + cta * 8192, &P.x, bars + (kBarX + p) * 8, p * 64, par, q0, b, (uint16_t)3);
    }
    __syncwarp();
    mbar_wait(bars + kBarX * 8);
    if (ge_cta) mbar_wait(bars + kBarP0 * 8);
    if (elect_one()) tma_load_4d_mc(sb + 3 * kSlot + cta * 8192, &P.x, bars + (kBarX + 3) * 8, 3 * 64, par, q0, b, (uint16_t)3);
    __syncwarp();
#pragma unroll
    for (int u = 5; u < 36; u++) {
      if (unit_wait(u) != unit_wait(u - 1)) mbar_wait(bars + (kBarE + unit_wait(u)) * 8);
      if (u == 28) mbar_wait(bars + kBarFX * 8);
      if (u >= 28 && (int)cta * 16 >= rvalid) continue;
      if (elect_one()) {
        const uint32_t dst = sb + unit_slot(u) * kSlot, bar = bars + (kBarW + u) * 8;
        if (u < 12) tma_load_3d(dst, &P.w1, bar, 0, (u % 3) * 256 + (u / 3) * 64, 2 * cta);
        else if (u < 24) tma_load_3d(dst, &P.w2, bar, 0, ((u - 12) % 3) * 256 + ((2 * cta + (u - 12) / 3) & 3) * 64, 2 * cta);
        else if (u < 28) tma_load_3d(dst, &P.wf, bar, 0, ((2 * cta + (u - 24)) & 3) * 64, 2 * cta);
        else tma_load_3d(dst, &P.wo, bar, 0, ((2 * cta + (u - 28)) & 3) * 64, ((u - 28) >> 2) * 2);
      }
      __syncwarp();
      if (u == 11) TS(2, 2);
      if (u == 23) TS(2, 3);
      if (u == 27) TS(2, 4);
      if (u == 35) TS(2, 5);
    }
    TS_DUMP(2, 0, 11); GT_DUMP(0);
  } else {
    asm volatile("setmaxnreg.inc.sync.aligned.u32 232;");
    const int wg = warp >> 2, w = warp & 3;
    const int gq = lane >> 2, q = lane & 3;
    const uint32_t panel = 2 * cta + wg;
    const int ch = panel * 64 + w * 16 + gq;
    const uint32_t dA = desc_lo(sb + wg * 8192, 8192);
    const uint32_t dB = desc_lo(sb, 16);
    const uint32_t dBo = desc_lo(sb + cta * 2 * 8192, 16), dBp = desc_lo(sb + (cta ^ 1) * 2 * 8192, 16);
    const uint32_t dFo = desc_lo(sb + cta * 2 * 4096, 16), dFp = desc_lo(sb + (cta ^ 1) * 2 * 4096, 16);
    if (elect_one()) {
#pragma unroll
      for (int i = 0; i < 6; i++) init_bar(bars, 9 + warp * 6 + i);
      asm volatile("fence.mbarrier_init.release.cluster;" ::: "memory");
    }
    __syncwarp();
    cluster_sync_relaxed();
    if (w == 0) TS(wg, 0);

    if (ge_cta) {
      float ga[4];
      mbar_wait(bars + kBarG * 8);
      wg_fence();
#pragma unroll
      for (int i = 0; i < 4; i++) {
#pragma unroll
        for (int s = 0; s < 4; s++)
          wgmma_ss_n8(ga, desc_at(dA, (9 + i) * kSlot + s * 2048), desc_at(dB, kOffG + i * 1024 + s * 32), (i | s) != 0);
      }
      wg_commit();
      wg_wait<0>();
      if (lane == 0) mbar_arrive(bars + kBarP0 * 8);
      const uint32_t gp = sb + kOffGE + cta * kGEHalf + ((ch & 7) >> 1) * kGEPitch + (((ch & 127) >> 4) * 4 + (ch & 1)) * 4;
      sts32(gp + (2 * q) * 4 * kGEPitch, ga[0]);
      sts32(gp + (2 * q + 1) * 4 * kGEPitch, ga[1]);
      sts32(gp + (2 * q) * 4 * kGEPitch + 8, ga[2]);
      sts32(gp + (2 * q + 1) * 4 * kGEPitch + 8, ga[3]);
      fence_async_smem();
      __syncwarp();
      if (lane == 0) mbar_arrive(bars + kBarGW * 8);
    }

    {
      float acc[32];
#pragma unroll
      for (int u = 0; u < 12; u++) {
        const int p = u / 3, tap = u % 3;
        if (u == 12 - kSkew) bar_sync_pred5(wg == 1);
        if (tap == 0) mbar_wait(bars + (kBarX + p) * 8);
        mbar_wait(bars + (kBarW + u) * 8);
        if (u == 0 && w == 0) TS(wg, 1);
        wg_fence();
#pragma unroll
        for (int s = 0; s < 4; s++)
          wgmma_ss_n64(acc, desc_at(dA, unit_slot(u) * kSlot + s * 2048),
                       desc_at(dB, p * kSlot + (tap == 1 ? 8192 : (tap == 2 ? 128 : 0)) + s * 32), (u | s) != 0);
        wg_commit();
        if (u == 11) bar_arrive_pred5(wg == 0);
        if (u > 0) {
          wg_wait<1>();
          if (lane == 0) mbar_arrive(bars + (kBarE + u - 1) * 8);
        }
      }
      wg_wait<0>();
      if (lane == 0) mbar_arrive(bars + (kBarE + 11) * 8);
      if (w == 0) TS(wg, 2);
      const uint32_t hp = sb + kSlotH * kSlot + panel * 8192;
      const int mi = lane >> 3, l8 = lane & 7;
#pragma unroll
      for (int jb = 0; jb < 8; jb += 2) {
        uint32_t r[4];
#pragma unroll
        for (int t = 0; t < 2; t++) {
          r[2 * t + 0] = pack_bf16(gelu_tanh(acc[4 * (jb + t) + 0]), gelu_tanh(acc[4 * (jb + t) + 1]));
          r[2 * t + 1] = pack_bf16(gelu_tanh(acc[4 * (jb + t) + 2]), gelu_tanh(acc[4 * (jb + t) + 3]));
        }
        const int n = 8 * (jb + (mi >> 1)) + l8;
        const int row = n >> 1, chunk = 2 * w + (mi & 1);
        stsm_x4_trans(hp + (n & 1) * 4096 + row * 128 + ((chunk ^ (row & 7)) << 4), r[0], r[1], r[2], r[3]);
      }
      __syncwarp();
      if (w == 0) TS(wg, 15);
      fence_async_smem();
      __syncwarp();
      if (lane == 0) mbar_arrive(bars + (kBarRH + wg) * 8);
      if (w == 0) TS(wg, 3);
    }
    {
      float acc[16];
#pragma unroll
      for (int v = 0; v < 12; v++) {
        const int i = v / 3, tap = v % 3;
        if (v == 12 - kSkew) bar_sync_pred6(wg == 1);
        if (v == 0) mbar_wait(bars + kBarRH * 8);
        if (v == 3) mbar_wait(bars + (kBarRH + 1) * 8);
        if (v == 6) { mbar_wait_cluster(bars + kBarHX * 8); if (w == 0) TS(wg, 4); }
        mbar_wait(bars + (kBarW + 12 + v) * 8);
        wg_fence();
#pragma unroll
        for (int s = 0; s < 4; s++)
          wgmma_ss_n32(acc, desc_at(dA, unit_slot(12 + v) * kSlot + s * 2048),
                       desc_at(i < 2 ? dBo : dBp, kSlotH * kSlot + (i & 1) * 8192 + (tap == 1 ? 4096 : (tap == 2 ? 128 : 0)) + s * 32), (v | s) != 0);
        wg_commit();
        if (v == 11) bar_arrive_pred6(wg == 0);
        if (v > 0) {
          wg_wait<1>();
          if (lane == 0) mbar_arrive(bars + (kBarE + 12 + v - 1) * 8);
        }
      }
      wg_wait<0>();
      if (lane == 0) mbar_arrive(bars + (kBarE + 23) * 8);
      if (w == 0) TS(wg, 5);
      const uint32_t fp = sb + kSlotF * kSlot + panel * 4096;
      const int mi = lane >> 3, l8 = lane & 7;
#pragma unroll
      for (int jb = 0; jb < 4; jb += 2) {
        uint32_t r[4];
#pragma unroll
        for (int t = 0; t < 2; t++) {
          r[2 * t + 0] = pack_bf16(gelu_tanh(acc[4 * (jb + t) + 0]), gelu_tanh(acc[4 * (jb + t) + 1]));
          r[2 * t + 1] = pack_bf16(gelu_tanh(acc[4 * (jb + t) + 2]), gelu_tanh(acc[4 * (jb + t) + 3]));
        }
        const int n = 8 * (jb + (mi >> 1)) + l8;
        const int chunk = 2 * w + (mi & 1);
        stsm_x4_trans(fp + n * 128 + ((chunk ^ (n & 7)) << 4), r[0], r[1], r[2], r[3]);
      }
      fence_async_smem();
      __syncwarp();
      if (lane == 0) mbar_arrive(bars + (kBarRF + wg) * 8);
      if (w == 0) TS(wg, 6);
    }
    {
      float acc[16];
#pragma unroll
      for (int i = 0; i < 4; i++) {
        if (i < 2) mbar_wait(bars + (kBarRF + i) * 8);
        if (i == 2) { mbar_wait_cluster(bars + kBarFX * 8); if (w == 0) TS(wg, 7); }
        mbar_wait(bars + (kBarW + 24 + i) * 8);
        wg_fence();
#pragma unroll
        for (int s = 0; s < 4; s++)
          wgmma_ss_n32(acc, desc_at(dA, unit_slot(24 + i) * kSlot + s * 2048),
                       desc_at(i < 2 ? dFo : dFp, kSlotF * kSlot + (i & 1) * 4096 + s * 32), (i | s) != 0);
        wg_commit();
        if (i > 0) {
          wg_wait<1>();
          if (lane == 0) mbar_arrive(bars + (kBarE + 24 + i - 1) * 8);
        }
      }
      wg_wait<0>();
      if (w == 0) TS(wg, 8);
      const uint32_t qk = gq >> 1;
      const uint32_t off0 = qk * 128 + (((2 * w) ^ (2 * qk)) << 4) + (gq & 1) * 8;
      const uint32_t off1 = qk * 128 + (((2 * w + 1) ^ (2 * qk)) << 4) + (gq & 1) * 8;
      const uint32_t own = sb + kSlotFE * kSlot + panel * 4096;
      const uint32_t stg = sb + kSlotH * kSlot + wg * 4096;
#pragma unroll
      for (int jb = 0; jb < 4; jb++) {
        const uint32_t base = (((uint32_t)(jb >> 1) == cta) ? own : stg) + (4 * (jb & 1) + q) * 512;
        sts64(base + off0, acc[4 * jb + 0], acc[4 * jb + 1]);
        sts64(base + off1, acc[4 * jb + 2], acc[4 * jb + 3]);
      }
      fence_async_smem();
      __syncwarp();
      if (lane == 0) { mbar_arrive(bars + (kBarRE + wg) * 8); mbar_arrive(bars + kBarFO * 8); }
      if (w == 0) TS(wg, 9);
    }
    const int rl0 = cta * 16 + wg * 8;
    mbar_wait(bars + kBarFO * 8);
    mbar_wait(bars + kBarGE * 8);
    if (wg == 1) asm volatile("bar.sync 4, 256;" ::: "memory");
    if (rl0 < rvalid) {
      if (w == 0) TS(wg, 10);
      const uint32_t fe_row = sb + kSlotFE * kSlot + ((4 * wg + w) * 4 + q) * 128;
      const uint32_t fe_h[2] = {fe_row + cta * 8192, fe_row + (cta ^ 1) * 8192};
      const uint32_t ge_h[2] = {sb + kOffGE + lane * kGEPitch + cta * kGEHalf, sb + kOffGE + lane * kGEPitch + (cta ^ 1) * kGEHalf};
      const int mi = lane >> 3, l8 = lane & 7;
      const uint32_t st = sb + (16 * w + (mi & 1) * 8 + l8) * 128;
      uint32_t A[64];
      float acc[2][32];
      {
        constexpr int PD = 2;
        float4 fa[PD], fb[PD], gg[PD];
#pragma unroll
        for (int kk = 0; kk < 16 + PD; kk++) {
          if (kk >= PD) {
            const int k = kk - PD, sl = k % PD;
            A[4 * k + 0] = tanh2_pack(fa[sl].x + gg[sl].x, fa[sl].z + gg[sl].y);
            A[4 * k + 1] = tanh2_pack(fa[sl].y + gg[sl].x, fa[sl].w + gg[sl].y);
            A[4 * k + 2] = tanh2_pack(fb[sl].x + gg[sl].z, fb[sl].z + gg[sl].w);
            A[4 * k + 3] = tanh2_pack(fb[sl].y + gg[sl].z, fb[sl].w + gg[sl].w);
          }
          if (kk < 16) {
            const int sl = kk % PD;
            if (kk == 8) mbar_wait_cluster(bars + kBarFE * 8);
            fa[sl] = lds128(fe_h[kk >> 3] + ((kk >> 2) & 1) * 4096 + ((((kk & 3) * 2) ^ (2 * q)) << 4));
            fb[sl] = lds128(fe_h[kk >> 3] + ((kk >> 2) & 1) * 4096 + ((((kk & 3) * 2 + 1) ^ (2 * q)) << 4));
            gg[sl] = lds128(ge_h[kk >> 3] + (kk & 7) * 16);
          }
        }
      }
      asm volatile("barrier.cluster.arrive.relaxed.aligned;" ::: "memory");
#pragma unroll
      for (int kk = 0; kk < 16; kk++) {
        if ((kk & 3) == 0) { mbar_wait(bars + (kBarW + 28 + (kk >> 2)) * 8); wg_fence(); }
        wgmma_rs_n64(acc[0], A[4 * kk], A[4 * kk + 1], A[4 * kk + 2], A[4 * kk + 3],
                     desc_at(dB, unit_slot(28 + (kk >> 2)) * kSlot + (kk & 3) * 2048), kk != 0);
        if (kk == 3) bar_arrive_pred4(wg == 0);
      }
      wg_commit();
      wg_wait<0>();
#pragma unroll
      for (int jb = 0; jb < 8; jb += 2) {
        const uint32_t r0_ = pack_bf16(acc[0][4 * jb + 0], acc[0][4 * jb + 1]), r1_ = pack_bf16(acc[0][4 * jb + 2], acc[0][4 * jb + 3]);
        const uint32_t r2_ = pack_bf16(acc[0][4 * jb + 4], acc[0][4 * jb + 5]), r3_ = pack_bf16(acc[0][4 * jb + 6], acc[0][4 * jb + 7]);
        stsm_x4(st + (wg ? stage_off(1, 0) : stage_off(0, 0)) + (((jb + (mi >> 1)) ^ l8) << 4), r0_, r1_, r2_, r3_);
      }
      fence_async_smem();
      __syncwarp();
      mbar_arrive_pred(bars + (kBarPR + wg * 4) * 8, lane == 0);
      if (w == 0) TS(wg, 11);
#pragma unroll
      for (int j = 0; j < 4; j++) {
        const int jn = j + 1;
        if (jn == 2) {
#pragma unroll
          for (int i = 0; i < 4; i++) mbar_wait(bars + (kBarW + 32 + i) * 8);
        }
        if (j < 3) wg_fence();
        const uint32_t stj = st + (wg ? stage_off(1, j) : stage_off(0, j));
#pragma unroll
        for (int kk = 0; kk < 16; kk++) {
          if (j < 3)
            wgmma_rs_n64(acc[jn & 1], A[4 * kk], A[4 * kk + 1], A[4 * kk + 2], A[4 * kk + 3],
                         desc_at(dB, unit_slot(28 + (jn >> 1) * 4 + (kk >> 2)) * kSlot + (jn & 1) * 8192 + (kk & 3) * 2048), kk != 0);
          if (kk == 1 && j > 0) {
            if (j < 3) { wg_commit(); wg_wait<1>(); } else { wg_wait<0>(); }
          }
          if (j > 0 && kk >= 2 && kk < 10 && (kk & 1) == 0) {
            const int jb = kk - 2;
            const uint32_t r0_ = pack_bf16(acc[j & 1][4 * jb + 0], acc[j & 1][4 * jb + 1]), r1_ = pack_bf16(acc[j & 1][4 * jb + 2], acc[j & 1][4 * jb + 3]);
            const uint32_t r2_ = pack_bf16(acc[j & 1][4 * jb + 4], acc[j & 1][4 * jb + 5]), r3_ = pack_bf16(acc[j & 1][4 * jb + 6], acc[j & 1][4 * jb + 7]);
            stsm_x4(stj + (((jb + (mi >> 1)) ^ l8) << 4), r0_, r1_, r2_, r3_);
          }
          if (j > 0 && kk == 9) {
            fence_async_smem();
            __syncwarp();
            mbar_arrive_pred(bars + (kBarPR + wg * 4 + j) * 8, lane == 0);
          }
        }
        if (j < 3) wg_commit();
        if (j == 0 && w == 0) TS(wg, 12);
        if (j == 2 && w == 0) TS(wg, 13);
      }
      if (w == 0) TS(wg, 14);
    } else {
      if (wg == 0) asm volatile("bar.arrive 4, 256;" ::: "memory");
      mbar_wait_cluster(bars + kBarFE * 8);
      asm volatile("barrier.cluster.arrive.relaxed.aligned;" ::: "memory");
    }
    asm volatile("barrier.cluster.wait.aligned;" ::: "memory");
    if (w == 0) TS_DUMP(wg, 0, 16);
  }
}

typedef CUresult (*EncodeFn)(CUtensorMap*, CUtensorMapDataType, cuuint32_t, void*, const cuuint64_t*, const cuuint64_t*,
                             const cuuint32_t*, const cuuint32_t*, CUtensorMapInterleave, CUtensorMapSwizzle,
                             CUtensorMapL2promotion, CUtensorMapFloatOOBfill);

void make_map3(EncodeFn enc, CUtensorMap* tm, const void* ptr, uint64_t rows, uint32_t box_rows, uint32_t box_panels) {
  cuuint64_t gd[3] = {64, rows, 4};
  cuuint64_t gs[2] = {512, 128};
  cuuint32_t bd[3] = {64, box_rows, box_panels};
  cuuint32_t es[3] = {1, 1, 1};
  enc(tm, CU_TENSOR_MAP_DATA_TYPE_BFLOAT16, 3, const_cast<void*>(ptr), gd, gs, bd, es, CU_TENSOR_MAP_INTERLEAVE_NONE,
      CU_TENSOR_MAP_SWIZZLE_128B, CU_TENSOR_MAP_L2_PROMOTION_L2_256B, CU_TENSOR_MAP_FLOAT_OOB_FILL_NONE);
}

}

extern "C" void kernel_launch(void* const* d_in, const int* in_sizes, int n_in, void* d_out, int out_size) {
  static EncodeFn enc = nullptr;
  if (!enc) {
    cudaDriverEntryPointQueryResult qr;
    cudaGetDriverEntryPoint("cuTensorMapEncodeTiled", (void**)&enc, cudaEnableDefault, &qr);
    cudaFuncSetAttribute(rnnt_joint_kernel, cudaFuncAttributeMaxDynamicSharedMemorySize, kSmemBytes);
  }
  Params P;
  {
    cuuint64_t gd[4] = {256, 2, 2000, 2};
    cuuint64_t gs[3] = {512, 1024, 4000ull * 512};
    cuuint32_t bd[4] = {64, 1, 64, 1};
    cuuint32_t es[4] = {1, 1, 1, 1};
    enc(&P.x, CU_TENSOR_MAP_DATA_TYPE_BFLOAT16, 4, d_in[0], gd, gs, bd, es, CU_TENSOR_MAP_INTERLEAVE_NONE,
        CU_TENSOR_MAP_SWIZZLE_128B, CU_TENSOR_MAP_L2_PROMOTION_L2_128B, CU_TENSOR_MAP_FLOAT_OOB_FILL_NONE);
  }
  make_map3(enc, &P.w1, d_in[1], 768, 64, 2);
  make_map3(enc, &P.w2, d_in[2], 768, 64, 2);
  make_map3(enc, &P.g, d_in[3], 16, 8, 4);
  make_map3(enc, &P.wf, d_in[4], 256, 64, 2);
  make_map3(enc, &P.wg, d_in[5], 256, 64, 2);
  make_map3(enc, &P.wo, d_in[6], 256, 64, 2);
  make_map3(enc, &P.out64, d_out, 16000, 64, 1);
  make_map3(enc, &P.out56, d_out, 16000, 56, 1);
  rnnt_joint_kernel<<<kNumCtas, kThreads, kSmemBytes>>>(P);
}
```
